```python
import torch

def _softmax(x, axis=-1):
    return torch.softmax(x, dim=axis)
def _gelu(x):
    return torch.nn.functional.gelu(x, approximate="tanh")
def _silu(x):
    return torch.nn.functional.silu(x)
def _sigmoid(x):
    return torch.sigmoid(x)
def _layernorm(x, axis=-1, eps=1e-5):
    m = x.mean(dim=axis, keepdim=True)
    v = x.var(dim=axis, keepdim=True, unbiased=False)
    return (x - m) / torch.sqrt(v + eps)
def _scatter_add(tgt, idx, src, axis=0):
    return tgt.clone().index_add_(axis, idx, src)
def _segment_sum(src, seg, n):
    out = torch.zeros((n,) + src.shape[1:], dtype=src.dtype)
    return out.index_add_(0, seg, src)
def _pad(x, pw):
    flat = tuple(v for pair in reversed(pw) for v in pair)
    return torch.nn.functional.pad(x, flat)

kernel_name = 'interleave_layers__sliding_local_dilated__moe_arch_mod__prompt'

def setup_inputs():

    _w = (lambda a: (lambda t: t.to(torch.bfloat16) if t.is_floating_point() else t)(torch.as_tensor(a)))
    def _A_setup():
        B, S, D = 1, 2048, 576
        return {
            "x": _w((lambda *s: torch.randn(*s, dtype=torch.bfloat16) * 0.05)(B, S, D)),
            "wqkv": _w((lambda *s: torch.randn(*s, dtype=torch.bfloat16) * 0.05)(D, 3 * D)),
            "wo": _w((lambda *s: torch.randn(*s, dtype=torch.bfloat16) * 0.05)(D, D)),
        }
    _A_in = _A_setup()

    def _B_setup():
        B, S, D, F, C = 1, 2048, 576, 4608, 1
        return {
            "x": _w((lambda *s: torch.randn(*s, dtype=torch.bfloat16) * 0.05)(B, S, D)),
            "w_r": _w((lambda *s: torch.randn(*s, dtype=torch.bfloat16) * 0.05)(D)),
            "w_gate": _w((lambda *s: torch.randn(*s, dtype=torch.bfloat16) * 0.05)(D, F)),
            "w_up": _w((lambda *s: torch.randn(*s, dtype=torch.bfloat16) * 0.05)(D, F)),
            "w_down": _w((lambda *s: torch.randn(*s, dtype=torch.bfloat16) * 0.05)(F, D)),
        }
    _B_in = _B_setup()

    return {
        "A_x": _A_in["x"],
        "A_wqkv": _A_in["wqkv"],
        "A_wo": _A_in["wo"],
        "B_x": _B_in["x"],
        "B_w_r": _B_in["w_r"],
        "B_w_gate": _B_in["w_gate"],
        "B_w_up": _B_in["w_up"],
        "B_w_down": _B_in["w_down"],
    }

def reference(A_x, A_wqkv, A_wo, B_x, B_w_r, B_w_gate, B_w_up, B_w_down):
    def _A_ref(x, wqkv, wo):
        B, S, D = x.shape
        H = 32; Dh = D // H
        W, dil = 8, 2
        qkv = (lambda x, *d: x.permute(*d))((x @ wqkv).reshape(B, S, 3, H, Dh), 2, 0, 3, 1, 4)
        q, k, v = qkv[0], qkv[1], qkv[2]
        scale = Dh ** -0.5
        pos = torch.arange(S)
        off = torch.arange(W) * dil
        idx = pos[:, None] - off[None, :]
        mask = idx >= 0
        idx_c = torch.where(mask, idx, 0).reshape(-1)
        kg = k[:, :, idx_c, :].reshape(B, H, S, W, Dh)
        vg = v[:, :, idx_c, :].reshape(B, H, S, W, Dh)
        logits = torch.einsum("bhsd,bhswd->bhsw", q, kg) * scale
        logits = torch.where(mask[None, None, :, :], logits, -1e9)
        attn = _softmax(logits, axis=-1)
        o = torch.einsum("bhsw,bhswd->bhsd", attn, vg)
        return (lambda x, *d: x.permute(*d))(o, 0, 2, 1, 3).reshape(B, S, D) @ wo

    def _B_ref(x, w_r, w_gate, w_up, w_down):
        B, S, D = x.shape
        C = 1
        r = x @ w_r
        idx = torch.argsort(-r, axis=-1)[:, :C]
        idx_e = (lambda x, n, axis: torch.repeat_interleave(x, n, dim=axis))(idx.reshape(B, C, 1), D, axis=2)
        x_sel = (lambda x, i, axis: torch.take_along_dim(x, i, dim=axis))(x, idx_e, axis=1)
        g = _silu(x_sel @ w_gate)
        u = x_sel @ w_up
        y = (g * u) @ w_down
        r_sel = _sigmoid((lambda x, i, axis: torch.take_along_dim(x, i, dim=axis))(r, idx, axis=1))
        y = y * r_sel.reshape(B, C, 1)
        b_off = (torch.arange(B) * S).reshape(B, 1)
        flat_idx = (idx + b_off).reshape(B * C)
        zero = (x * 0.0).reshape(B * S, D)
        upd = _scatter_add(zero, flat_idx, y.reshape(B * C, D), axis=0)
        return x + upd.reshape(B, S, D)

    x = A_x
    x = x + _A_ref(_layernorm(x, axis=-1), A_wqkv, A_wo)
    x = x + _B_ref(_layernorm(x, axis=-1), B_w_r, B_w_gate, B_w_up, B_w_down)
    x = x + _A_ref(_layernorm(x, axis=-1), A_wqkv, A_wo)
    x = x + _B_ref(_layernorm(x, axis=-1), B_w_r, B_w_gate, B_w_up, B_w_down)
    return x
```

```cpp
#include <cuda_runtime.h>
#include <cuda_bf16.h>
#include <cuda.h>
#include <stdint.h>
#include <stddef.h>

#define DEVI __device__ __forceinline__

namespace {

constexpr int kD = 576, kF = 4608;
constexpr uint32_t WSTAGE = 27648, XSTAGE = 8192;
constexpr float kEps = 1e-5f;

constexpr uint32_t WDP = 1168;
constexpr uint32_t SM_W = 0;
constexpr uint32_t SM_X = 110592;
constexpr uint32_t SM_WD = 176128;
constexpr uint32_t SM_LEFT = SM_WD + 36 * WDP;
constexpr uint32_t SM_COLSUM = SM_LEFT + 9216;
constexpr uint32_t SM_ROWC = SM_COLSUM + 960;
constexpr uint32_t SM_ROWM = SM_ROWC + 512;
constexpr uint32_t SM_PART = SM_ROWM + 1024;
constexpr uint32_t SM_FIXQ = SM_PART;
constexpr uint32_t SM_X2R = SM_PART + 864;
constexpr uint32_t SM_H = SM_PART + 1152;
constexpr uint32_t SM_GEMV = SM_H;
constexpr uint32_t SM_RED = SM_H + 320;
constexpr uint32_t SM_SEL = SM_RED + 256;
constexpr uint32_t SM_EP = SM_SEL + 8, SM_WSUM = SM_SEL + 12;
constexpr uint32_t SM_BAR = SM_SEL + 16;
constexpr uint32_t B_WFULL = SM_BAR, B_WEMPTY = B_WFULL + 32, B_XFULL = B_WEMPTY + 32, B_XEMPTY = B_XFULL + 64;
constexpr uint32_t B_RC = B_XEMPTY + 64;
constexpr uint32_t B_COLSUM = B_RC + 16, B_PKF = B_COLSUM + 8, B_FIX = B_PKF + 8, B_DONE = B_FIX + 8;
constexpr uint32_t B_FF = B_DONE + 8;
constexpr uint32_t B_IDX = B_FF + 24;
constexpr uint32_t B_WD = B_IDX + 16, B_WANT = B_WD + 8, B_EPI = B_WANT + 8, B_EP = B_EPI + 8, B_OS = B_EP + 8, B_FD = B_OS + 8;
constexpr uint32_t B_WL = B_FD + 8;
constexpr uint32_t B_RES = B_WL + 32;
constexpr uint32_t SM_TOTAL = B_RES + 16;
constexpr int NBAR = (SM_TOTAL - SM_BAR) / 8, NBAR4 = (B_FF - SM_BAR) / 8;
constexpr uint32_t FSLOT = 16384;
static_assert(SM_TOTAL + 256 <= 232448, "smem");

struct __align__(1024) Checked {
  uint32_t candrow[2][128][288];
  uint4 halo[128][2][2][5][32];
  uint8_t wpack[8][12 * WSTAGE];
  uint8_t act[3][16][2][73728];
};
struct __align__(1024) Scratch {
  uint4 cand[2][8][128];
  uint4 ypart[72][128][2];
  uint32_t x2msg[8][576];
  uint32_t fixmsg[8][256];
  uint32_t flagP[8][12][32];
  uint32_t flagX[16][2][32];
  uint32_t epoch[128][8];
  uint4 stats0[16][2][64];
  uint4 statsP[16][2][8][64];
  float colpart[8][8][216];
  Checked chk[2];
};
__device__ Scratch g_s;
#define GA(member, off) (gb + offsetof(Scratch, member) + (uint32_t)(off))
#define GC(member, off) (gb + offsetof(Scratch, chk) + offsetof(Checked, member) + (uint32_t)((off) + (epoch & 1) * (uint32_t)sizeof(Checked)))
constexpr uint32_t ACT = 16 * 2 * 73728;

#define TR(role, i)
#define TRL(role, i)
#define TRDUMP(role)
#define TRW(i)
#define TRZ(i)
#define TRQ(i)

__device__ __forceinline__ void wgmma_n144(float* d, uint32_t alo, uint32_t ahi, uint32_t blo) {
  asm volatile("{\n.reg .b64 da, db;\nmov.b64 da, {%72, %73};\nmov.b64 db, {%74, 8};\n"
    "wgmma.mma_async.sync.aligned.m64n144k16.f32.bf16.bf16 "
    "{%0, %1, %2, %3, %4, %5, %6, %7, %8, %9, %10, %11, %12, %13, %14, %15, %16, %17, %18, %19, %20, %21, %22, %23, %24, %25, %26, %27, %28, %29, %30, %31, %32, %33, %34, %35, %36, %37, %38, %39, %40, %41, %42, %43, %44, %45, %46, %47, %48, %49, %50, %51, %52, %53, %54, %55, %56, %57, %58, %59, %60, %61, %62, %63, %64, %65, %66, %67, %68, %69, %70, %71}, da, db, 1, 1, 1, 0, 1;\n}\n"
    : "+f"(d[0]), "+f"(d[1]), "+f"(d[2]), "+f"(d[3]), "+f"(d[4]), "+f"(d[5]), "+f"(d[6]), "+f"(d[7]), "+f"(d[8]),
      "+f"(d[9]), "+f"(d[10]), "+f"(d[11]), "+f"(d[12]), "+f"(d[13]), "+f"(d[14]), "+f"(d[15]), "+f"(d[16]), "+f"(d[17]),
      "+f"(d[18]), "+f"(d[19]), "+f"(d[20]), "+f"(d[21]), "+f"(d[22]), "+f"(d[23]), "+f"(d[24]), "+f"(d[25]), "+f"(d[26]),
      "+f"(d[27]), "+f"(d[28]), "+f"(d[29]), "+f"(d[30]), "+f"(d[31]), "+f"(d[32]), "+f"(d[33]), "+f"(d[34]), "+f"(d[35]),
      "+f"(d[36]), "+f"(d[37]), "+f"(d[38]), "+f"(d[39]), "+f"(d[40]), "+f"(d[41]), "+f"(d[42]), "+f"(d[43]), "+f"(d[44]),
      "+f"(d[45]), "+f"(d[46]), "+f"(d[47]), "+f"(d[48]), "+f"(d[49]), "+f"(d[50]), "+f"(d[51]), "+f"(d[52]), "+f"(d[53]),
      "+f"(d[54]), "+f"(d[55]), "+f"(d[56]), "+f"(d[57]), "+f"(d[58]), "+f"(d[59]), "+f"(d[60]), "+f"(d[61]), "+f"(d[62]),
      "+f"(d[63]), "+f"(d[64]), "+f"(d[65]), "+f"(d[66]), "+f"(d[67]), "+f"(d[68]), "+f"(d[69]), "+f"(d[70]), "+f"(d[71])
    : "r"(alo), "r"(ahi), "r"(blo));
}
__device__ __forceinline__ void wgmma_n144_set(float* d, const uint32_t* a, uint32_t blo) {
  asm volatile("{\n.reg .b64 db;\nmov.b64 db, {%76, 2};\n"
    "wgmma.mma_async.sync.aligned.m64n144k16.f32.bf16.bf16 "
    "{%0, %1, %2, %3, %4, %5, %6, %7, %8, %9, %10, %11, %12, %13, %14, %15, %16, %17, %18, %19, %20, %21, %22, %23, %24, %25, %26, %27, %28, %29, %30, %31, %32, %33, %34, %35, %36, %37, %38, %39, %40, %41, %42, %43, %44, %45, %46, %47, %48, %49, %50, %51, %52, %53, %54, %55, %56, %57, %58, %59, %60, %61, %62, %63, %64, %65, %66, %67, %68, %69, %70, %71}, {%72, %73, %74, %75}, db, 0, -1, 1, 1;\n}\n"
    : "=f"(d[0]), "=f"(d[1]), "=f"(d[2]), "=f"(d[3]), "=f"(d[4]), "=f"(d[5]), "=f"(d[6]), "=f"(d[7]), "=f"(d[8]),
      "=f"(d[9]), "=f"(d[10]), "=f"(d[11]), "=f"(d[12]), "=f"(d[13]), "=f"(d[14]), "=f"(d[15]), "=f"(d[16]), "=f"(d[17]),
      "=f"(d[18]), "=f"(d[19]), "=f"(d[20]), "=f"(d[21]), "=f"(d[22]), "=f"(d[23]), "=f"(d[24]), "=f"(d[25]), "=f"(d[26]),
      "=f"(d[27]), "=f"(d[28]), "=f"(d[29]), "=f"(d[30]), "=f"(d[31]), "=f"(d[32]), "=f"(d[33]), "=f"(d[34]), "=f"(d[35]),
      "=f"(d[36]), "=f"(d[37]), "=f"(d[38]), "=f"(d[39]), "=f"(d[40]), "=f"(d[41]), "=f"(d[42]), "=f"(d[43]), "=f"(d[44]),
      "=f"(d[45]), "=f"(d[46]), "=f"(d[47]), "=f"(d[48]), "=f"(d[49]), "=f"(d[50]), "=f"(d[51]), "=f"(d[52]), "=f"(d[53]),
      "=f"(d[54]), "=f"(d[55]), "=f"(d[56]), "=f"(d[57]), "=f"(d[58]), "=f"(d[59]), "=f"(d[60]), "=f"(d[61]), "=f"(d[62]),
      "=f"(d[63]), "=f"(d[64]), "=f"(d[65]), "=f"(d[66]), "=f"(d[67]), "=f"(d[68]), "=f"(d[69]), "=f"(d[70]), "=f"(d[71])
    : "r"(a[0]), "r"(a[1]), "r"(a[2]), "r"(a[3]), "r"(blo));
}
__device__ __forceinline__ void wgmma_n144_add(float* d, const uint32_t* a, uint32_t blo) {
  asm volatile("{\n.reg .b64 db;\nmov.b64 db, {%76, 2};\n"
    "wgmma.mma_async.sync.aligned.m64n144k16.f32.bf16.bf16 "
    "{%0, %1, %2, %3, %4, %5, %6, %7, %8, %9, %10, %11, %12, %13, %14, %15, %16, %17, %18, %19, %20, %21, %22, %23, %24, %25, %26, %27, %28, %29, %30, %31, %32, %33, %34, %35, %36, %37, %38, %39, %40, %41, %42, %43, %44, %45, %46, %47, %48, %49, %50, %51, %52, %53, %54, %55, %56, %57, %58, %59, %60, %61, %62, %63, %64, %65, %66, %67, %68, %69, %70, %71}, {%72, %73, %74, %75}, db, 1, -1, 1, 1;\n}\n"
    : "+f"(d[0]), "+f"(d[1]), "+f"(d[2]), "+f"(d[3]), "+f"(d[4]), "+f"(d[5]), "+f"(d[6]), "+f"(d[7]), "+f"(d[8]),
      "+f"(d[9]), "+f"(d[10]), "+f"(d[11]), "+f"(d[12]), "+f"(d[13]), "+f"(d[14]), "+f"(d[15]), "+f"(d[16]), "+f"(d[17]),
      "+f"(d[18]), "+f"(d[19]), "+f"(d[20]), "+f"(d[21]), "+f"(d[22]), "+f"(d[23]), "+f"(d[24]), "+f"(d[25]), "+f"(d[26]),
      "+f"(d[27]), "+f"(d[28]), "+f"(d[29]), "+f"(d[30]), "+f"(d[31]), "+f"(d[32]), "+f"(d[33]), "+f"(d[34]), "+f"(d[35]),
      "+f"(d[36]), "+f"(d[37]), "+f"(d[38]), "+f"(d[39]), "+f"(d[40]), "+f"(d[41]), "+f"(d[42]), "+f"(d[43]), "+f"(d[44]),
      "+f"(d[45]), "+f"(d[46]), "+f"(d[47]), "+f"(d[48]), "+f"(d[49]), "+f"(d[50]), "+f"(d[51]), "+f"(d[52]), "+f"(d[53]),
      "+f"(d[54]), "+f"(d[55]), "+f"(d[56]), "+f"(d[57]), "+f"(d[58]), "+f"(d[59]), "+f"(d[60]), "+f"(d[61]), "+f"(d[62]),
      "+f"(d[63]), "+f"(d[64]), "+f"(d[65]), "+f"(d[66]), "+f"(d[67]), "+f"(d[68]), "+f"(d[69]), "+f"(d[70]), "+f"(d[71])
    : "r"(a[0]), "r"(a[1]), "r"(a[2]), "r"(a[3]), "r"(blo));
}
__device__ __forceinline__ void wgmma_n72(float* d, uint32_t alo, uint32_t ahi, uint32_t blo) {
  asm volatile("{\n.reg .b64 da, db;\nmov.b64 da, {%36, %37};\nmov.b64 db, {%38, 8};\n"
    "wgmma.mma_async.sync.aligned.m64n72k16.f32.bf16.bf16 "
    "{%0, %1, %2, %3, %4, %5, %6, %7, %8, %9, %10, %11, %12, %13, %14, %15, %16, %17, %18, %19, %20, %21, %22, %23, %24, %25, %26, %27, %28, %29, %30, %31, %32, %33, %34, %35}, da, db, 1, 1, 1, 0, 1;\n}\n"
    : "+f"(d[0]), "+f"(d[1]), "+f"(d[2]), "+f"(d[3]), "+f"(d[4]), "+f"(d[5]), "+f"(d[6]), "+f"(d[7]), "+f"(d[8]),
      "+f"(d[9]), "+f"(d[10]), "+f"(d[11]), "+f"(d[12]), "+f"(d[13]), "+f"(d[14]), "+f"(d[15]), "+f"(d[16]), "+f"(d[17]),
      "+f"(d[18]), "+f"(d[19]), "+f"(d[20]), "+f"(d[21]), "+f"(d[22]), "+f"(d[23]), "+f"(d[24]), "+f"(d[25]), "+f"(d[26]),
      "+f"(d[27]), "+f"(d[28]), "+f"(d[29]), "+f"(d[30]), "+f"(d[31]), "+f"(d[32]), "+f"(d[33]), "+f"(d[34]), "+f"(d[35])
    : "r"(alo), "r"(ahi), "r"(blo));
}
__device__ __forceinline__ void wgmma_n72_set(float* d, const uint32_t* a, uint32_t blo) {
  asm volatile("{\n.reg .b64 db;\nmov.b64 db, {%40, 2};\n"
    "wgmma.mma_async.sync.aligned.m64n72k16.f32.bf16.bf16 "
    "{%0, %1, %2, %3, %4, %5, %6, %7, %8, %9, %10, %11, %12, %13, %14, %15, %16, %17, %18, %19, %20, %21, %22, %23, %24, %25, %26, %27, %28, %29, %30, %31, %32, %33, %34, %35}, {%36, %37, %38, %39}, db, 0, -1, 1, 1;\n}\n"
    : "=f"(d[0]), "=f"(d[1]), "=f"(d[2]), "=f"(d[3]), "=f"(d[4]), "=f"(d[5]), "=f"(d[6]), "=f"(d[7]), "=f"(d[8]),
      "=f"(d[9]), "=f"(d[10]), "=f"(d[11]), "=f"(d[12]), "=f"(d[13]), "=f"(d[14]), "=f"(d[15]), "=f"(d[16]), "=f"(d[17]),
      "=f"(d[18]), "=f"(d[19]), "=f"(d[20]), "=f"(d[21]), "=f"(d[22]), "=f"(d[23]), "=f"(d[24]), "=f"(d[25]), "=f"(d[26]),
      "=f"(d[27]), "=f"(d[28]), "=f"(d[29]), "=f"(d[30]), "=f"(d[31]), "=f"(d[32]), "=f"(d[33]), "=f"(d[34]), "=f"(d[35])
    : "r"(a[0]), "r"(a[1]), "r"(a[2]), "r"(a[3]), "r"(blo));
}
__device__ __forceinline__ void wgmma_n72_add(float* d, const uint32_t* a, uint32_t blo) {
  asm volatile("{\n.reg .b64 db;\nmov.b64 db, {%40, 2};\n"
    "wgmma.mma_async.sync.aligned.m64n72k16.f32.bf16.bf16 "
    "{%0, %1, %2, %3, %4, %5, %6, %7, %8, %9, %10, %11, %12, %13, %14, %15, %16, %17, %18, %19, %20, %21, %22, %23, %24, %25, %26, %27, %28, %29, %30, %31, %32, %33, %34, %35}, {%36, %37, %38, %39}, db, 1, -1, 1, 1;\n}\n"
    : "+f"(d[0]), "+f"(d[1]), "+f"(d[2]), "+f"(d[3]), "+f"(d[4]), "+f"(d[5]), "+f"(d[6]), "+f"(d[7]), "+f"(d[8]),
      "+f"(d[9]), "+f"(d[10]), "+f"(d[11]), "+f"(d[12]), "+f"(d[13]), "+f"(d[14]), "+f"(d[15]), "+f"(d[16]), "+f"(d[17]),
      "+f"(d[18]), "+f"(d[19]), "+f"(d[20]), "+f"(d[21]), "+f"(d[22]), "+f"(d[23]), "+f"(d[24]), "+f"(d[25]), "+f"(d[26]),
      "+f"(d[27]), "+f"(d[28]), "+f"(d[29]), "+f"(d[30]), "+f"(d[31]), "+f"(d[32]), "+f"(d[33]), "+f"(d[34]), "+f"(d[35])
    : "r"(a[0]), "r"(a[1]), "r"(a[2]), "r"(a[3]), "r"(blo));
}
__device__ __forceinline__ void q_tail(float* d, uint32_t* v, uint32_t ahi, const uint32_t* dsc, const uint32_t* bar, const uint32_t* adr) {
  asm volatile(
    "{\n.reg .pred p<2>, q;\n.reg .b64 da, db;\n.reg .u32 n;\n"
    "mbarrier.test_wait.parity.shared::cta.b64 p0, [%116], %117;\n"
    "mbarrier.test_wait.parity.shared::cta.b64 p1, [%118], %119;\n"
    "ld.volatile.shared.u32 %108, [%120];\n"
    "mov.b64 da, {%110, %109};\nmov.b64 db, {%111, 8};\n"
    "wgmma.mma_async.sync.aligned.m64n144k16.f32.bf16.bf16 {%36, %37, %38, %39, %40, %41, %42, %43, %44, %45, %46, %47, %48, %49, %50, %51, %52, %53, %54, %55, %56, %57, %58, %59, %60, %61, %62, %63, %64, %65, %66, %67, %68, %69, %70, %71, %72, %73, %74, %75, %76, %77, %78, %79, %80, %81, %82, %83, %84, %85, %86, %87, %88, %89, %90, %91, %92, %93, %94, %95, %96, %97, %98, %99, %100, %101, %102, %103, %104, %105, %106, %107}, da, db, 1, 1, 1, 0, 1;\n"
    "mov.b64 da, {%112, %109};\nmov.b64 db, {%113, 8};\n"
    "wgmma.mma_async.sync.aligned.m64n72k16.f32.bf16.bf16 {%0, %1, %2, %3, %4, %5, %6, %7, %8, %9, %10, %11, %12, %13, %14, %15, %16, %17, %18, %19, %20, %21, %22, %23, %24, %25, %26, %27, %28, %29, %30, %31, %32, %33, %34, %35}, da, db, 1, 1, 1, 0, 1;\n"
    "mov.b64 da, {%114, %109};\nmov.b64 db, {%115, 8};\n"
    "wgmma.mma_async.sync.aligned.m64n144k16.f32.bf16.bf16 {%36, %37, %38, %39, %40, %41, %42, %43, %44, %45, %46, %47, %48, %49, %50, %51, %52, %53, %54, %55, %56, %57, %58, %59, %60, %61, %62, %63, %64, %65, %66, %67, %68, %69, %70, %71, %72, %73, %74, %75, %76, %77, %78, %79, %80, %81, %82, %83, %84, %85, %86, %87, %88, %89, %90, %91, %92, %93, %94, %95, %96, %97, %98, %99, %100, %101, %102, %103, %104, %105, %106, %107}, da, db, 1, 1, 1, 0, 1;\n"
    "wgmma.commit_group.sync.aligned;\n"
    "@p0 bra.uni D0;\nmov.u32 n, 0;\nW0:\nmbarrier.try_wait.parity.shared::cta.b64 q, [%116], %117;\n@q bra.uni R0;\nadd.u32 n, n, 1;\nsetp.lt.u32 q, n, 8192;\n@q bra.uni W0;\nR0:\n"
    "D0:\n"
    "@p1 bra.uni D1;\nmov.u32 n, 0;\nW1:\nmbarrier.try_wait.parity.shared::cta.b64 q, [%118], %119;\n@q bra.uni R1;\nadd.u32 n, n, 1;\nsetp.lt.u32 q, n, 8192;\n@q bra.uni W1;\nR1:\n"
    "ld.volatile.shared.u32 %108, [%120];\n"
    "D1:\n"
    "}\n"
    : "+f"(d[0]), "+f"(d[1]), "+f"(d[2]), "+f"(d[3]), "+f"(d[4]), "+f"(d[5]), "+f"(d[6]), "+f"(d[7]), "+f"(d[8]),
      "+f"(d[9]), "+f"(d[10]), "+f"(d[11]), "+f"(d[12]), "+f"(d[13]), "+f"(d[14]), "+f"(d[15]), "+f"(d[16]), "+f"(d[17]),
      "+f"(d[18]), "+f"(d[19]), "+f"(d[20]), "+f"(d[21]), "+f"(d[22]), "+f"(d[23]), "+f"(d[24]), "+f"(d[25]), "+f"(d[26]),
      "+f"(d[27]), "+f"(d[28]), "+f"(d[29]), "+f"(d[30]), "+f"(d[31]), "+f"(d[32]), "+f"(d[33]), "+f"(d[34]), "+f"(d[35]),
      "+f"(d[36]), "+f"(d[37]), "+f"(d[38]), "+f"(d[39]), "+f"(d[40]), "+f"(d[41]), "+f"(d[42]), "+f"(d[43]), "+f"(d[44]),
      "+f"(d[45]), "+f"(d[46]), "+f"(d[47]), "+f"(d[48]), "+f"(d[49]), "+f"(d[50]), "+f"(d[51]), "+f"(d[52]), "+f"(d[53]),
      "+f"(d[54]), "+f"(d[55]), "+f"(d[56]), "+f"(d[57]), "+f"(d[58]), "+f"(d[59]), "+f"(d[60]), "+f"(d[61]), "+f"(d[62]),
      "+f"(d[63]), "+f"(d[64]), "+f"(d[65]), "+f"(d[66]), "+f"(d[67]), "+f"(d[68]), "+f"(d[69]), "+f"(d[70]), "+f"(d[71]),
      "+f"(d[72]), "+f"(d[73]), "+f"(d[74]), "+f"(d[75]), "+f"(d[76]), "+f"(d[77]), "+f"(d[78]), "+f"(d[79]), "+f"(d[80]),
      "+f"(d[81]), "+f"(d[82]), "+f"(d[83]), "+f"(d[84]), "+f"(d[85]), "+f"(d[86]), "+f"(d[87]), "+f"(d[88]), "+f"(d[89]),
      "+f"(d[90]), "+f"(d[91]), "+f"(d[92]), "+f"(d[93]), "+f"(d[94]), "+f"(d[95]), "+f"(d[96]), "+f"(d[97]), "+f"(d[98]),
      "+f"(d[99]), "+f"(d[100]), "+f"(d[101]), "+f"(d[102]), "+f"(d[103]), "+f"(d[104]), "+f"(d[105]), "+f"(d[106]), "+f"(d[107]),
      "=&r"(v[0])
    : "r"(ahi), "r"(dsc[0]), "r"(dsc[1]), "r"(dsc[2]), "r"(dsc[3]), "r"(dsc[4]), "r"(dsc[5]), "r"(bar[0]), "r"(bar[1]), "r"(bar[2]), "r"(bar[3]), "r"(adr[0]) : "memory");
}
__device__ __forceinline__ void kv_tail(float* d, uint32_t* v, uint32_t ahi, const uint32_t* dsc, const uint32_t* bar, const uint32_t* adr) {
  asm volatile(
    "{\n.reg .pred p<3>, q;\n.reg .b64 da, db;\n.reg .u32 n;\n"
    "mbarrier.test_wait.parity.shared::cta.b64 p0, [%79], %80;\n"
    "mbarrier.test_wait.parity.shared::cta.b64 p1, [%81], %82;\n"
    "mbarrier.test_wait.parity.shared::cta.b64 p2, [%83], %84;\n"
    "ld.volatile.shared.u32 %72, [%85];\n"
    "ld.volatile.shared.u32 %73, [%86];\n"
    "mov.b64 da, {%75, %74};\nmov.b64 db, {%76, 8};\n"
    "wgmma.mma_async.sync.aligned.m64n144k16.f32.bf16.bf16 {%0, %1, %2, %3, %4, %5, %6, %7, %8, %9, %10, %11, %12, %13, %14, %15, %16, %17, %18, %19, %20, %21, %22, %23, %24, %25, %26, %27, %28, %29, %30, %31, %32, %33, %34, %35, %36, %37, %38, %39, %40, %41, %42, %43, %44, %45, %46, %47, %48, %49, %50, %51, %52, %53, %54, %55, %56, %57, %58, %59, %60, %61, %62, %63, %64, %65, %66, %67, %68, %69, %70, %71}, da, db, 1, 1, 1, 0, 1;\n"
    "mov.b64 da, {%77, %74};\nmov.b64 db, {%78, 8};\n"
    "wgmma.mma_async.sync.aligned.m64n144k16.f32.bf16.bf16 {%0, %1, %2, %3, %4, %5, %6, %7, %8, %9, %10, %11, %12, %13, %14, %15, %16, %17, %18, %19, %20, %21, %22, %23, %24, %25, %26, %27, %28, %29, %30, %31, %32, %33, %34, %35, %36, %37, %38, %39, %40, %41, %42, %43, %44, %45, %46, %47, %48, %49, %50, %51, %52, %53, %54, %55, %56, %57, %58, %59, %60, %61, %62, %63, %64, %65, %66, %67, %68, %69, %70, %71}, da, db, 1, 1, 1, 0, 1;\n"
    "wgmma.commit_group.sync.aligned;\n"
    "@p0 bra.uni D0;\nmov.u32 n, 0;\nW0:\nmbarrier.try_wait.parity.shared::cta.b64 q, [%79], %80;\n@q bra.uni R0;\nadd.u32 n, n, 1;\nsetp.lt.u32 q, n, 8192;\n@q bra.uni W0;\nR0:\n"
    "D0:\n"
    "@p1 bra.uni D1;\nmov.u32 n, 0;\nW1:\nmbarrier.try_wait.parity.shared::cta.b64 q, [%81], %82;\n@q bra.uni R1;\nadd.u32 n, n, 1;\nsetp.lt.u32 q, n, 8192;\n@q bra.uni W1;\nR1:\n"
    "ld.volatile.shared.u32 %72, [%85];\n"
    "D1:\n"
    "@p2 bra.uni D2;\nmov.u32 n, 0;\nW2:\nmbarrier.try_wait.parity.shared::cta.b64 q, [%83], %84;\n@q bra.uni R2;\nadd.u32 n, n, 1;\nsetp.lt.u32 q, n, 8192;\n@q bra.uni W2;\nR2:\n"
    "ld.volatile.shared.u32 %73, [%86];\n"
    "D2:\n"
    "}\n"
    : "+f"(d[36]), "+f"(d[37]), "+f"(d[38]), "+f"(d[39]), "+f"(d[40]), "+f"(d[41]), "+f"(d[42]), "+f"(d[43]), "+f"(d[44]),
      "+f"(d[45]), "+f"(d[46]), "+f"(d[47]), "+f"(d[48]), "+f"(d[49]), "+f"(d[50]), "+f"(d[51]), "+f"(d[52]), "+f"(d[53]),
      "+f"(d[54]), "+f"(d[55]), "+f"(d[56]), "+f"(d[57]), "+f"(d[58]), "+f"(d[59]), "+f"(d[60]), "+f"(d[61]), "+f"(d[62]),
      "+f"(d[63]), "+f"(d[64]), "+f"(d[65]), "+f"(d[66]), "+f"(d[67]), "+f"(d[68]), "+f"(d[69]), "+f"(d[70]), "+f"(d[71]),
      "+f"(d[72]), "+f"(d[73]), "+f"(d[74]), "+f"(d[75]), "+f"(d[76]), "+f"(d[77]), "+f"(d[78]), "+f"(d[79]), "+f"(d[80]),
      "+f"(d[81]), "+f"(d[82]), "+f"(d[83]), "+f"(d[84]), "+f"(d[85]), "+f"(d[86]), "+f"(d[87]), "+f"(d[88]), "+f"(d[89]),
      "+f"(d[90]), "+f"(d[91]), "+f"(d[92]), "+f"(d[93]), "+f"(d[94]), "+f"(d[95]), "+f"(d[96]), "+f"(d[97]), "+f"(d[98]),
      "+f"(d[99]), "+f"(d[100]), "+f"(d[101]), "+f"(d[102]), "+f"(d[103]), "+f"(d[104]), "+f"(d[105]), "+f"(d[106]), "+f"(d[107]),
      "=&r"(v[0]), "=&r"(v[1])
    : "r"(ahi), "r"(dsc[0]), "r"(dsc[1]), "r"(dsc[2]), "r"(dsc[3]), "r"(bar[0]), "r"(bar[1]), "r"(bar[2]), "r"(bar[3]), "r"(bar[4]), "r"(bar[5]), "r"(adr[0]), "r"(adr[1]) : "memory");
}
__device__ __forceinline__ void kv_last(float* d, uint32_t* v, uint32_t ahi, const uint32_t* dsc, const uint32_t* bar, const uint32_t* adr) {
  asm volatile(
    "{\n.reg .pred p<1>, q;\n.reg .b64 da, db;\n.reg .u32 n;\n"
    "mbarrier.test_wait.parity.shared::cta.b64 p0, [%81], %82;\n"
    "mov.b64 da, {%73, %72};\nmov.b64 db, {%74, 8};\n"
    "wgmma.mma_async.sync.aligned.m64n144k16.f32.bf16.bf16 {%0, %1, %2, %3, %4, %5, %6, %7, %8, %9, %10, %11, %12, %13, %14, %15, %16, %17, %18, %19, %20, %21, %22, %23, %24, %25, %26, %27, %28, %29, %30, %31, %32, %33, %34, %35, %36, %37, %38, %39, %40, %41, %42, %43, %44, %45, %46, %47, %48, %49, %50, %51, %52, %53, %54, %55, %56, %57, %58, %59, %60, %61, %62, %63, %64, %65, %66, %67, %68, %69, %70, %71}, da, db, 1, 1, 1, 0, 1;\n"
    "mov.b64 da, {%75, %72};\nmov.b64 db, {%76, 8};\n"
    "wgmma.mma_async.sync.aligned.m64n144k16.f32.bf16.bf16 {%0, %1, %2, %3, %4, %5, %6, %7, %8, %9, %10, %11, %12, %13, %14, %15, %16, %17, %18, %19, %20, %21, %22, %23, %24, %25, %26, %27, %28, %29, %30, %31, %32, %33, %34, %35, %36, %37, %38, %39, %40, %41, %42, %43, %44, %45, %46, %47, %48, %49, %50, %51, %52, %53, %54, %55, %56, %57, %58, %59, %60, %61, %62, %63, %64, %65, %66, %67, %68, %69, %70, %71}, da, db, 1, 1, 1, 0, 1;\n"
    "mov.b64 da, {%77, %72};\nmov.b64 db, {%78, 8};\n"
    "wgmma.mma_async.sync.aligned.m64n144k16.f32.bf16.bf16 {%0, %1, %2, %3, %4, %5, %6, %7, %8, %9, %10, %11, %12, %13, %14, %15, %16, %17, %18, %19, %20, %21, %22, %23, %24, %25, %26, %27, %28, %29, %30, %31, %32, %33, %34, %35, %36, %37, %38, %39, %40, %41, %42, %43, %44, %45, %46, %47, %48, %49, %50, %51, %52, %53, %54, %55, %56, %57, %58, %59, %60, %61, %62, %63, %64, %65, %66, %67, %68, %69, %70, %71}, da, db, 1, 1, 1, 0, 1;\n"
    "mov.b64 da, {%79, %72};\nmov.b64 db, {%80, 8};\n"
    "wgmma.mma_async.sync.aligned.m64n144k16.f32.bf16.bf16 {%0, %1, %2, %3, %4, %5, %6, %7, %8, %9, %10, %11, %12, %13, %14, %15, %16, %17, %18, %19, %20, %21, %22, %23, %24, %25, %26, %27, %28, %29, %30, %31, %32, %33, %34, %35, %36, %37, %38, %39, %40, %41, %42, %43, %44, %45, %46, %47, %48, %49, %50, %51, %52, %53, %54, %55, %56, %57, %58, %59, %60, %61, %62, %63, %64, %65, %66, %67, %68, %69, %70, %71}, da, db, 1, 1, 1, 0, 1;\n"
    "wgmma.commit_group.sync.aligned;\n"
    "@p0 bra.uni D0;\nmov.u32 n, 0;\nW0:\nmbarrier.try_wait.parity.shared::cta.b64 q, [%81], %82;\n@q bra.uni R0;\nadd.u32 n, n, 1;\nsetp.lt.u32 q, n, 8192;\n@q bra.uni W0;\nR0:\n"
    "D0:\n"
    "}\n"
    : "+f"(d[36]), "+f"(d[37]), "+f"(d[38]), "+f"(d[39]), "+f"(d[40]), "+f"(d[41]), "+f"(d[42]), "+f"(d[43]), "+f"(d[44]),
      "+f"(d[45]), "+f"(d[46]), "+f"(d[47]), "+f"(d[48]), "+f"(d[49]), "+f"(d[50]), "+f"(d[51]), "+f"(d[52]), "+f"(d[53]),
      "+f"(d[54]), "+f"(d[55]), "+f"(d[56]), "+f"(d[57]), "+f"(d[58]), "+f"(d[59]), "+f"(d[60]), "+f"(d[61]), "+f"(d[62]),
      "+f"(d[63]), "+f"(d[64]), "+f"(d[65]), "+f"(d[66]), "+f"(d[67]), "+f"(d[68]), "+f"(d[69]), "+f"(d[70]), "+f"(d[71]),
      "+f"(d[72]), "+f"(d[73]), "+f"(d[74]), "+f"(d[75]), "+f"(d[76]), "+f"(d[77]), "+f"(d[78]), "+f"(d[79]), "+f"(d[80]),
      "+f"(d[81]), "+f"(d[82]), "+f"(d[83]), "+f"(d[84]), "+f"(d[85]), "+f"(d[86]), "+f"(d[87]), "+f"(d[88]), "+f"(d[89]),
      "+f"(d[90]), "+f"(d[91]), "+f"(d[92]), "+f"(d[93]), "+f"(d[94]), "+f"(d[95]), "+f"(d[96]), "+f"(d[97]), "+f"(d[98]),
      "+f"(d[99]), "+f"(d[100]), "+f"(d[101]), "+f"(d[102]), "+f"(d[103]), "+f"(d[104]), "+f"(d[105]), "+f"(d[106]), "+f"(d[107])
    : "r"(ahi), "r"(dsc[0]), "r"(dsc[1]), "r"(dsc[2]), "r"(dsc[3]), "r"(dsc[4]), "r"(dsc[5]), "r"(dsc[6]), "r"(dsc[7]), "r"(bar[0]), "r"(bar[1]) : "memory");
}
__device__ __forceinline__ void o_tail(float* d, uint32_t* v, uint32_t ahi, const uint32_t* dsc, const uint32_t* bar, const uint32_t* adr) {
  asm volatile(
    "{\n.reg .pred p<1>, q;\n.reg .b64 da, db;\n.reg .u32 n;\n"
    "mbarrier.test_wait.parity.shared::cta.b64 p0, [%42], %43;\n"
    "ld.volatile.shared.u32 %36, [%44];\n"
    "mov.b64 da, {%38, %37};\nmov.b64 db, {%39, 8};\n"
    "wgmma.mma_async.sync.aligned.m64n72k16.f32.bf16.bf16 {%0, %1, %2, %3, %4, %5, %6, %7, %8, %9, %10, %11, %12, %13, %14, %15, %16, %17, %18, %19, %20, %21, %22, %23, %24, %25, %26, %27, %28, %29, %30, %31, %32, %33, %34, %35}, da, db, 1, 1, 1, 0, 1;\n"
    "mov.b64 da, {%40, %37};\nmov.b64 db, {%41, 8};\n"
    "wgmma.mma_async.sync.aligned.m64n72k16.f32.bf16.bf16 {%0, %1, %2, %3, %4, %5, %6, %7, %8, %9, %10, %11, %12, %13, %14, %15, %16, %17, %18, %19, %20, %21, %22, %23, %24, %25, %26, %27, %28, %29, %30, %31, %32, %33, %34, %35}, da, db, 1, 1, 1, 0, 1;\n"
    "wgmma.commit_group.sync.aligned;\n"
    "@p0 bra.uni D0;\nmov.u32 n, 0;\nW0:\nmbarrier.try_wait.parity.shared::cta.b64 q, [%42], %43;\n@q bra.uni R0;\nadd.u32 n, n, 1;\nsetp.lt.u32 q, n, 8192;\n@q bra.uni W0;\nR0:\n"
    "ld.volatile.shared.u32 %36, [%44];\n"
    "D0:\n"
    "}\n"
    : "+f"(d[0]), "+f"(d[1]), "+f"(d[2]), "+f"(d[3]), "+f"(d[4]), "+f"(d[5]), "+f"(d[6]), "+f"(d[7]), "+f"(d[8]),
      "+f"(d[9]), "+f"(d[10]), "+f"(d[11]), "+f"(d[12]), "+f"(d[13]), "+f"(d[14]), "+f"(d[15]), "+f"(d[16]), "+f"(d[17]),
      "+f"(d[18]), "+f"(d[19]), "+f"(d[20]), "+f"(d[21]), "+f"(d[22]), "+f"(d[23]), "+f"(d[24]), "+f"(d[25]), "+f"(d[26]),
      "+f"(d[27]), "+f"(d[28]), "+f"(d[29]), "+f"(d[30]), "+f"(d[31]), "+f"(d[32]), "+f"(d[33]), "+f"(d[34]), "+f"(d[35]),
      "=&r"(v[0])
    : "r"(ahi), "r"(dsc[0]), "r"(dsc[1]), "r"(dsc[2]), "r"(dsc[3]), "r"(bar[0]), "r"(bar[1]), "r"(adr[0]) : "memory");
}
__device__ __forceinline__ void o_tail2(float* d, uint32_t* v, uint32_t ahi, const uint32_t* dsc, const uint32_t* bar, const uint32_t* adr) {
  asm volatile(
    "{\n.reg .pred p<2>, q;\n.reg .b64 da, db;\n.reg .u32 n;\n"
    "mbarrier.test_wait.parity.shared::cta.b64 p0, [%42], %43;\n"
    "mbarrier.test_wait.parity.shared::cta.b64 p1, [%44], %45;\n"
    "ld.volatile.shared.u32 %36, [%46];\n"
    "mov.b64 da, {%38, %37};\nmov.b64 db, {%39, 8};\n"
    "wgmma.mma_async.sync.aligned.m64n72k16.f32.bf16.bf16 {%0, %1, %2, %3, %4, %5, %6, %7, %8, %9, %10, %11, %12, %13, %14, %15, %16, %17, %18, %19, %20, %21, %22, %23, %24, %25, %26, %27, %28, %29, %30, %31, %32, %33, %34, %35}, da, db, 1, 1, 1, 0, 1;\n"
    "mov.b64 da, {%40, %37};\nmov.b64 db, {%41, 8};\n"
    "wgmma.mma_async.sync.aligned.m64n72k16.f32.bf16.bf16 {%0, %1, %2, %3, %4, %5, %6, %7, %8, %9, %10, %11, %12, %13, %14, %15, %16, %17, %18, %19, %20, %21, %22, %23, %24, %25, %26, %27, %28, %29, %30, %31, %32, %33, %34, %35}, da, db, 1, 1, 1, 0, 1;\n"
    "wgmma.commit_group.sync.aligned;\n"
    "@p0 bra.uni D0;\nmov.u32 n, 0;\nW0:\nmbarrier.try_wait.parity.shared::cta.b64 q, [%42], %43;\n@q bra.uni R0;\nadd.u32 n, n, 1;\nsetp.lt.u32 q, n, 8192;\n@q bra.uni W0;\nR0:\n"
    "D0:\n"
    "@p1 bra.uni D1;\nmov.u32 n, 0;\nW1:\nmbarrier.try_wait.parity.shared::cta.b64 q, [%44], %45;\n@q bra.uni R1;\nadd.u32 n, n, 1;\nsetp.lt.u32 q, n, 8192;\n@q bra.uni W1;\nR1:\n"
    "ld.volatile.shared.u32 %36, [%46];\n"
    "D1:\n"
    "}\n"
    : "+f"(d[0]), "+f"(d[1]), "+f"(d[2]), "+f"(d[3]), "+f"(d[4]), "+f"(d[5]), "+f"(d[6]), "+f"(d[7]), "+f"(d[8]),
      "+f"(d[9]), "+f"(d[10]), "+f"(d[11]), "+f"(d[12]), "+f"(d[13]), "+f"(d[14]), "+f"(d[15]), "+f"(d[16]), "+f"(d[17]),
      "+f"(d[18]), "+f"(d[19]), "+f"(d[20]), "+f"(d[21]), "+f"(d[22]), "+f"(d[23]), "+f"(d[24]), "+f"(d[25]), "+f"(d[26]),
      "+f"(d[27]), "+f"(d[28]), "+f"(d[29]), "+f"(d[30]), "+f"(d[31]), "+f"(d[32]), "+f"(d[33]), "+f"(d[34]), "+f"(d[35]),
      "=&r"(v[0])
    : "r"(ahi), "r"(dsc[0]), "r"(dsc[1]), "r"(dsc[2]), "r"(dsc[3]), "r"(bar[0]), "r"(bar[1]), "r"(bar[2]), "r"(bar[3]), "r"(adr[0]) : "memory");
}

DEVI void mbar_init(uint32_t b, int c) { asm volatile("mbarrier.init.shared::cta.b64 [%0], %1;" ::"r"(b), "r"(c)); }
DEVI void mbar_arrive(uint32_t b) { asm volatile("mbarrier.arrive.shared::cta.b64 _, [%0];" ::"r"(b) : "memory"); }
DEVI void mbar_expect(uint32_t b, uint32_t tx) {
  asm volatile("mbarrier.arrive.expect_tx.shared::cta.b64 _, [%0], %1;" ::"r"(b), "r"(tx) : "memory");
}
DEVI void mbar_wait(uint32_t b, uint32_t ph) {
  asm volatile(
      "{\n.reg .pred p;\n.reg .u32 n;\nmov.u32 n, 0;\n"
      "LW:\nmbarrier.try_wait.parity.shared::cta.b64 p, [%0], %1;\n"
      "@p bra LD;\nadd.u32 n, n, 1;\nsetp.lt.u32 p, n, 8192;\n@p bra LW;\nLD:\n}\n" ::"r"(b), "r"(ph)
      : "memory");
}
DEVI void mbar_wait2(uint32_t a, uint32_t pa, uint32_t b, uint32_t pb) {
  asm volatile(
      "{\n.reg .pred p, q;\n.reg .u32 n;\nmov.u32 n, 0;\n"
      "LW:\nmbarrier.try_wait.parity.shared::cta.b64 p, [%0], %1;\nmbarrier.try_wait.parity.shared::cta.b64 q, [%2], %3;\n"
      "and.pred p, p, q;\n@p bra LD;\nadd.u32 n, n, 1;\nsetp.lt.u32 p, n, 8192;\n@p bra LW;\nLD:\n}\n" ::"r"(a), "r"(pa), "r"(b), "r"(pb)
      : "memory");
}
DEVI bool elect() {
  uint32_t el;
  asm volatile("{\n.reg .pred p;\nelect.sync _|p, 0xffffffff;\nselp.u32 %0,1,0,p;\n}\n" : "=r"(el));
  return el;
}
DEVI void bulk_g2s(uint32_t dst, const void* src, uint32_t bytes, uint32_t bar) {
  asm volatile("cp.async.bulk.shared::cluster.global.mbarrier::complete_tx::bytes [%0], [%1], %2, [%3];" ::"r"(dst),
               "l"(src), "r"(bytes), "r"(bar)
               : "memory");
}
DEVI void bulk_g2s_pair(uint32_t dst, const void* src, uint32_t bytes, uint32_t bar) {
  asm volatile("cp.async.bulk.shared::cluster.global.mbarrier::complete_tx::bytes.multicast::cluster [%0], [%1], %2, [%3], %4;" ::"r"(dst),
               "l"(src), "r"(bytes), "r"(bar), "h"((uint16_t)3)
               : "memory");
}
DEVI void mbar_arrive_pair(uint32_t b) {
  asm volatile("mbarrier.arrive.shared::cta.b64 _, [%0];\nmbarrier.arrive.shared::cluster.b64 _, [%1];\n" ::"r"(b), "r"(b ^ 0x1000000u) : "memory");
}
DEVI void cluster_arrive() { asm volatile("barrier.cluster.arrive.relaxed.aligned;" ::: "memory"); }
DEVI void cluster_wait() { asm volatile("barrier.cluster.wait.aligned;" ::: "memory"); }
DEVI void tma3(uint32_t dst, const CUtensorMap* m, int c0, int c1, int c2, uint32_t bar) {
  asm volatile(
      "cp.async.bulk.tensor.3d.shared::cluster.global.mbarrier::complete_tx::bytes [%0], [%1, {%3,%4,%5}], [%2];" ::"r"(dst),
      "l"(m), "r"(bar), "r"(c0), "r"(c1), "r"(c2)
      : "memory");
}
DEVI constexpr uint32_t mkdesc(uint32_t addr, uint32_t lbo) { return ((addr & 0x3FFFF) >> 4) | ((lbo >> 4) << 16); }
DEVI void bar_sync(int id) { asm volatile("bar.sync %0, 128;" ::"r"(id) : "memory"); }
DEVI uint4 ld_msg(const void* p) {
  uint4 v;
  asm volatile("ld.relaxed.gpu.global.v4.u32 {%0,%1,%2,%3}, [%4];" : "=r"(v.x), "=r"(v.y), "=r"(v.z), "=r"(v.w) : "l"(p) : "memory");
  return v;
}
DEVI void st_msg(void* p, uint32_t a, uint32_t b, uint32_t c, uint32_t d) {
  asm volatile("st.relaxed.gpu.global.v4.u32 [%0], {%1,%2,%3,%4};" ::"l"(p), "r"(a), "r"(b), "r"(c), "r"(d) : "memory");
}
DEVI uint4 ld_gen(const void* p) {
  uint4 v;
  asm volatile("ld.relaxed.gpu.v4.u32 {%0,%1,%2,%3}, [%4];" : "=r"(v.x), "=r"(v.y), "=r"(v.z), "=r"(v.w) : "l"(p) : "memory");
  return v;
}
DEVI void st_gen(void* p, uint32_t a, uint32_t b, uint32_t c, uint32_t d) {
  asm volatile("st.relaxed.gpu.v4.u32 [%0], {%1,%2,%3,%4};" ::"l"(p), "r"(a), "r"(b), "r"(c), "r"(d) : "memory");
}
DEVI uint32_t ld_rlx(const void* p) {
  uint32_t v;
  asm volatile("ld.relaxed.gpu.global.u32 %0, [%1];" : "=r"(v) : "l"(p) : "memory");
  return v;
}
DEVI uint2 ld_rlx2(const void* p) {
  uint2 v;
  asm volatile("ld.relaxed.gpu.global.v2.u32 {%0,%1}, [%2];" : "=r"(v.x), "=r"(v.y) : "l"(p) : "memory");
  return v;
}
DEVI void st_rlx(void* p, uint32_t v) { asm volatile("st.relaxed.gpu.global.u32 [%0], %1;" ::"l"(p), "r"(v) : "memory"); }
#define spin_guard(n) if (++n > (1u << 16)) break
DEVI void wait_flags(const uint8_t* p, int word, uint32_t target) {
  uint32_t n = 0;
  p += 4 * word;
  _Pragma("unroll 1") while (__any_sync(0xffffffffu, (int)(ld_rlx(p) - target) < 0)) spin_guard(n);
  asm volatile("fence.acquire.gpu;" ::: "memory");
  asm volatile("fence.proxy.async.global;" ::: "memory");
}
DEVI void bulk_s2g(void* dst, uint32_t src, uint32_t bytes) {
  asm volatile("cp.async.bulk.global.shared::cta.bulk_group [%0], [%1], %2;" ::"l"(dst), "r"(src), "r"(bytes) : "memory");
}
#define ABL 0
DEVI void l2_prefetch(const void* p, uint32_t bytes) { if (!(ABL & 2)) asm volatile("cp.async.bulk.prefetch.L2.global [%0], %1;" ::"l"(p), "r"(bytes) : "memory"); }
DEVI void fence_async_smem() { asm volatile("fence.proxy.async.shared::cta;" ::: "memory"); }
DEVI void tma2(uint32_t dst, const CUtensorMap* m, int c0, int c1, uint32_t bar) {
  asm volatile("cp.async.bulk.tensor.2d.shared::cluster.global.mbarrier::complete_tx::bytes [%0], [%1, {%3,%4}], [%2];" ::"r"(dst),
               "l"(m), "r"(bar), "r"(c0), "r"(c1) : "memory");
}
DEVI void stsm4(uint32_t a, uint32_t r0, uint32_t r1, uint32_t r2, uint32_t r3) {
  asm volatile("stmatrix.sync.aligned.m8n8.x4.shared.b16 [%0], {%1,%2,%3,%4};" ::"r"(a), "r"(r0), "r"(r1), "r"(r2), "r"(r3) : "memory");
}
DEVI void stsm2(uint32_t a, uint32_t r0, uint32_t r1) {
  asm volatile("stmatrix.sync.aligned.m8n8.x2.shared.b16 [%0], {%1,%2};" ::"r"(a), "r"(r0), "r"(r1) : "memory");
}
DEVI uint32_t mbar_test(uint32_t b, uint32_t ph) {
  uint32_t ok;
  asm volatile("{\n.reg .pred p;\nmbarrier.test_wait.parity.shared::cta.b64 p, [%1], %2;\nselp.u32 %0,1,0,p;\n}\n"
               : "=r"(ok) : "r"(b), "r"(ph) : "memory");
  return ok;
}
DEVI void st_rlx2(void* p, uint32_t a, uint32_t b) {
  asm volatile("{\n.reg .b64 v;\nmov.b64 v, {%1,%2};\nst.relaxed.gpu.global.b64 [%0], v;\n}\n" ::"l"(p), "r"(a), "r"(b) : "memory");
}
DEVI float selp(int c, float a, float b) {
  float y;
  asm("{\n.reg .pred p;\nsetp.ne.s32 p, %3, 0;\nselp.f32 %0, %1, %2, p;\n}\n" : "=f"(y) : "f"(a), "f"(b), "r"(c));
  return y;
}
DEVI float ex2(float x) { float y; asm("ex2.approx.ftz.f32 %0, %1;" : "=f"(y) : "f"(x)); return y; }
DEVI float rcp(float x) { float y; asm("rcp.approx.ftz.f32 %0, %1;" : "=f"(y) : "f"(x)); return y; }
DEVI float sqrt_a(float x) { float y; asm("sqrt.approx.ftz.f32 %0, %1;" : "=f"(y) : "f"(x)); return y; }
DEVI void ldsm4t(uint32_t* r, uint32_t a) {
  asm volatile("ldmatrix.sync.aligned.m8n8.x4.trans.shared.b16 {%0,%1,%2,%3}, [%4];"
               : "=r"(r[0]), "=r"(r[1]), "=r"(r[2]), "=r"(r[3]) : "r"(a) : "memory");
}
DEVI void ldsm4(uint32_t* r, uint32_t a) {
  asm volatile("ldmatrix.sync.aligned.m8n8.x4.shared.b16 {%0,%1,%2,%3}, [%4];"
               : "=r"(r[0]), "=r"(r[1]), "=r"(r[2]), "=r"(r[3]) : "r"(a) : "memory");
}
DEVI uint32_t lds16(uint32_t a) {
  uint32_t v;
  asm volatile("ld.shared.u16 %0, [%1];" : "=r"(v) : "r"(a) : "memory");
  return v;
}
DEVI void sts16(uint32_t a, uint32_t x) { asm volatile("st.shared.u16 [%0], %1;" ::"r"(a), "r"(x) : "memory"); }
DEVI uint4 ldg128(const void* p) {
  uint4 v;
  asm volatile("ld.global.nc.v4.u32 {%0,%1,%2,%3}, [%4];" : "=r"(v.x), "=r"(v.y), "=r"(v.z), "=r"(v.w) : "l"(p));
  return v;
}
DEVI uint2 ldg64(const void* p) {
  uint2 v;
  asm volatile("ld.global.nc.v2.u32 {%0,%1}, [%2];" : "=r"(v.x), "=r"(v.y) : "l"(p));
  return v;
}
DEVI uint32_t ldg32(const void* p) {
  uint32_t v;
  asm volatile("ld.global.nc.u32 %0, [%1];" : "=r"(v) : "l"(p));
  return v;
}
DEVI uint4 ldcg128(const void* p) {
  uint4 v;
  asm volatile("ld.global.cg.v4.u32 {%0,%1,%2,%3}, [%4];" : "=r"(v.x), "=r"(v.y), "=r"(v.z), "=r"(v.w) : "l"(p) : "memory");
  return v;
}
DEVI uint2 ldcg64(const void* p) {
  uint2 v;
  asm volatile("ld.global.cg.v2.u32 {%0,%1}, [%2];" : "=r"(v.x), "=r"(v.y) : "l"(p) : "memory");
  return v;
}
DEVI uint32_t ldcg32(const void* p) {
  uint32_t v;
  asm volatile("ld.global.cg.u32 %0, [%1];" : "=r"(v) : "l"(p) : "memory");
  return v;
}
DEVI void stg128(void* p, uint32_t a, uint32_t b, uint32_t c, uint32_t d) {
  asm volatile("st.global.v4.u32 [%0], {%1,%2,%3,%4};" ::"l"(p), "r"(a), "r"(b), "r"(c), "r"(d) : "memory");
}
DEVI void stg32(void* p, uint32_t a) { asm volatile("st.global.u32 [%0], %1;" ::"l"(p), "r"(a) : "memory"); }
DEVI uint4 lds128(uint32_t a) {
  uint4 v;
  asm volatile("ld.shared.v4.u32 {%0,%1,%2,%3}, [%4];" : "=r"(v.x), "=r"(v.y), "=r"(v.z), "=r"(v.w) : "r"(a) : "memory");
  return v;
}
DEVI uint2 lds64(uint32_t a) {
  uint2 v;
  asm volatile("ld.shared.v2.u32 {%0,%1}, [%2];" : "=r"(v.x), "=r"(v.y) : "r"(a) : "memory");
  return v;
}
DEVI uint32_t lds32(uint32_t a) {
  uint32_t v;
  asm volatile("ld.shared.u32 %0, [%1];" : "=r"(v) : "r"(a) : "memory");
  return v;
}
DEVI void lds64f_if(bool p, float& a, float& b, uint32_t addr) {
  asm volatile("{\n.reg .pred p;\nsetp.ne.u32 p, %3, 0;\n@p ld.shared.v2.f32 {%0,%1}, [%2];\n}\n"
               : "+f"(a), "+f"(b) : "r"(addr), "r"((uint32_t)p) : "memory");
}
DEVI float ldsf(uint32_t a) { return __uint_as_float(lds32(a)); }
DEVI void sts128(uint32_t a, uint32_t x, uint32_t y, uint32_t z, uint32_t w) {
  asm volatile("st.shared.v4.u32 [%0], {%1,%2,%3,%4};" ::"r"(a), "r"(x), "r"(y), "r"(z), "r"(w) : "memory");
}
DEVI void sts64(uint32_t a, uint32_t x, uint32_t y) { asm volatile("st.shared.v2.u32 [%0], {%1,%2};" ::"r"(a), "r"(x), "r"(y) : "memory"); }
DEVI void sts32(uint32_t a, uint32_t x) { asm volatile("st.shared.u32 [%0], %1;" ::"r"(a), "r"(x) : "memory"); }
DEVI void stsf(uint32_t a, float x) { sts32(a, __float_as_uint(x)); }
DEVI uint32_t packbf(float lo, float hi) {
  uint32_t r;
  asm("cvt.rn.bf16x2.f32 %0, %1, %2;" : "=r"(r) : "f"(hi), "f"(lo));
  return r;
}
DEVI uint32_t nz(uint32_t w) { uint32_t y; asm("max.u32 %0, %1, 1;" : "=r"(y) : "r"(w)); return y; }
DEVI float blo(uint32_t w) { return __uint_as_float(w << 16); }
DEVI float bhi(uint32_t w) { return __uint_as_float(w & 0xffff0000u); }
DEVI float rbf(float x) { return __uint_as_float(packbf(0.f, x)); }
DEVI float shx(float v, int m) { return __shfl_xor_sync(0xffffffffu, v, m); }
DEVI float quad_sum(float v) { v += shx(v, 1); v += shx(v, 2); return v; }
DEVI uint32_t movm(uint32_t a) {
  uint32_t d;
  asm volatile("movmatrix.sync.aligned.m8n8.trans.b16 %0, %1;" : "=r"(d) : "r"(a));
  return d;
}
DEVI void mma16(float* d, uint32_t a0, uint32_t a1, uint32_t a2, uint32_t a3, uint32_t b0, uint32_t b1) {
  asm("mma.sync.aligned.m16n8k16.row.col.f32.bf16.bf16.f32 {%0,%1,%2,%3},{%4,%5,%6,%7},{%8,%9},{%0,%1,%2,%3};"
      : "+f"(d[0]), "+f"(d[1]), "+f"(d[2]), "+f"(d[3])
      : "r"(a0), "r"(a1), "r"(a2), "r"(a3), "r"(b0), "r"(b1));
}
DEVI void mma8z(float* d, uint32_t a0, uint32_t a1, uint32_t b0) {
  asm("mma.sync.aligned.m16n8k8.row.col.f32.bf16.bf16.f32 {%0,%1,%2,%3},{%4,%5},{%6},{%7,%7,%7,%7};"
      : "=f"(d[0]), "=f"(d[1]), "=f"(d[2]), "=f"(d[3])
      : "r"(a0), "r"(a1), "r"(b0), "f"(0.f));
}
DEVI void mma8(float* d, uint32_t a0, uint32_t a1, uint32_t b0) {
  asm("mma.sync.aligned.m16n8k8.row.col.f32.bf16.bf16.f32 {%0,%1,%2,%3},{%4,%5},{%6},{%0,%1,%2,%3};"
      : "+f"(d[0]), "+f"(d[1]), "+f"(d[2]), "+f"(d[3])
      : "r"(a0), "r"(a1), "r"(b0));
}
DEVI void mma16z(float* d, uint32_t a0, uint32_t a1, uint32_t a2, uint32_t a3, uint32_t b0, uint32_t b1) {
  asm("mma.sync.aligned.m16n8k16.row.col.f32.bf16.bf16.f32 {%0,%1,%2,%3},{%4,%5,%6,%7},{%8,%9},{%10,%10,%10,%10};"
      : "=f"(d[0]), "=f"(d[1]), "=f"(d[2]), "=f"(d[3])
      : "r"(a0), "r"(a1), "r"(a2), "r"(a3), "r"(b0), "r"(b1), "f"(0.f));
}
DEVI void mma16a(float* d, const uint32_t* a, uint32_t b0, uint32_t b1) { mma16(d, a[0], a[1], a[2], a[3], b0, b1); }
DEVI float ln_sd(float var) { return rbf(sqrt_a(rbf(rbf(var) + kEps))); }
DEVI int fkey(float f) { int i = __float_as_int(f); return i ^ ((i >> 31) & 0x7fffffff); }
DEVI float sigmoidf(float x) { return rcp(1.f + ex2(-1.4426950408889634f * x)); }

DEVI uint32_t probe_stage(uint32_t pa) { return lds32(pa); }
DEVI void check_stage(uint32_t pv, uint32_t fa, const uint8_t* src) {
  if (__any_sync(0xffffffffu, pv == 0)) {
    uint32_t n = 0, tid;
    asm volatile("mov.u32 %0, %%tid.x;" : "=r"(tid));
    const uint32_t fo = (tid & 96) * 8 + (tid & 16) * 64 + (tid & 15) * 16;
    fa += fo; src += fo;
#pragma unroll 1
    for (uint32_t o = 0; o < 8192;) {
      const uint4 v = ld_msg(src + o);
      sts128(fa + o, v.x, v.y, v.z, v.w);
      if (!__any_sync(0xffffffffu, min(min(v.x, v.y), min(v.z, v.w)) == 0) || ++n > (1u << 16)) o += 2048;
    }
    fence_async_smem();
    __syncwarp();
  }
}

struct Params {
  const uint8_t *x, *wqkv, *wo, *wr, *wg, *wu, *wd;
  uint8_t* out;
  Scratch* g;
};

struct Maps { CUtensorMap wq, x, wo, xr, wg, wu, out; };
#define QPRE 2
#define FDEPTH 2
#define PFSTART 700
#define PFPRE 0
#define PFPER 3
#define PFNS 200
#define XSTART 100
#define XSTEP 300
#define PKSTEP 350
#define WPOLL 300
#define CSROUND 0
#define XLROUND 0
#define CLNS 20
#define FSTART 4000
#define XLSTART 3000
#define WGAP0 0
#define XGAP 150
#define WEARLY 1

__global__ void __cluster_dims__(2, 1, 1) __launch_bounds__(512, 1) fused_kernel(const Params p, const __grid_constant__ Maps tm) {
  extern __shared__ __align__(1024) uint8_t smem_raw[];
  constexpr uint32_t sbd = 1024;
  int cta;
  uint32_t rank;
  {
    asm volatile("mov.u32 %0, %%cluster_ctarank;" : "=r"(rank));
    const int c = blockIdx.x >> 1, t = c - 4, u = c - 36, uq = (u * 37) >> 8;
    const int gpc = c < 4 ? 0 : c < 36 ? t & 7 : 1 + u - 7 * uq, idx = c < 4 ? 4 + c : c < 36 ? t >> 3 : 4 + uq;
    cta = __shfl_sync(0xffffffffu, (2 * gpc + (int)rank) * 8 + idx, 0);
  }
  const uint32_t sb = sbd | (rank << 24);
  if ((uint32_t)__cvta_generic_to_shared(smem_raw) != sb) return;
  const int m = cta >> 3, r = cta & 7;
  const int warp = __shfl_sync(0xffffffffu, (int)(threadIdx.x >> 5), 0);
  const int lane = threadIdx.x & 31;
  uint8_t* const gb = reinterpret_cast<uint8_t*>(p.g);
  auto pack = [&]() -> uint32_t {
    const uint32_t t0 = clock();
    const uint32_t tp = sb + SM_W + 3 * WSTAGE + warp * 2304, bar = sb + SM_PART + 8 * warp;
    uint8_t* flag = GA(flagP, (12 * r + warp) * 128 + 4 * m);
    if (warp > 1) {
      asm volatile("bar.sync 4, 512;" ::: "memory");
      cluster_arrive();
      while ((uint32_t)clock() - t0 < (warp - 1) * PKSTEP) {}
    }
    if (elect()) {
      mbar_init(bar, 1);
      asm volatile("fence.mbarrier_init.release.cluster;" ::: "memory");
      mbar_expect(bar, 2304);
      if (warp < 9) tma3(tp, &tm.wq, 72 * r, 64 * warp + 8 * (m >> 1), m & 1, bar);
      else tma2(tp, &tm.wo, 72 * r, 192 * (warp - 9) + 24 * (m >> 1) + 8 * (m & 1), bar);
    }
    __syncwarp();
    if (lane == 0) st_rlx(flag, 0);
    if (warp <= 1) { asm volatile("bar.sync 4, 512;" ::: "memory"); cluster_arrive(); }
    mbar_wait(sb + B_EP, 0);
    const uint32_t epoch = lds32(sb + SM_EP);
    uint8_t* dst = GC(wpack, (r * 12 + warp) * WSTAGE + (27 * (m >> 1) + 14 * (m & 1)) * 128 + lane * 16);
    mbar_wait(bar, 0);
#pragma unroll
    for (int i = 0; i < 4; i++) {
      const int u = 4 * i + (lane >> 3) + 5 * (m & 1);
      const uint4 x = lds128(tp + (lane & 7) * 144 + u * 16 + (u >= 9 ? 1008 : 0));
      if (u < 14 + 4 * (m & 1)) stg128(dst + 512 * i, nz(x.x), nz(x.y), nz(x.z), nz(x.w));
    }
    if (lane == 0) st_rlx(flag, epoch);
    fence_async_smem();
    __syncwarp();
    if (elect()) asm volatile("mbarrier.inval.shared::cta.b64 [%0];" ::"r"(bar) : "memory");
    cluster_wait();
    return epoch;
  };

  if (warp >= 12) {
    asm volatile("setmaxnreg.dec.sync.aligned.u32 24;");
    uint32_t e0 = 0;
    if (warp == 15) e0 = ld_rlx(GA(epoch, 32 * cta));
    if (elect()) {
#pragma unroll
      for (int i = 0; i < NBAR; i++)
        if (warp - 12 == (i * 4) / NBAR)
          mbar_init(sb + SM_BAR + 8 * i, i < 4 ? 1 : i < 8 ? 16 : i < 16 ? 2 : i == (B_PKF - SM_BAR) / 8 ? 8 : i < NBAR4 ? 4 : 1);
      asm volatile("fence.mbarrier_init.release.cluster;" ::: "memory");
    }
    __syncwarp();
    asm volatile("bar.sync 4, 512;" ::: "memory");
    cluster_arrive();
    if (warp == 12) {
      mbar_wait(sb + B_EP, 0);
      cluster_wait();
      const uint32_t epoch = lds32(sb + SM_EP);
      const uint32_t half = (m & 1) * (WSTAGE / 2);
      const uint8_t* src = GC(wpack, r * 12 * WSTAGE + half);
      __nanosleep(WPOLL);
#pragma unroll 1
      for (int g = 0; g < 24; g++) {
        const uint32_t slot = g & 3;
        if (g < 12) wait_flags(GA(flagP, (12 * r + g) * 128), lane & 15, epoch);
        if (g == 0) TRL(3, 0);
        if (g == 3) mbar_wait(sb + B_PKF, 0);
        if (g >= 4) mbar_wait(sb + B_WEMPTY + 8 * slot, ((g >> 2) - 1) & 1);
        if (elect()) {
          const uint32_t bar = sb + (g < 12 ? B_WL : B_WFULL) + 8 * slot;
          mbar_expect(bar, WSTAGE);
          bulk_g2s_pair(sb + SM_W + slot * WSTAGE + half, src + (g >= 12 ? g - 12 : g) * WSTAGE, WSTAGE / 2, bar);
        }
      }
    } else if (warp <= 14) {
      const int w = warp - 13;
      const uint32_t full = sb + B_XFULL + 32 * w, empty = sb + B_XEMPTY + 32 * w, ring = sb + SM_X + w * 4 * XSTAGE;
      mbar_wait(sb + B_EP, 0);
      cluster_wait();
      const uint32_t epoch = lds32(sb + SM_EP);
      if (lane < 4) st_rlx(GA(flagX, 128 * (2 * m + w) + 16 * r + 4 * lane), epoch * 4);
#pragma unroll 1
      for (int gemm = 0; gemm < 4; gemm++) {
        const uint8_t* src = GC(act, (gemm - 1) * ACT + (2 * m + w) * 73728);
        if (gemm & 1) {
          mbar_wait(empty, 0);
          if (elect()) {
            mbar_expect(sb + B_RES + 8 * w, 9216);
            if (gemm == 1) tma3(ring, &tm.xr, 72 * r, w, m * 64, sb + B_RES + 8 * w);
            else bulk_g2s(ring, GC(act, ACT + (2 * m + w) * 73728 + r * 9216), 9216, sb + B_RES + 8 * w);
          }
        }
        if (gemm > 0) {
          mbar_wait(gemm & 1 ? sb + B_RC + 8 * w : empty, gemm & 1 ? gemm >> 1 : 1);
          TRL(3, 11 + w * 4 + gemm);
          wait_flags(GA(flagX, 128 * (2 * m + w)), lane, epoch * 4 + gemm);
          TRL(3, 1 + w * 4 + gemm);
        }
        if (gemm & 1) {
          if (elect()) {
#pragma unroll
            for (int s = 0; s < 9; s++) {
              if (s >= 4) mbar_wait(empty + 8 * (s & 3), s == 4);
              mbar_expect(full + 8 * (s & 3), XSTAGE);
              bulk_g2s(ring + (s & 3) * XSTAGE, src + s * XSTAGE, XSTAGE, full + 8 * (s & 3));
              mbar_arrive(full + 8 * (s & 3));
            }
          }
          __syncwarp();
          continue;
        }
        bool gate = gemm == 2;
#pragma unroll 1
        for (int s = 0; s < (gemm == 2 ? 11 : 9); s++) {
          const uint32_t slot = s & 3;
          if (gemm == 0 && s < 4) __nanosleep(s ? XSTEP : XSTART);
          if (gemm == 2 && s > 0 && s < 4) __nanosleep(XGAP);
          if (s >= 4) mbar_wait(empty + 8 * slot, s >> 3);
          const bool hold = gate && s >= 4 && mbar_test(sb + B_WANT, 0);
          if (lane == 0 && !hold && (gemm != 2 || (s & ~1) != 2)) mbar_arrive(full + 8 * (gemm == 2 && s >= 4 ? (s - 2) & 3 : slot));
          if (s < 9 && elect()) {
            mbar_expect(full + 8 * slot, XSTAGE);
            if (gemm == 0) tma3(ring + slot * XSTAGE, &tm.x, s * 64, w, m * 64, full + 8 * slot);
            else bulk_g2s(ring + slot * XSTAGE, src + s * XSTAGE, XSTAGE, full + 8 * slot);
          }
          if (hold) {
            mbar_wait(sb + B_DONE, 0);
            gate = false;
            if (lane == 0) mbar_arrive(full + 8 * ((s - 2) & 3));
          }
        }
      }
    } else {
      const uint32_t epoch = e0 + 1;
      if (lane == 0) {
        sts32(sb + SM_EP, epoch);
        mbar_arrive(sb + B_EP);
      }
      __syncwarp();
      cluster_wait();
      int pi = lane;
      auto prefetch = [&]() {
        const uint8_t* pp = pi < 648 ? ((cta & 1) ? p.wu : p.wg) + (uint32_t)(((pi / 72) * 63 + (cta >> 1)) * 9216 + pi * 128)
                                     : p.wd + (uint32_t)((cta * 324 + pi - 648) * 128);
        if (pi < 972 && !(ABL & 2)) asm volatile("prefetch.global.L2 [%0];" ::"l"(pp));
        pi += 32;
      };
      __nanosleep(PFSTART);
#pragma unroll 1
      for (int i = 0; i < PFPRE; i++) { prefetch(); __nanosleep(PFNS); }
      uint32_t ph = 0;
#pragma unroll 1
      for (int g = 0; g < 12; g++) {
        const uint32_t slot = g & 3;
#pragma unroll 1
        for (int n = 0; n < 4096; n++) {
          mbar_wait(sb + B_WL + 8 * slot, (ph >> slot) & 1);
          ph ^= 1 << slot;
          const uint32_t a = sb + SM_W + slot * WSTAGE + lane * 128 + (lane & 3) * 32 + (lane >> 2) * 4;
          uint32_t mn = lds32(a + (lane < 24 ? 6 * 4096 : 0));
#pragma unroll
          for (int u = 0; u < 6; u++) mn = min(mn, lds32(a + u * 4096));
          if (!__any_sync(0xffffffffu, mn == 0) || (ABL & 32)) break;
          fence_async_smem();
          __syncwarp();
          if (elect()) {
            mbar_expect(sb + B_WL + 8 * slot, WSTAGE);
            bulk_g2s(sb + SM_W + slot * WSTAGE, GC(wpack, (r * 12 + g) * WSTAGE), WSTAGE, sb + B_WL + 8 * slot);
          }
        }
        if (lane == 0) mbar_arrive(sb + B_WFULL + 8 * slot);
#pragma unroll 1
        for (int i = 0; i < PFPER; i++) prefetch();
      }
      TRL(3, 22);
      mbar_wait(sb + B_FD, 0);
      TRL(3, 20);
      if (elect()) {
        mbar_expect(sb + B_WD, (ABL & 64) ? 0 : 41472);
#pragma unroll 4
        for (int i = 0; i < 36; i++)
          if (!(ABL & 64)) bulk_g2s(sb + SM_WD + i * WDP, p.wd + (uint32_t)(cta * 36 + i) * 1152u, 1152, sb + B_WD);
      }
      __syncwarp();
      TRL(3, 21);
      {
        const uint32_t epoch = e0, h = (lane >> 1) * 128 + (lane & 1) * 16;
        mbar_wait(sb + B_OS, 0);
#pragma unroll 1
        for (int i = cta; i < 1296; i += 128) { stg128(GC(wpack, i * 2048 + (lane & 6) * 16 + h), 0, 0, 0, 0); __nanosleep(CLNS); }
#pragma unroll 1
        for (int i = 0; i < 5; i++) {
          stg128(GC(halo, (cta * 5 + i) * 2048 + h), 0, 0, 0, 0);
          if (i < 4 || lane < 16) stg128(GC(candrow, cta * 2304 + i * 512 + lane * 16), 0, 0, 0, 0);
          stg128(GC(act, (cta * 27 + i) * 2048 + 96 + h), 0, 0, 0, 0);
          __nanosleep(CLNS);
        }
        mbar_wait(sb + B_OS, 1);
#pragma unroll 1
        for (int i = 5; i < 27; i++) { stg128(GC(act, (cta * 27 + i) * 2048 + 96 + h), 0, 0, 0, 0); __nanosleep(CLNS); }
      }
      TRL(3, 23);
    }
  } else if (warp >= 8) {
    asm volatile("setmaxnreg.inc.sync.aligned.u32 200;");
    const int sw = warp - 8, s = threadIdx.x - 256;
    const uint32_t t0 = clock();
    const uint32_t epoch = pack();
    TR(2, 0);
    auto ffn_round = [&](int u) {
      const uint32_t bar = sb + B_FF + 8 * (u % FDEPTH), dst = sb + SM_WD + (u % FDEPTH) * FSLOT;
      if (ABL & 4) { mbar_arrive(bar); return; }
      mbar_expect(bar, 12288);
      tma2(dst, &tm.wg, ((cta * 72) >> 5) << 4, 64 * u, bar);
      tma2(dst + FSLOT / 2, &tm.wu, ((cta * 72) >> 5) << 4, 64 * u, bar);
    };
    const int xi = 8 * r + 4 * (sw >> 1) + (lane >> 3);
    uint4 xv[9];
    uint32_t wr[9];
        {
          const uint8_t* xsrc = p.x + (uint32_t)((128 * m + 2 * xi + (sw & 1)) * 1152 + (lane & 7) * 16);
#pragma unroll
          for (int u = 0; u < 9; u++) xv[u] = ldg128(xsrc + u * 128);
#pragma unroll
          for (int u = 0; u < 9; u++) wr[u] = sw == 0 ? ldg32(p.wr + 128 * u + 4 * lane) : 0u;
        }
    {
      asm volatile("bar.sync 15, 384;" ::: "memory");
      const int u = (s >> 3) + 5 * (m & 1);
      uint4 v[9];
#pragma unroll
      for (int g = 0; g < 9; g++) v[g] = lds128(sb + SM_W + 3 * WSTAGE + g * 2304 + u * 16 + (u >= 9 ? 1008 : 0) + (s & 7) * 144);
      fence_async_smem();
      __syncwarp();
      if (lane == 0) mbar_arrive_pair(sb + B_PKF);
      float a[8] = {};
#pragma unroll
      for (int g = 0; g < 9; g++) {
        a[0] += blo(v[g].x); a[1] += bhi(v[g].x); a[2] += blo(v[g].y); a[3] += bhi(v[g].y);
        a[4] += blo(v[g].z); a[5] += bhi(v[g].z); a[6] += blo(v[g].w); a[7] += bhi(v[g].w);
      }
      const bool b4 = s & 4, b2 = s & 2;
      float b[4];
#pragma unroll
      for (int e = 0; e < 4; e++) b[e] = (b4 ? a[4 + e] : a[e]) + shx(b4 ? a[e] : a[4 + e], 4);
      float c0 = (b2 ? b[2] : b[0]) + shx(b2 ? b[0] : b[2], 2), c1 = (b2 ? b[3] : b[1]) + shx(b2 ? b[1] : b[3], 2);
      c0 += shx(c0, 1); c1 += shx(c1, 1);
      if (!(s & 1) && (s >> 3) < 14 - (m & 1))
        st_rlx2(GA(colpart, (8 * r + (m >> 1)) * 864 + 14 * (m & 1) * 32 + 4 * s), __float_as_uint(c0), (__float_as_uint(c1) & ~15u) | (epoch & 15));
      TR(2, 1);
    }
    if (sw == 0) {
      while ((uint32_t)clock() - t0 < FSTART) {}
      if (elect()) {
#pragma unroll
        for (int u = 0; u < FDEPTH; u++) ffn_round(u);
      }
      __syncwarp();
    }
        {
          float sum = 0.f;
#pragma unroll
          for (int u = 0; u < 9; u++)
            sum += (blo(xv[u].x) + bhi(xv[u].x)) + (blo(xv[u].y) + bhi(xv[u].y)) + (blo(xv[u].z) + bhi(xv[u].z)) + (blo(xv[u].w) + bhi(xv[u].w));
          sum += shx(sum, 1); sum += shx(sum, 2); sum += shx(sum, 4);
          const float mu = sum * (1.f / kD);
          float q = 0.f;
#pragma unroll
          for (int u = 0; u < 9; u++) {
            const uint32_t ww[4] = {xv[u].x, xv[u].y, xv[u].z, xv[u].w};
#pragma unroll
            for (int e = 0; e < 4; e++) {
              const float d0 = blo(ww[e]) - mu, d1 = bhi(ww[e]) - mu;
              q = fmaf(d0, d0, q); q = fmaf(d1, d1, q);
            }
          }
          q += shx(q, 1); q += shx(q, 2); q += shx(q, 4);
          const float rho = rcp(ln_sd(q * (1.f / kD)));
          if ((lane & 7) == 0) st_msg(GA(stats0, 16 * (128 * m + 64 * (sw & 1) + xi)), __float_as_uint(rho), __float_as_uint(mu), 0, epoch);
          if (sw == 0) {
            float wsum = 0.f;
#pragma unroll
            for (int u = 0; u < 9; u++) wsum += blo(wr[u]) + bhi(wr[u]);
#pragma unroll
            for (int o = 1; o < 32; o <<= 1) wsum += shx(wsum, o);
            if (lane == 0) stsf(sb + SM_WSUM, wsum);
          }
          TR(2, 3);
        }
    uint32_t WF[9][4][4];
    {
      const int g = lane >> 2, t = lane & 3;
      const uint32_t c0 = (cta * 72) & 31, ra = 2 * (lane & 6) + (lane & 1) + 2 * ((lane >> 4) ^ ((lane >> 2) & 1));
      const uint32_t fa = sb + SM_WD + (16 * sw + ra) * 128 + ((((c0 + 8) >> 4) + ((lane >> 3) & 1)) << 4);
      const uint32_t fa0 = fa ^ ((ra & 7) << 4), fa1 = (fa + 32) ^ ((ra & 7) << 4);
      const uint32_t rl = 2 * (g & 6) + (g & 1) + 2 * (g >> 2);
      const uint32_t fl = sb + SM_WD + 16 * sw * 128 + (t >> 1) * (FSLOT / 2) + c0 + 64 * (~cta & 1) + 4 * (t & 1);
      const uint32_t fl0 = (fl + rl * 128) ^ ((rl & 7) << 4), fl1 = (fl + (rl ^ 2) * 128) ^ (((rl ^ 2) & 7) << 4);
#pragma unroll
      for (int i = 0; i < 9; i++) {
        mbar_wait(sb + B_FF + 8 * (i % FDEPTH), (i / FDEPTH) & 1);
#pragma unroll
        for (int e = 0; e < 4; e++) ldsm4t(WF[i][e], ((e & 1) ? fa1 : fa0) + (e >> 1) * (FSLOT / 2) + (i % FDEPTH) * FSLOT);
        const uint32_t v0 = lds32(fl0 + (i % FDEPTH) * FSLOT), v1 = lds32(fl1 + (i % FDEPTH) * FSLOT);
        if (i + FDEPTH < 9 || i == 8) {
          fence_async_smem();
          bar_sync(3);
          if (sw == 0 && elect()) {
            if (i < 8) ffn_round(i + FDEPTH);
            else mbar_arrive(sb + B_FD);
          }
        }
        sts64(sb + SM_LEFT + i * 1024 + s * 8, movm(v0), movm(v1));
        if (i == CSROUND) {
          TR(2, 21);
          float c0, c1;
          uint4 s0;
          uint32_t nc = 0;
          _Pragma("unroll 1") while (true) {
            s0 = ld_msg(GA(stats0, 16 * (128 * m + s)));
            uint32_t bad = s0.w != epoch;
            c0 = 0.f; c1 = 0.f;
#pragma unroll
            for (int mm = 0; mm < 8; mm++) {
              const uint2 v = ld_rlx2(GA(colpart, 8 * 864 * r + 8 * min(s, 107)) + mm * 864);
              c0 += __uint_as_float(v.x); c1 += __uint_as_float(v.y & ~15u);
              bad |= v.y ^ epoch;
            }
            if (!__any_sync(0xffffffffu, bad & 15)) break;
            spin_guard(nc);
          }
          if (s < 108) {
            const uint32_t hi = packbf(c0, c1);
            sts32(sb + SM_COLSUM + 32 * (s >> 2) + 4 * (s & 3), hi);
            sts32(sb + SM_COLSUM + 32 * (s >> 2) + 4 * (s & 3) + 16, packbf(c0 - blo(hi), c1 - bhi(hi)));
          }
          sts32(sb + SM_ROWC + 4 * s, s0.x);
          sts64(sb + SM_ROWM + 8 * s, s0.y, __float_as_uint(1.f));
          fence_async_smem();
          __syncwarp();
          if (lane == 0) mbar_arrive(sb + B_COLSUM);
          TR(2, 13);
        }
      }
      TR(2, 4);
    }
    {
      const uint32_t y = epoch * 2 - 1;
      st_msg(GA(ypart, (s >> 1) * 4096 + cta * 32 + (s & 1) * 16), y, y, y, y);
      if (s < 16) {
        st_msg(GA(ypart, (64 + (s >> 1)) * 4096 + cta * 32 + (s & 1) * 16), y, y, y, y);
        st_rlx(GA(fixmsg, 1024 * r + 64 * m + 4 * s), epoch - 1);
      }
      if (s < 64 && cta < 72) st_rlx(GA(x2msg, (s >> 3) * 2304 + 32 * cta + 4 * (s & 7)), epoch - 1);
    }
#pragma unroll 1
    for (int L = 0; L < 2; L++) {
      const uint32_t tag = epoch * 2 + L;
      int s0 = __shfl_sync(0xffffffffu, (int)threadIdx.x + L, threadIdx.x & 31) - L - 256;
#define RELANE asm volatile("" : "+r"(s0)); const int s = s0, lane = s & 31, g = lane >> 2, t = lane & 3; (void)g; (void)t
      RELANE;
      const uint8_t* crow = GC(candrow, L * 128 * 1152 + 32 * sw + 8 * t);
      const uint8_t* cptr = GA(cand, (8 * L + r) * 2048 + 16 * s);
      asm volatile("" : "+l"(crow), "+l"(cptr));
      mbar_wait2(sb + B_WD, 0, sb + B_EPI, L);
      uint32_t win;
      {
        uint32_t c, n = 0;
        _Pragma("unroll 1") while (true) {
          c = ld_rlx(cptr) ^ (epoch & 0x7f);
          if (!__any_sync(0xffffffffu, c & 0x7f)) break;
          spin_guard(n);
        }
        const int wm = __reduce_max_sync(0xffffffffu, (int)(c | s));
        if (lane == 0) sts32(sb + SM_RED + 4 * sw, wm);
        bar_sync(3);
        const uint4 v = lds128(sb + SM_RED);
        win = max(max((int)v.x, (int)v.y), max((int)v.z, (int)v.w));
      }
      crow += (win & 127) * 1152;
      if (s == 0) {
        if (L == 0 && WEARLY) mbar_arrive(sb + B_WANT);
        sts32(sb + SM_SEL + 4 * L, win & 0x7ff);
        mbar_arrive(sb + B_IDX + 8 * L);
      }
      TR(2, 5 + 10 * L);
      uint2 xw[9];
      {
        uint32_t n = 0;
        _Pragma("unroll 1") while (true) {
          uint32_t mn = ~0u;
#pragma unroll
          for (int i = 0; i < 9; i++) { xw[i] = ld_rlx2(crow + 128 * i); mn = min(mn, min(xw[i].x, xw[i].y)); }
          if (!__any_sync(0xffffffffu, mn == 0)) break;
          spin_guard(n);
        }
      }
      if (L == 0 && !WEARLY && s == 0) mbar_arrive(sb + B_WANT);
      TR(2, 6 + 10 * L);
      {
        float a[4][4] = {}, al[4] = {};
#pragma unroll
        for (int i = 0; i < 9; i++) {
          const uint2 wl = lds64(sb + SM_LEFT + s * 8 + i * 1024);
#pragma unroll
          for (int e = 0; e < 4; e++) mma16a(a[e], WF[i][e], xw[i].x, xw[i].y);
          mma8(al, wl.x, wl.y, (g & 1) ? xw[i].y : xw[i].x);
        }
        const uint32_t pp = sb + SM_PART + ((t >> 1) * 36 + 16 * (t & 1) + g + 4 * (cta & 1)) * 16 + 4 * sw;
        stsf(pp, selp(t & 2, selp(t & 1, a[3][0], a[2][0]), selp(t & 1, a[1][0], a[0][0])));
        stsf(pp + 128, selp(t & 2, selp(t & 1, a[3][2], a[2][2]), selp(t & 1, a[1][2], a[0][2])));
        stsf(sb + SM_PART + ((g >> 2) * 36 + 32 * (~cta & 1) + (g & 3)) * 16 + 4 * sw, al[0] + al[3]);
      }
      {
        RELANE;
        const uint32_t wa = sb + SM_WD + 288 * sw + ((lane >> 3) & 1) * 16 + ((lane & 7) + 8 * (lane >> 4)) * WDP;
        const uint32_t wb = sb + SM_WD + 288 * sw + ((lane >> 3) & 1) * 16 + (32 + (lane & 3)) * WDP;
        uint32_t f[4][4];
#pragma unroll
        for (int u = 0; u < 4; u++) ldsm4t(f[u], wa + 32 * (u & 1) + (u >> 1) * 16 * WDP);
        bar_sync(3);
        {
          float hv[2];
#pragma unroll
          for (int e = 0; e < 2; e++) {
            const uint32_t pp = sb + SM_PART + 16 * (e ? 32 + t : lane);
            const uint4 pg = lds128(pp), pu = lds128(pp + 576);
            const float gp = rbf((__uint_as_float(pg.x) + __uint_as_float(pg.y)) + (__uint_as_float(pg.z) + __uint_as_float(pg.w)));
            const float u = rbf((__uint_as_float(pu.x) + __uint_as_float(pu.y)) + (__uint_as_float(pu.z) + __uint_as_float(pu.w)));
            hv[e] = rbf(gp * sigmoidf(gp)) * u;
          }
          const uint32_t hh = packbf(hv[0], hv[1]);
          sts16(sb + SM_H + 80 * sw + 2 * lane, hh);
          sts16(sb + SM_H + 80 * sw + 64 + 2 * t, hh >> 16);
          __syncwarp();
        }
        TR(2, 7 + 10 * L);
        uint32_t hp[5];
#pragma unroll
        for (int i = 0; i < 4; i++) hp[i] = lds32(sb + SM_H + 80 * sw + 16 * i + 4 * t);
        hp[4] = lds32(sb + SM_H + 80 * sw + 64 + 4 * (t & 1));
        float Y[4] = {}, Z[4] = {}, C[4] = {};
        {
          uint32_t e0[4], e1[4], e2[4];
          const uint32_t wq = wb + 32 * (((lane >> 2) & 1) + 2 * (lane >> 4));
          ldsm4t(e0, wq); ldsm4t(e1, wq + 128); ldsm4t(e2, wb + 256);
          mma16a(Y, e0, g == (t >> 1) ? hp[4] : 0u, g == 2 + (t >> 1) ? hp[4] : 0u);
          mma16a(Z, e1, g == 4 + (t >> 1) ? hp[4] : 0u, g == 6 + (t >> 1) ? hp[4] : 0u);
          mma8(C, e2[0], e2[1], t < 2 ? hp[4] : 0u);
        }
#pragma unroll
        for (int u = 0; u < 4; u++) {
          const uint32_t wn = wa + 64 * (u + 1);
          const bool p0 = g == 2 * u, p1 = g == 2 * u + 1;
          mma16a(Y, f[0], p0 ? hp[0] : 0u, p0 ? hp[1] : 0u);
          mma16a(Z, f[1], p1 ? hp[0] : 0u, p1 ? hp[1] : 0u);
          ldsm4t(f[0], wn);
          if (u < 3) ldsm4t(f[1], wn + 32);
          mma16a(Y, f[2], p0 ? hp[2] : 0u, p0 ? hp[3] : 0u);
          mma16a(Z, f[3], p1 ? hp[2] : 0u, p1 ? hp[3] : 0u);
          ldsm4t(f[2], wn + 16 * WDP);
          if (u < 3) ldsm4t(f[3], wn + 32 + 16 * WDP);
        }
        mma16a(C, f[0], hp[0], hp[1]);
        mma16a(C, f[2], hp[2], hp[3]);
#pragma unroll
        for (int e = 0; e < 4; e++) Y[e] += Z[e];
        const uint32_t t4 = tag & 15;
        {
          uint8_t* yo = GA(ypart, (18 * sw + 4 * t) * 4096 + cta * 32 + 4 * g);
#pragma unroll
          for (int e = 0; e < 4; e++) st_rlx(yo + (2 * (e & 1) + (e >> 1)) * 4096, (__float_as_uint(Y[e]) & ~15u) | t4);
          if (t < 2) st_rlx(yo + (16 - 3 * t) * 4096, (__float_as_uint(t ? C[2] : C[0]) & ~15u) | t4);
          if (L == 0 && lane == 0) mbar_arrive(sb + B_DONE);
        }
      }
      TR(2, 8 + 10 * L);
      if (cta < 72) {
        RELANE;
        const uint32_t xn = ld_rlx(GC(candrow, (L * 128 + (win & 127)) * 1152 + 16 * cta + 2 * ((s & 6) ^ (2 * (cta & 1)))));
        const uint4 cm = ld_msg(GA(cand, (8 * L + r) * 2048 + 16 * (win & 127)));
        const uint8_t* yp = GA(ypart, cta * 4096 + s * 16);
        uint4 u0, u1;
        uint32_t n = 0;
        _Pragma("unroll 1") while (true) {
          u0 = ld_msg(yp);
          u1 = ld_msg(yp + 2048);
          const uint32_t t4 = tag & 15;
          u0.x ^= t4; u0.y ^= t4; u0.z ^= t4; u0.w ^= t4; u1.x ^= t4; u1.y ^= t4; u1.z ^= t4; u1.w ^= t4;
          if (!__any_sync(0xffffffffu, (u0.x | u0.y | u0.z | u0.w | u1.x | u1.y | u1.z | u1.w) & 15)) break;
          spin_guard(n);
        }
        const float a0 = __uint_as_float(u0.x) + __uint_as_float(u1.x), a1 = __uint_as_float(u0.y) + __uint_as_float(u1.y);
        const float a2 = __uint_as_float(u0.z) + __uint_as_float(u1.z), a3 = __uint_as_float(u0.w) + __uint_as_float(u1.w);
        const bool b4 = lane & 4, b2 = lane & 2;
        const float c0 = (b4 ? a2 : a0) + shx(b4 ? a0 : a2, 4), c1 = (b4 ? a3 : a1) + shx(b4 ? a1 : a3, 4);
        float d = (b2 ? c1 : c0) + shx(b2 ? c0 : c1, 2);
        d += shx(d, 8);
        if (!(lane & 8)) stsf(sb + SM_RED + 32 * (4 * (lane & 1) + ((lane >> 1) & 3)) + 8 * sw + 4 * (lane >> 4), d);
        bar_sync(3);
        if (s < 64) {
          const uint4 p0 = lds128(sb + SM_RED + 32 * (s & 7)), p1 = lds128(sb + SM_RED + 32 * (s & 7) + 16);
          const float y = rbf(((__uint_as_float(p0.x) + __uint_as_float(p0.y)) + (__uint_as_float(p0.z) + __uint_as_float(p0.w))) +
                              ((__uint_as_float(p1.x) + __uint_as_float(p1.y)) + (__uint_as_float(p1.z) + __uint_as_float(p1.w))));
          const uint32_t v = packbf(0.f, fmaf((s & 1) ? bhi(xn) : blo(xn), __uint_as_float(cm.z), __uint_as_float(cm.w)) + rbf(y * __uint_as_float(cm.y)));
          if (L == 0) st_rlx(GA(x2msg, (s >> 3) * 2304 + 32 * cta + 4 * (s & 7)), v | (epoch & 0xffff));
          const int tok = 128 * ((win >> 3) & 15) + 2 * (16 * (win & 3) + ((win >> 7) & 15)) + ((win >> 2) & 1);
          if (L == 1 && s < 8) *reinterpret_cast<uint16_t*>(p.out + (uint32_t)(tok * 1152 + 16 * cta + 2 * s)) = (uint16_t)(v >> 16);
        }
      }
      TR(2, 9 + 10 * L);
      if (L == 0 && m < 14) {
        RELANE;
        const int c = min(2 * m + ((s >> 3) & 1), 26);
        const uint8_t* wsrc = GC(wpack, r * 12 * WSTAGE + (s >> 4) * 3456 + c * 128 + (s & 7) * 16);
        const int k0 = 8 * (s >> 4) + (s & 7);
        uint4 wv[5];
#pragma unroll
        for (int i = 0; i < 5; i++) wv[i] = ldcg128(wsrc + i * WSTAGE);
        uint32_t xv[9];
        {
          uint32_t n = 0;
          _Pragma("unroll 1") while (true) {
            uint32_t bad = 0;
#pragma unroll
            for (int i = 0; i < 9; i++) { xv[i] = ld_rlx(GA(x2msg, r * 2304 + 4 * k0) + 256 * i); bad |= xv[i] ^ epoch; }
            if (!__any_sync(0xffffffffu, bad & 0xffff)) break;
            spin_guard(n);
          }
        }
        TR(2, 10);
        float a[8], z = 0.f;
#pragma unroll
        for (int e = 0; e < 8; e++) a[e] = 0.f;
#pragma unroll
        for (int i = 0; i < 9; i++) {
          const float xx = bhi(xv[i]);
          const uint4 w4 = wv[i % 5];
          if (i < 4) wv[i] = ldcg128(wsrc + (i + 5) * WSTAGE);
          z = fmaf(xx, (lane & 8) ? xx : 1.f, z);
          a[0] = fmaf(xx, blo(w4.x), a[0]); a[1] = fmaf(xx, bhi(w4.x), a[1]);
          a[2] = fmaf(xx, blo(w4.y), a[2]); a[3] = fmaf(xx, bhi(w4.y), a[3]);
          a[4] = fmaf(xx, blo(w4.z), a[4]); a[5] = fmaf(xx, bhi(w4.z), a[5]);
          a[6] = fmaf(xx, blo(w4.w), a[6]); a[7] = fmaf(xx, bhi(w4.w), a[7]);
        }
        const bool b4 = lane & 4, b2 = lane & 2, b1 = lane & 1;
        float b[4];
#pragma unroll
        for (int e = 0; e < 4; e++) b[e] = (b4 ? a[4 + e] : a[e]) + shx(b4 ? a[e] : a[4 + e], 4);
        z += shx(z, 4);
        const float c0 = (b2 ? b[2] : b[0]) + shx(b2 ? b[0] : b[2], 2);
        const float c1 = (b2 ? b[3] : b[1]) + shx(b2 ? b[1] : b[3], 2);
        z += shx(z, 2);
        float d = (b1 ? c1 : c0) + shx(b1 ? c0 : c1, 1);
        z += shx(z, 1);
        d += shx(d, 16);
        z += shx(z, 16);
        if (lane < 16) stsf(sb + SM_GEMV + 16 * lane + 4 * sw, d);
        if ((lane & 23) == 0) stsf(sb + SM_GEMV + 256 + 2 * lane + 4 * sw, z);
        bar_sync(3);
        if (s < 16) {
          const uint4 pd = lds128(sb + SM_GEMV + 16 * s), p1 = lds128(sb + SM_GEMV + 256), p2 = lds128(sb + SM_GEMV + 272);
          const float acc = (__uint_as_float(pd.x) + __uint_as_float(pd.y)) + (__uint_as_float(pd.z) + __uint_as_float(pd.w));
          const float m1 = ((__uint_as_float(p1.x) + __uint_as_float(p1.y)) + (__uint_as_float(p1.z) + __uint_as_float(p1.w))) * (1.f / kD);
          const float m2 = ((__uint_as_float(p2.x) + __uint_as_float(p2.y)) + (__uint_as_float(p2.z) + __uint_as_float(p2.w))) * (1.f / kD);
          const float cs = blo(lds16(sb + SM_COLSUM + 32 * c + 2 * (s & 7))) + blo(lds16(sb + SM_COLSUM + 32 * c + 2 * (s & 7) + 16));
          const float v = (acc - m1 * cs) * rcp(ln_sd(fmaxf(m2 - m1 * m1, 0.f)));
          st_rlx(GA(fixmsg, 1024 * r + 64 * m + 4 * s), __float_as_uint(rbf(v)) | (epoch & 0xffff));
        }
        TR(2, 11);
      }
      {
        if (L == 0 && (int)((win >> 3) & 15) == m) {
          RELANE;
          if (s < 72) {
            const uint8_t* fp = s < 54 ? GA(fixmsg, 1024 * r + 16 * s) : GA(x2msg, r * (2304 + 288) + 16 * (s - 54));
            uint4 v;
            uint32_t n = 0;
            _Pragma("unroll 1") while (true) {
              v = ld_msg(fp);
              if ((((v.x ^ epoch) | (v.y ^ epoch) | (v.z ^ epoch) | (v.w ^ epoch)) & 0xffff) == 0) break;
              spin_guard(n);
            }
            sts128(sb + SM_FIXQ + 16 * s, v.x & 0xffff0000u, v.y & 0xffff0000u, v.z & 0xffff0000u, v.w & 0xffff0000u);
          }
          __syncwarp();
          if (lane == 0) mbar_arrive(sb + B_FIX);
          TR(2, 12);
        }
      }
    }
    if (s == 0) st_rlx(GA(epoch, 32 * cta), epoch);
  } else {
    asm volatile("setmaxnreg.inc.sync.aligned.u32 144;");
    const int w = warp >> 2, j = warp & 3;
    const uint32_t xfull = sb + B_XFULL + 32 * w, xempty = sb + B_XEMPTY + 32 * w, xring = sb + SM_X + w * 4 * XSTAGE;
    if (threadIdx.x >= 128 && threadIdx.x < 188) { sts128(sb + SM_COLSUM + 16 * (threadIdx.x - 128), 0, 0, 0, 0); fence_async_smem(); }
    {
      const uint32_t epoch = pack();
      asm volatile("bar.arrive 15, 384;" ::: "memory");
      TRW(24);
      if (!(ABL & 8)) {
        if (lane < 16) st_msg(GA(statsP, (2 * m + w) * 8192 + r * 1024 + (16 * j + lane) * 16), 0, 0, 0, 0);
        if (lane < 2) st_msg(GA(cand, (8 * lane + r) * 2048 + 16 * (8 * m + warp)), ~epoch, 0, 0, 0);
        if (j == 3) {
#pragma unroll
          for (int u = 0; u < 10; u++) st_msg(GC(halo, (4 * cta + w) * 2560 + lane * 16) + (u / 5) * 5120 + (u % 5) * 512, 0, 0, 0, 0);
        }
        __syncwarp();
      }
      TRW(11);
    }
    const uint32_t mw = 2 * m + w, cid = 8 * m + warp;
    const uint32_t rowc = sb + SM_ROWC + 64 * warp, rowm = sb + SM_ROWM + 128 * warp;
#pragma unroll 1
    for (int L = 0; L < 2; L++) {
      int ln0 = __shfl_sync(0xffffffffu, lane + L, lane) - L;
#define RELANE2 asm volatile("" : "+r"(ln0)); const int ln = ln0, g = ln >> 2, t = ln & 3; \
      const uint32_t pa = xring + j * 256 + (ln & 7) * 1028 + ((ln >> 3) & 1) * 128 + 96; (void)pa
      uint32_t P[27][2], H[20];
      const uint8_t* hl;
      auto halo = [&]() {
#pragma unroll
        for (int u = 0; u < 5; u++) {
          const uint4 v = ld_gen(hl + u * 512);
          H[4 * u] = v.x; H[4 * u + 1] = v.y; H[4 * u + 2] = v.z; H[4 * u + 3] = v.w;
        }
      };
      {
        RELANE2;
        const uint32_t epoch = __shfl_sync(0xffffffffu, lds32(sb + SM_EP), 0);
        int selrow = -1;
        float d[108];
        uint32_t am[4];
        auto split_mean = [&](float m0, float m1) {
          const uint32_t h0 = packbf(m0, m0), h1 = packbf(m1, m1);
          const float l0 = m0 - bhi(h0), l1 = m1 - bhi(h1);
          am[0] = t ? 0u : h0; am[1] = t ? 0u : h1; am[2] = t ? 0u : packbf(l0, l0); am[3] = t ? 0u : packbf(l1, l1);
        };
        const uint32_t cdesc = mkdesc(sbd + SM_COLSUM, 0);
        am[0] = am[1] = am[2] = am[3] = 0;
        if (L == 1) split_mean(ldsf(rowm + 8 * g), ldsf(rowm + 8 * g + 64));
        asm volatile("wgmma.fence.sync.aligned;" ::: "memory");
        wgmma_n144_set(d + 36, am, cdesc + 18);
        wgmma_n72_set(d, am, cdesc);
        asm volatile("wgmma.commit_group.sync.aligned;" ::: "memory");
        const uint32_t adesc = mkdesc(sbd + SM_X + w * 4 * XSTAGE, 1024), ahi = L == 0 ? 0x40000040u : 8u, astep = L == 0 ? 2 : 128;
        const uint32_t bdesc = mkdesc(sbd + SM_W, 3456);
        const uint8_t* xsrc = GC(act, ACT + mw * 73728);
        mbar_wait2(sb + B_WFULL, L, xfull, 0);
        if (L == 1) check_stage(probe_stage(pa), xring, xsrc);
        TRW(0 + 12 * L);
#pragma unroll 1
        for (int s = 0; s < 7; s++) {
          TRQ(s + 9 * L);
          const uint32_t da = adesc + (s & 3) * (XSTAGE >> 4), db = bdesc + (s & 3) * (WSTAGE >> 4);
          const uint32_t nx = (s + 1) & 3, px = ((s + 1) >> 2) & 1;
          asm volatile("wgmma.fence.sync.aligned;" ::: "memory");
          wgmma_n72(d, da, ahi, db);
          wgmma_n144(d + 36, da, ahi, db + (1152 >> 4));
          wgmma_n72(d, da + astep, ahi, db + (6912 >> 4));
          asm volatile("wgmma.commit_group.sync.aligned;" ::: "memory");
          asm volatile("wgmma.wait_group.sync.aligned 1;" ::: "memory");
          if (s > 0 && ln == 0) {
            mbar_arrive_pair(sb + B_WEMPTY + 8 * ((s - 1) & 3));
            mbar_arrive(xempty + 8 * ((s - 1) & 3));
          }
          wgmma_n144(d + 36, da + astep, ahi, db + ((6912 + 1152) >> 4));
          wgmma_n72(d, da + 2 * astep, ahi, db + 2 * (6912 >> 4));
          uint32_t pv;
          const uint32_t dsc[6] = {da + 2 * astep, db + ((2 * 6912 + 1152) >> 4), da + 3 * astep, db + 3 * (6912 >> 4),
                                   da + 3 * astep, db + ((3 * 6912 + 1152) >> 4)};
          const uint32_t bar[4] = {sb + B_WFULL + 8 * nx, px ^ L, xfull + 8 * nx, px}, adr = pa + nx * XSTAGE;
          q_tail(d, &pv, ahi, dsc, bar, &adr);
          if (L == 1) check_stage(pv, xring + nx * XSTAGE, xsrc + (s + 1) * XSTAGE);
        }
        TRQ(7 + 9 * L);
        const uint32_t da7 = adesc + 3 * (XSTAGE >> 4), db7 = bdesc + 3 * (WSTAGE >> 4);
        asm volatile("wgmma.fence.sync.aligned;" ::: "memory");
        wgmma_n144(d + 36, da7, ahi, db7 + (1152 >> 4));
        wgmma_n144(d + 36, da7 + astep, ahi, db7 + ((6912 + 1152) >> 4));
        asm volatile("wgmma.commit_group.sync.aligned;" ::: "memory");
        asm volatile("wgmma.wait_group.sync.aligned 1;" ::: "memory");
        if (ln == 0) { mbar_arrive_pair(sb + B_WEMPTY + 16); mbar_arrive(xempty + 16); }
        {
          uint32_t v[2];
          const uint32_t dsc[4] = {da7 + 2 * astep, db7 + ((2 * 6912 + 1152) >> 4), da7 + 3 * astep, db7 + ((3 * 6912 + 1152) >> 4)};
          const uint32_t bar[6] = {sb + B_WFULL, (uint32_t)L, xfull, 0, sb + (L ? B_IDX : B_COLSUM), 0}, adr[2] = {pa, sb + SM_SEL + (ln >> 5)};
          kv_tail(d, v, ahi, dsc, bar, adr);
          if (L == 1) {
            if ((v[1] & 127) == cid) selrow = v[1] >> 7;
            check_stage(v[0], xring, xsrc + 8 * XSTAGE);
          }
        }
        TRQ(8 + 9 * L);
        const float m0 = ldsf(rowm + 8 * g), m1 = ldsf(rowm + 8 * g + 64);
        {
          uint32_t dsc[8];
#pragma unroll
          for (int kk = 0; kk < 4; kk++) { dsc[2 * kk] = adesc + kk * astep; dsc[2 * kk + 1] = bdesc + ((kk * 6912 + 1152) >> 4); }
          const uint32_t bar[2] = {xempty + 16, 1};
          asm volatile("wgmma.fence.sync.aligned;" ::: "memory");
          kv_last(d, nullptr, ahi, dsc, bar, nullptr);
        }
        if (L == 0) {
          split_mean(m0, m1);
          asm volatile("wgmma.fence.sync.aligned;" ::: "memory");
          wgmma_n144_add(d + 36, am, cdesc + 18);
          wgmma_n72_add(d, am, cdesc);
          asm volatile("wgmma.commit_group.sync.aligned;" ::: "memory");
        }
        auto qstep = [&](int k) {
          wgmma_n72(d, (k < 4 ? da7 : adesc) + (k & 3) * astep, ahi, (k < 4 ? db7 : bdesc) + (k & 3) * (6912 >> 4));
        };
#pragma unroll
        for (int k = 0; k < QPRE; k++) qstep(k);
        asm volatile("wgmma.commit_group.sync.aligned;" ::: "memory");
        asm volatile("wgmma.wait_group.sync.aligned 1;" ::: "memory");
#pragma unroll
        for (int i = 36; i < 108; i++) asm volatile("" : "+f"(d[i])::"memory");
        if (selrow >= 0) {
          mbar_wait(sb + B_FIX, 0);
          stsf(rowc + 4 * selrow, 1.f);
#pragma unroll
          for (int q = 18; q < 54; q++) lds64f_if(selrow == g + 8 * (q & 1), d[2 * q], d[2 * q + 1], sb + SM_FIXQ + 32 * (q >> 1) + 8 * t);
          __syncwarp();
        }
#pragma unroll
        for (int q = 26; q >= 9; q--) { P[q][1] = packbf(d[4 * q + 2], d[4 * q + 3]); P[q][0] = packbf(d[4 * q], d[4 * q + 1]); }
#pragma unroll
        for (int q = 26; q >= 18; q--) P[q][1] = movm(P[q][1]);
        const uint2 ck1 = lds64(rowc + 32 + 8 * t);
        uint8_t* ha = (j < 3 ? smem_raw + (SM_X + (4 * w + 2) * XSTAGE + j * 2560) : GC(halo, (4 * cta + 2 * L + w) * 2560)) + ln * 16;
        P[9][1] = nz(P[9][1]); P[13][1] = nz(P[13][1]); P[17][1] = nz(P[17][1]);
        st_gen(ha, P[9][1], P[10][1], P[11][1], P[12][1]);
        st_gen(ha + 512, P[13][1], P[14][1], P[15][1], P[16][1]);
        st_gen(ha + 2048, nz(ck1.y), P[24][1], P[25][1], P[26][1]);
        st_gen(ha + 1536, nz(ck1.x), P[21][1], P[22][1], P[23][1]);
        st_gen(ha + 1024, P[17][1], P[18][1], P[19][1], P[20][1]);
#pragma unroll
        for (int q = 9; q < 27; q++) asm volatile("" : "+r"(P[q][0]));
        if (j < 3) asm volatile("bar.arrive %0, 64;" ::"r"(5 + warp) : "memory");
        mbar_wait(sb + B_EP, 0);
#pragma unroll
        for (int q = 26; q >= 18; q--) P[q][0] = movm(P[q][0]);
#pragma unroll
        for (int k = QPRE; k < 8; k++) qstep(k);
        asm volatile("wgmma.commit_group.sync.aligned;" ::: "memory");
        hl = (j > 0 || m == 0 ? smem_raw + (SM_X + (4 * w + 2) * XSTAGE + max(j - 1, 0) * 2560)
                              : GC(halo, (4 * (cta - 8) + 2 * L + w) * 2560)) + ln * 16;
        if (j > 0) asm volatile("bar.sync %0, 64;" ::"r"(4 + warp) : "memory");
        asm volatile("wgmma.wait_group.sync.aligned 0;" ::: "memory");
#pragma unroll
        for (int i = 0; i < 36; i++) asm volatile("" : "+f"(d[i])::"memory");
        TRW(1 + 12 * L);
        if (selrow >= 0) {
#pragma unroll
          for (int q = 0; q < 18; q++) lds64f_if(selrow == g + 8 * (q & 1), d[2 * q], d[2 * q + 1], sb + SM_FIXQ + 32 * (q >> 1) + 8 * t);
        }
#pragma unroll
        for (int q = 0; q < 9; q++) { P[q][0] = packbf(d[4 * q], d[4 * q + 1]); P[q][1] = packbf(d[4 * q + 2], d[4 * q + 3]); }
      }
      TRW(2 + 12 * L);
      const uint32_t epoch = lds32(sb + SM_EP);
      uint8_t* fptr = GA(flagX, 128 * mw + 16 * r + 4 * j + ln0);
      {
        RELANE2;
        halo();
        if (ln == 0) { mbar_arrive(xempty + 24); mbar_arrive(xempty); }
        const bool le0 = 2 * t <= g, le1 = 2 * t + 1 <= g;
        uint32_t A0[4][2], A2[4][2];
        float s0[4][4], s1[4][4];
#pragma unroll
        for (int h = 0; h < 4; h++) {
          const int T = 2 * h;
          A0[h][0] = t >= h ? P[T][0] : 0u; A0[h][1] = t >= h ? P[T][1] : 0u;
          A2[h][0] = t <= h ? P[T + 2][0] : 0u; A2[h][1] = t <= h ? P[T + 2][1] : 0u;
          mma8z(s0[h], A2[h][0], A2[h][1], P[9 + T + 2][0]);
          mma8z(s1[h], A2[h][0], A2[h][1], P[9 + T + 2][1]);
        }
#pragma unroll
        for (int h = 0; h < 4; h++) {
          const int T = 2 * h;
          mma16(s0[h], A0[h][0], A0[h][1], P[T + 1][0], P[T + 1][1], P[9 + T][0], P[9 + T + 1][0]);
          mma16(s1[h], A0[h][0], A0[h][1], P[T + 1][0], P[T + 1][1], P[9 + T][1], P[9 + T + 1][1]);
        }
        const uint2 ck0 = lds64(rowc + 8 * t), ck1 = lds64(rowc + 32 + 8 * t);
        const float sc = 0.23570226039551584f * 1.4426950408889634f;
        const float cq0 = ldsf(rowc + 4 * g) * sc, cq1 = ldsf(rowc + 32 + 4 * g) * sc;
        uint8_t* ob = GC(act, 2 * L * ACT + mw * 73728 + r * 9216 + j * 256 + ln * 4);
        float l[2][4][2], ks[2][2], mx[2][4];
        ks[1][0] = __uint_as_float(le0 ? ck1.x : ck0.x); ks[1][1] = __uint_as_float(le1 ? ck1.y : ck0.y);
#pragma unroll
        for (int h = 0; h < 4; h++) {
          l[1][h][0] = (le0 ? s1[h][2] : s0[h][2]) * (cq1 * ks[1][0]); l[1][h][1] = (le1 ? s1[h][3] : s0[h][3]) * (cq1 * ks[1][1]);
          asm volatile("" : "+f"(l[1][h][0]), "+f"(l[1][h][1]));
        }
        asm volatile("" : "+l"(fptr), "+l"(ob));
        {
          uint32_t n = 0;
          _Pragma("unroll 1") while (__any_sync(0xffffffffu, min(min(min(H[0], H[4]), min(H[8], H[12])), H[16]) == 0)) {
            halo();
            spin_guard(n);
          }
        }
        if (ln == 0) mbar_arrive_pair(sb + B_WEMPTY + 24);
        TRW(3 + 12 * L);
        {
          float sm[4][4];
#pragma unroll
          for (int h = 0; h < 4; h++) mma8z(sm[h], A2[h][0], A2[h][1], H[2 * h + 2]);
#pragma unroll
          for (int h = 0; h < 4; h++) mma16(sm[h], A0[h][0], A0[h][1], P[2 * h + 1][0], P[2 * h + 1][1], H[2 * h], H[2 * h + 1]);
          ks[0][0] = __uint_as_float(le0 ? ck0.x : H[12]); ks[0][1] = __uint_as_float(le1 ? ck0.y : H[16]);
          const bool nohalo = (m == 0 && j == 0);
          const float b0 = (nohalo && !le0) ? -INFINITY : 0.f, b1 = (nohalo && !le1) ? -INFINITY : 0.f;
#pragma unroll
          for (int h = 0; h < 4; h++) {
            l[0][h][0] = fmaf(le0 ? s0[h][0] : sm[h][0], cq0 * ks[0][0], b0);
            l[0][h][1] = fmaf(le1 ? s0[h][1] : sm[h][1], cq0 * ks[0][1], b1);
          }
        }
#pragma unroll
        for (int i = 7; i >= 0; i--) mx[i >> 2][i & 3] = fmaxf(l[i >> 2][i & 3][0], l[i >> 2][i & 3][1]);
#pragma unroll
        for (int x = 1; x <= 2; x <<= 1) {
#pragma unroll
          for (int i = 7; i >= 0; i--) mx[i >> 2][i & 3] = fmaxf(mx[i >> 2][i & 3], shx(mx[i >> 2][i & 3], x));
        }
        const uint32_t mle = (le0 ? 0xffffu : 0u) | (le1 ? 0xffff0000u : 0u);
        uint32_t pp[2][4], pc[2][4];
#pragma unroll
        for (int i = 3; i >= 0; i--) {
          const int e = i >> 1, h = 2 * (i & 1);
          const float p0 = ex2(l[e][h][0] - mx[e][h]), p1 = ex2(l[e][h][1] - mx[e][h]);
          const float p2 = ex2(l[e][h + 1][0] - mx[e][h + 1]), p3 = ex2(l[e][h + 1][1] - mx[e][h + 1]);
          float sum[4];
          mma8z(sum, packbf(p0, p1), packbf(p2, p3), 0x3f803f80u);
          const float inv = rcp(sum[0] * sum[2]);
          const float ia = inv * sum[2], ib = inv * sum[0];
          const uint32_t u0 = packbf(p0 * ks[e][0] * ia, p1 * ks[e][1] * ia), u1 = packbf(p2 * ks[e][0] * ib, p3 * ks[e][1] * ib);
          pp[e][h] = u0 & ~mle; pc[e][h] = u0 & mle; pp[e][h + 1] = u1 & ~mle; pc[e][h + 1] = u1 & mle;
        }
#pragma unroll
        for (int e = 1; e >= 0; e--) {
#pragma unroll
          for (int q = 8; q >= 0; q--) {
            const int h = q < 4 ? 0 : q == 4 ? 1 : 2;
            float a[4];
            mma16z(a, pp[e][h], pp[e][h + 1], pc[e][h], pc[e][h + 1], e ? P[18 + q][0] : H[9 + q + q / 3], P[18 + q][e]);
            const bool second = q == 2 * h + 2 ? t > h : q > 2 * h + 2;
            st_rlx(ob + q * 1024 + e * 128, nz(packbf(second ? a[2] : a[0], second ? a[3] : a[1])));
          }
        }
        if (ln == 0) st_rlx(fptr, epoch * 4 + 1 + 2 * L);
        TRW(4 + 12 * L);
      }
      RELANE2;
      float d[36];
      uint32_t WB[9];
      {
        uint32_t R[10][2];
        const uint32_t qs = L == 0 ? 16 : 1024, ra = xring + (16 * j + (ln & 15)) * (L == 0 ? 144 : 16) + (ln >> 4) * qs;
        mbar_wait(sb + B_RES + 8 * w, L);
#pragma unroll
        for (int q = 0; q < 10; q += 2) ldsm4(&R[q][0], ra + q * qs);
        fence_async_smem();
        __syncwarp();
        if (ln == 0) mbar_arrive(sb + B_RC + 8 * w);
#pragma unroll
        for (int q = 0; q < 9; q++) WB[q] = ldg32(p.wr + (uint32_t)(r * 144 + 4 * t) + 16 * q);
#pragma unroll
        for (int h = 0; h < 2; h++) {
          const uint2 mf = lds64(rowm + 8 * g + 64 * h);
          const float f = __uint_as_float(mf.y), k = -__uint_as_float(mf.x) * f;
#pragma unroll
          for (int q = 0; q < 9; q++) { d[4 * q + 2 * h] = fmaf(blo(R[q][h]), f, k); d[4 * q + 2 * h + 1] = fmaf(bhi(R[q][h]), f, k); }
        }
        const uint32_t sel = lds32(sb + SM_SEL);
        if (L == 1 && (sel & 127) == cid) {
          const int selrow = sel >> 7;
#pragma unroll
          for (int q = 0; q < 18; q++) lds64f_if(selrow == g + 8 * (q & 1), d[2 * q], d[2 * q + 1], sb + SM_X2R + 32 * (q >> 1) + 8 * t);
        }
#pragma unroll
        for (int q = 0; q < 9; q++) WB[q] = (g & 1) ? WB[q] : 0x3f803f80u;
        __syncwarp();
      }
      uint8_t* xb = GC(act, ACT + mw * 73728 + r * 9216 + j * 256 + ln * 4);
      uint8_t* sst = GA(statsP, mw * 8192 + r * 1024 + (16 * j + g + 8 * t) * 16);
      const uint8_t* sld = GA(statsP, mw * 8192 + (ln >> 4) * 4096 + (16 * j + (ln & 15)) * 16);
      uint8_t* cptr = GA(cand, (8 * L + r) * 2048 + 16 * cid);
      uint8_t* crow = GC(candrow, (128 * L + cid) * 1152 + 144 * r + 4 * t);
      uint32_t tag = epoch * 2 + L, ktag = ((ln & 15) << 7) | (epoch & 0x7f);
      float wsum = ldsf(sb + SM_WSUM);
      float pivot = __uint_as_float(ld_rlx(GA(stats0, 16 * (16 * cid + (ln & 15)) + 4))) + (L ? ldsf(rowm + 8 * (ln & 15)) : 0.f);
      asm volatile("" : "+l"(xb), "+l"(sst), "+l"(sld), "+l"(cptr), "+l"(crow), "+r"(tag), "+r"(ktag), "+f"(wsum), "+f"(pivot));
      TRW(5 + 12 * L);
      {
        constexpr uint32_t bdesc = mkdesc(sbd + SM_W + WSTAGE, 1152);
        uint32_t adesc[3];
#pragma unroll
        for (int i = 0; i < 3; i++) adesc[i] = __shfl_sync(0xffffffffu, mkdesc(sbd + SM_X + w * 4 * XSTAGE, 1024) + (ln >> 2), i);
#pragma unroll
        for (int i = 0; i < 36; i++) asm volatile("" : "+f"(d[i])::"memory");
        const bool lead = warp == 0 && ln == 0;
        const uint8_t* osrc = GC(act, 2 * L * ACT + mw * 73728);
        mbar_wait2(sb + B_WFULL + 8, L, xfull, 1);
        check_stage(probe_stage(pa), xring, osrc);
        TRW(6 + 12 * L);
#pragma unroll
        for (int s = 0; s < 9; s++) {
          TRQ(18 + s);
          const uint32_t da = adesc[s >> 2] + (s & 3) * (XSTAGE >> 4), db = bdesc + s * (9216 >> 4);
          const uint32_t nx = (s + 1) & 3;
          asm volatile("wgmma.fence.sync.aligned;" ::: "memory");
          wgmma_n72(d, da, 8u, db);
          wgmma_n72(d, da + 128, 8u, db + (2304 >> 4));
          asm volatile("wgmma.commit_group.sync.aligned;" ::: "memory");
          if (s > 0) {
            asm volatile("wgmma.wait_group.sync.aligned 1;" ::: "memory");
            if (ln == 0) {
              mbar_arrive(xempty + 8 * ((s - 1) & 3));
              if ((s == 1 || s == 3 || s == 6) && L == 0) mbar_arrive_pair(sb + B_WEMPTY + (s / 3) * 8);
            }
          }
          const uint32_t px = (((s + 1) >> 2) + (nx == 0)) & 1;
          if ((s == 0 || s == 5) && lead) mbar_arrive(sb + (s ? B_EPI : B_OS));
          if (s < 8) {
            uint32_t pv;
            const uint32_t dsc[4] = {da + 256, db + (4608 >> 4), da + 384, db + (6912 >> 4)};
            const uint32_t bar[4] = {sb + B_WFULL + 8 + 8 * ((s + 1) / 3), (uint32_t)L, xfull + 8 * nx, px}, adr = pa + nx * XSTAGE;
            o_tail2(d, &pv, 8u, dsc, bar, &adr);
            check_stage(pv, xring + nx * XSTAGE, osrc + (s + 1) * XSTAGE);
          } else {
            wgmma_n72(d, da + 256, 8u, db + (4608 >> 4));
            wgmma_n72(d, da + 384, 8u, db + (6912 >> 4));
            asm volatile("wgmma.commit_group.sync.aligned;" ::: "memory");
          }
        }
        asm volatile("wgmma.wait_group.sync.aligned 0;" ::: "memory");
#pragma unroll
        for (int i = 0; i < 36; i++) asm volatile("" : "+f"(d[i])::"memory");
        if (ln == 0) { if (L == 0) mbar_arrive_pair(sb + B_WEMPTY + 24); mbar_arrive(xempty); }
      }
      TRW(7 + 12 * L);
      uint32_t R[9][2];
#pragma unroll
      for (int q = 0; q < 9; q++) { R[q][0] = packbf(d[4 * q], d[4 * q + 1]); R[q][1] = packbf(d[4 * q + 2], d[4 * q + 3]); }
      if (L == 0) {
#pragma unroll
        for (int q = 0; q < 9; q++) { st_rlx(xb + q * 1024, nz(R[q][0])); st_rlx(xb + q * 1024 + 128, nz(R[q][1])); }
        if (ln == 0) st_rlx(fptr, epoch * 4 + 2);
      }
      {
        float sa[4], sc[4];
        mma16z(sa, R[0][0], R[0][1], R[1][0], R[1][1], WB[0], WB[1]);
        mma16z(sc, R[2][0], R[2][1], R[3][0], R[3][1], WB[2], WB[3]);
        mma16(sa, R[4][0], R[4][1], R[5][0], R[5][1], WB[4], WB[5]);
        mma16(sc, R[6][0], R[6][1], R[7][0], R[7][1], WB[6], WB[7]);
        mma8(sa, R[8][0], R[8][1], WB[8]);
        float qq[4] = {0.f, 0.f, 0.f, 0.f};
#pragma unroll
        for (int q = 0; q < 36; q++) qq[q & 3] = fmaf(d[q], d[q], qq[q & 3]);
        const float qa = qq[0] + qq[1], qc = qq[2] + qq[3];
        const bool odd = t & 1;
        float q2 = (odd ? qc : qa) + shx(odd ? qa : qc, 1);
        q2 += shx(q2, 2);
        if (t < 2)
          st_msg(sst, __float_as_uint(odd ? sa[2] + sc[2] : sa[0] + sc[0]), __float_as_uint(q2),
                 __float_as_uint(odd ? sa[3] + sc[3] : sa[1] + sc[1]), tag);
      }
      TRW(8 + 12 * L);
      {
        uint4 u[4];
        uint32_t n = 0;
        _Pragma("unroll 1") while (true) {
#pragma unroll
          for (int i = 0; i < 4; i++) u[i] = ld_msg(sld + 1024 * i);
          if (!__any_sync(0xffffffffu, (u[0].w ^ tag) | (u[1].w ^ tag) | (u[2].w ^ tag) | (u[3].w ^ tag))) break;
          spin_guard(n);
        }
        TRW(9 + 12 * L);
        float s1 = (__uint_as_float(u[0].x) + __uint_as_float(u[1].x)) + (__uint_as_float(u[2].x) + __uint_as_float(u[3].x));
        float s2 = (__uint_as_float(u[0].y) + __uint_as_float(u[1].y)) + (__uint_as_float(u[2].y) + __uint_as_float(u[3].y));
        float s3 = (__uint_as_float(u[0].z) + __uint_as_float(u[1].z)) + (__uint_as_float(u[2].z) + __uint_as_float(u[3].z));
        s1 += shx(s1, 16); s2 += shx(s2, 16); s3 += shx(s3, 16);
        const float mu = s1 * (1.f / kD);
        const float var = fmaxf(fmaf(s2, 1.f / kD, -mu * mu), 0.f);
        const float sd = ln_sd(var), rho = rcp(sd);
        const float rr = (s3 - mu * wsum) * rho;
        const int key = __reduce_max_sync(0xffffffffu, (int)((fkey(rr) & ~0x7ff) | ktag));
        const int best = (key >> 7) & 15;
        if (ln == best) st_msg(cptr, key, __float_as_uint(rbf(sigmoidf(rbf(rr)))), __float_as_uint(1.f + sd), __float_as_uint(L ? pivot + mu : 0.f));
        const float rb = __shfl_sync(0xffffffffu, rho, best), nb = __shfl_sync(0xffffffffu, -mu * rho, best);
        if ((best & 7) == g) {
          const bool hi = best >= 8;
#pragma unroll
          for (int q = 0; q < 9; q++)
            st_rlx(crow + (((q ^ r) & 1) * (4 - 8 * (t & 1))) + 16 * q, nz(packbf(fmaf(hi ? d[4 * q + 2] : d[4 * q], rb, nb), fmaf(hi ? d[4 * q + 3] : d[4 * q + 1], rb, nb))));
        }
        const float f = 1.f + rho, k = pivot - mu * rho;
        sts32(rowc + 4 * (ln & 15), __float_as_uint(f * rcp(ln_sd(var * f * f))));
        sts64(rowm + 8 * (ln & 15), __float_as_uint(L == 0 ? mu : k), __float_as_uint(f));
        __syncwarp();
      }
      TRW(10 + 12 * L);
      if (L == 1) {
#pragma unroll
        for (int h = 0; h < 2; h++) {
          const uint2 kf = lds64(rowm + 8 * g + 64 * h);
          const float k = __uint_as_float(kf.x), f = __uint_as_float(kf.y);
#pragma unroll
          for (int q = 0; q < 9; q++) R[q][h] = packbf(fmaf(d[4 * q + 2 * h], f, k), fmaf(d[4 * q + 2 * h + 1], f, k));
        }
        mbar_wait(xempty + 16, 1);
        const uint32_t st = xring + XSTAGE + (16 * j + (ln & 15)) * 144;
#pragma unroll
        for (int q = 0; q < 8; q += 2) stsm4(st + (ln >> 4) * 16 + q * 16, R[q][0], R[q][1], R[q + 1][0], R[q + 1][1]);
        stsm2(st + 128, R[8][0], R[8][1]);
        fence_async_smem();
        __syncwarp();
        mbar_wait(sb + B_IDX + 8, 0);
        const uint32_t sel = lds32(sb + SM_SEL + 4);
        if ((sel & 127) != cid) {
          if (elect())
            asm volatile("cp.async.bulk.tensor.3d.global.shared::cta.bulk_group [%0, {%2,%3,%4}], [%1];" ::"l"(&tm.out),
                         "r"(xring + XSTAGE + 16 * j * 144), "r"(72 * r), "r"(w), "r"(64 * m + 16 * j) : "memory");
        } else if (ln < 16 && ln != (sel >> 7)) {
          bulk_s2g(p.out + (uint32_t)((128 * m + 2 * (16 * j + ln) + w) * 1152 + r * 144), st, 144);
        }
        asm volatile("cp.async.bulk.commit_group;" ::: "memory");
        asm volatile("cp.async.bulk.wait_group.read 0;" ::: "memory");
        TRW(11 + 12 * L);
        TRDUMP(w);
      }
    }
  }
}

typedef CUresult (*EncodeFn)(CUtensorMap*, CUtensorMapDataType, cuuint32_t, void*, const cuuint64_t*, const cuuint64_t*,
                             const cuuint32_t*, const cuuint32_t*, CUtensorMapInterleave, CUtensorMapSwizzle,
                             CUtensorMapL2promotion, CUtensorMapFloatOOBfill);

}

extern "C" void kernel_launch(void* const* d_in, const int* in_sizes, int n_in, void* d_out, int out_size) {
  static EncodeFn enc = nullptr;
  static Scratch* scratch = nullptr;
  if (!enc) {
    cudaDriverEntryPointQueryResult q;
    cudaGetDriverEntryPoint("cuTensorMapEncodeTiled", (void**)&enc, cudaEnableDefault, &q);
    cudaGetSymbolAddress((void**)&scratch, g_s);
    cudaFuncSetAttribute(fused_kernel, cudaFuncAttributeMaxDynamicSharedMemorySize, 232448);
  }
  Maps tm;
  auto mk = [&](CUtensorMap* t, void* ptr, int rank, const cuuint64_t* dims, const cuuint64_t* strides, const cuuint32_t* box,
                CUtensorMapSwizzle sw, CUtensorMapL2promotion pr) {
    const cuuint32_t es[4] = {1, 1, 1, 1};
    enc(t, CU_TENSOR_MAP_DATA_TYPE_BFLOAT16, rank, ptr, dims, strides, box, es, CU_TENSOR_MAP_INTERLEAVE_NONE, sw, pr,
        CU_TENSOR_MAP_FLOAT_OOB_FILL_NONE);
  };
  { const cuuint64_t d[3] = {576, 2, 1024}, st[2] = {1152, 2304}; const cuuint32_t bx[3] = {64, 1, 64};
    mk(&tm.x, d_in[0], 3, d, st, bx, CU_TENSOR_MAP_SWIZZLE_128B, CU_TENSOR_MAP_L2_PROMOTION_NONE);
    const cuuint32_t br[3] = {72, 1, 64};
    mk(&tm.xr, d_in[0], 3, d, st, br, CU_TENSOR_MAP_SWIZZLE_NONE, CU_TENSOR_MAP_L2_PROMOTION_NONE);
    const cuuint32_t bo[3] = {72, 1, 16};
    mk(&tm.out, d_out, 3, d, st, bo, CU_TENSOR_MAP_SWIZZLE_NONE, CU_TENSOR_MAP_L2_PROMOTION_NONE); }
  { const cuuint64_t d[3] = {576, 576, 3}, st[2] = {3456, 1152}; const cuuint32_t bx[3] = {72, 8, 2};
    mk(&tm.wq, d_in[1], 3, d, st, bx, CU_TENSOR_MAP_SWIZZLE_NONE, CU_TENSOR_MAP_L2_PROMOTION_NONE); }
  { const cuuint64_t d[2] = {576, 576}, st[1] = {1152}; const cuuint32_t bx[2] = {72, 16};
    mk(&tm.wo, d_in[2], 2, d, st, bx, CU_TENSOR_MAP_SWIZZLE_NONE, CU_TENSOR_MAP_L2_PROMOTION_NONE); }
  { const cuuint64_t d[2] = {4608, 576}, st[1] = {9216}; const cuuint32_t bx[2] = {48, 64};
    mk(&tm.wg, d_in[5], 2, d, st, bx, CU_TENSOR_MAP_SWIZZLE_128B, CU_TENSOR_MAP_L2_PROMOTION_L2_128B);
    mk(&tm.wu, d_in[6], 2, d, st, bx, CU_TENSOR_MAP_SWIZZLE_128B, CU_TENSOR_MAP_L2_PROMOTION_L2_128B); }
  Params p;
  p.x = (const uint8_t*)d_in[0]; p.wqkv = (const uint8_t*)d_in[1]; p.wo = (const uint8_t*)d_in[2];
  p.wr = (const uint8_t*)d_in[4]; p.wg = (const uint8_t*)d_in[5]; p.wu = (const uint8_t*)d_in[6]; p.wd = (const uint8_t*)d_in[7];
  p.out = (uint8_t*)d_out;
  p.g = scratch;
  fused_kernel<<<128, 512, 232448>>>(p, tm);
}
```

```cpp
#include <cuda_runtime.h>
#include <cuda_bf16.h>
#include <cuda.h>
#include <stdint.h>
#include <stddef.h>

#define DEVI __device__ __forceinline__

namespace {

constexpr int kD = 576, kF = 4608;
constexpr uint32_t WSTAGE = 27648, XSTAGE = 8192;
constexpr float kEps = 1e-5f;

constexpr uint32_t WDP = 1168;
constexpr uint32_t SM_W = 0;
constexpr uint32_t SM_X = 110592;
constexpr uint32_t SM_WD = 176128;
constexpr uint32_t SM_LEFT = SM_WD + 36 * WDP;
constexpr uint32_t SM_COLSUM = SM_LEFT + 9216;
constexpr uint32_t SM_ROWC = SM_COLSUM + 960;
constexpr uint32_t SM_ROWM = SM_ROWC + 512;
constexpr uint32_t SM_PART = SM_ROWM + 1024;
constexpr uint32_t SM_FIXQ = SM_PART;
constexpr uint32_t SM_X2R = SM_PART + 864;
constexpr uint32_t SM_H = SM_PART + 1152;
constexpr uint32_t SM_GEMV = SM_H;
constexpr uint32_t SM_RED = SM_H + 320;
constexpr uint32_t SM_SEL = SM_RED + 256;
constexpr uint32_t SM_EP = SM_SEL + 8, SM_WSUM = SM_SEL + 12;
constexpr uint32_t SM_BAR = SM_SEL + 16;
constexpr uint32_t B_WFULL = SM_BAR, B_WEMPTY = B_WFULL + 32, B_XFULL = B_WEMPTY + 32, B_XEMPTY = B_XFULL + 64;
constexpr uint32_t B_RC = B_XEMPTY + 64;
constexpr uint32_t B_COLSUM = B_RC + 16, B_PKF = B_COLSUM + 8, B_FIX = B_PKF + 8, B_DONE = B_FIX + 8;
constexpr uint32_t B_FF = B_DONE + 8;
constexpr uint32_t B_IDX = B_FF + 24;
constexpr uint32_t B_WD = B_IDX + 16, B_WANT = B_WD + 8, B_EPI = B_WANT + 8, B_EP = B_EPI + 8, B_OS = B_EP + 8, B_FD = B_OS + 8;
constexpr uint32_t B_WL = B_FD + 8;
constexpr uint32_t B_RES = B_WL + 32;
constexpr uint32_t SM_TOTAL = B_RES + 16;
constexpr int NBAR = (SM_TOTAL - SM_BAR) / 8, NBAR4 = (B_FF - SM_BAR) / 8;
constexpr uint32_t FSLOT = 16384;
static_assert(SM_TOTAL + 256 <= 232448, "smem");

struct __align__(1024) Checked {
  uint32_t candrow[2][128][288];
  uint4 halo[128][2][2][5][32];
  uint8_t wpack[8][12 * WSTAGE];
  uint8_t act[3][16][2][73728];
};
struct __align__(1024) Scratch {
  uint4 cand[2][8][128];
  uint4 ypart[72][128][2];
  uint32_t x2msg[8][576];
  uint32_t fixmsg[8][256];
  uint32_t flagP[8][12][32];
  uint32_t flagX[16][2][32];
  uint32_t epoch[128][8];
  uint4 stats0[16][2][64];
  uint4 statsP[16][2][8][64];
  float colpart[8][8][216];
  Checked chk[2];
};
__device__ Scratch g_s;
#define GA(member, off) (gb + offsetof(Scratch, member) + (uint32_t)(off))
#define GC(member, off) (gb + offsetof(Scratch, chk) + offsetof(Checked, member) + (uint32_t)((off) + (epoch & 1) * (uint32_t)sizeof(Checked)))
constexpr uint32_t ACT = 16 * 2 * 73728;

#define TR(role, i)
#define TRL(role, i)
#define TRDUMP(role)
#define TRW(i)
#define TRZ(i)
#define TRQ(i)

__device__ __forceinline__ void wgmma_n144(float* d, uint32_t alo, uint32_t ahi, uint32_t blo) {
  asm volatile("{\n.reg .b64 da, db;\nmov.b64 da, {%72, %73};\nmov.b64 db, {%74, 8};\n"
    "wgmma.mma_async.sync.aligned.m64n144k16.f32.bf16.bf16 "
    "{%0, %1, %2, %3, %4, %5, %6, %7, %8, %9, %10, %11, %12, %13, %14, %15, %16, %17, %18, %19, %20, %21, %22, %23, %24, %25, %26, %27, %28, %29, %30, %31, %32, %33, %34, %35, %36, %37, %38, %39, %40, %41, %42, %43, %44, %45, %46, %47, %48, %49, %50, %51, %52, %53, %54, %55, %56, %57, %58, %59, %60, %61, %62, %63, %64, %65, %66, %67, %68, %69, %70, %71}, da, db, 1, 1, 1, 0, 1;\n}\n"
    : "+f"(d[0]), "+f"(d[1]), "+f"(d[2]), "+f"(d[3]), "+f"(d[4]), "+f"(d[5]), "+f"(d[6]), "+f"(d[7]), "+f"(d[8]),
      "+f"(d[9]), "+f"(d[10]), "+f"(d[11]), "+f"(d[12]), "+f"(d[13]), "+f"(d[14]), "+f"(d[15]), "+f"(d[16]), "+f"(d[17]),
      "+f"(d[18]), "+f"(d[19]), "+f"(d[20]), "+f"(d[21]), "+f"(d[22]), "+f"(d[23]), "+f"(d[24]), "+f"(d[25]), "+f"(d[26]),
      "+f"(d[27]), "+f"(d[28]), "+f"(d[29]), "+f"(d[30]), "+f"(d[31]), "+f"(d[32]), "+f"(d[33]), "+f"(d[34]), "+f"(d[35]),
      "+f"(d[36]), "+f"(d[37]), "+f"(d[38]), "+f"(d[39]), "+f"(d[40]), "+f"(d[41]), "+f"(d[42]), "+f"(d[43]), "+f"(d[44]),
      "+f"(d[45]), "+f"(d[46]), "+f"(d[47]), "+f"(d[48]), "+f"(d[49]), "+f"(d[50]), "+f"(d[51]), "+f"(d[52]), "+f"(d[53]),
      "+f"(d[54]), "+f"(d[55]), "+f"(d[56]), "+f"(d[57]), "+f"(d[58]), "+f"(d[59]), "+f"(d[60]), "+f"(d[61]), "+f"(d[62]),
      "+f"(d[63]), "+f"(d[64]), "+f"(d[65]), "+f"(d[66]), "+f"(d[67]), "+f"(d[68]), "+f"(d[69]), "+f"(d[70]), "+f"(d[71])
    : "r"(alo), "r"(ahi), "r"(blo));
}
__device__ __forceinline__ void wgmma_n144_set(float* d, const uint32_t* a, uint32_t blo) {
  asm volatile("{\n.reg .b64 db;\nmov.b64 db, {%76, 2};\n"
    "wgmma.mma_async.sync.aligned.m64n144k16.f32.bf16.bf16 "
    "{%0, %1, %2, %3, %4, %5, %6, %7, %8, %9, %10, %11, %12, %13, %14, %15, %16, %17, %18, %19, %20, %21, %22, %23, %24, %25, %26, %27, %28, %29, %30, %31, %32, %33, %34, %35, %36, %37, %38, %39, %40, %41, %42, %43, %44, %45, %46, %47, %48, %49, %50, %51, %52, %53, %54, %55, %56, %57, %58, %59, %60, %61, %62, %63, %64, %65, %66, %67, %68, %69, %70, %71}, {%72, %73, %74, %75}, db, 0, -1, 1, 1;\n}\n"
    : "=f"(d[0]), "=f"(d[1]), "=f"(d[2]), "=f"(d[3]), "=f"(d[4]), "=f"(d[5]), "=f"(d[6]), "=f"(d[7]), "=f"(d[8]),
      "=f"(d[9]), "=f"(d[10]), "=f"(d[11]), "=f"(d[12]), "=f"(d[13]), "=f"(d[14]), "=f"(d[15]), "=f"(d[16]), "=f"(d[17]),
      "=f"(d[18]), "=f"(d[19]), "=f"(d[20]), "=f"(d[21]), "=f"(d[22]), "=f"(d[23]), "=f"(d[24]), "=f"(d[25]), "=f"(d[26]),
      "=f"(d[27]), "=f"(d[28]), "=f"(d[29]), "=f"(d[30]), "=f"(d[31]), "=f"(d[32]), "=f"(d[33]), "=f"(d[34]), "=f"(d[35]),
      "=f"(d[36]), "=f"(d[37]), "=f"(d[38]), "=f"(d[39]), "=f"(d[40]), "=f"(d[41]), "=f"(d[42]), "=f"(d[43]), "=f"(d[44]),
      "=f"(d[45]), "=f"(d[46]), "=f"(d[47]), "=f"(d[48]), "=f"(d[49]), "=f"(d[50]), "=f"(d[51]), "=f"(d[52]), "=f"(d[53]),
      "=f"(d[54]), "=f"(d[55]), "=f"(d[56]), "=f"(d[57]), "=f"(d[58]), "=f"(d[59]), "=f"(d[60]), "=f"(d[61]), "=f"(d[62]),
      "=f"(d[63]), "=f"(d[64]), "=f"(d[65]), "=f"(d[66]), "=f"(d[67]), "=f"(d[68]), "=f"(d[69]), "=f"(d[70]), "=f"(d[71])
    : "r"(a[0]), "r"(a[1]), "r"(a[2]), "r"(a[3]), "r"(blo));
}
__device__ __forceinline__ void wgmma_n144_add(float* d, const uint32_t* a, uint32_t blo) {
  asm volatile("{\n.reg .b64 db;\nmov.b64 db, {%76, 2};\n"
    "wgmma.mma_async.sync.aligned.m64n144k16.f32.bf16.bf16 "
    "{%0, %1, %2, %3, %4, %5, %6, %7, %8, %9, %10, %11, %12, %13, %14, %15, %16, %17, %18, %19, %20, %21, %22, %23, %24, %25, %26, %27, %28, %29, %30, %31, %32, %33, %34, %35, %36, %37, %38, %39, %40, %41, %42, %43, %44, %45, %46, %47, %48, %49, %50, %51, %52, %53, %54, %55, %56, %57, %58, %59, %60, %61, %62, %63, %64, %65, %66, %67, %68, %69, %70, %71}, {%72, %73, %74, %75}, db, 1, -1, 1, 1;\n}\n"
    : "+f"(d[0]), "+f"(d[1]), "+f"(d[2]), "+f"(d[3]), "+f"(d[4]), "+f"(d[5]), "+f"(d[6]), "+f"(d[7]), "+f"(d[8]),
      "+f"(d[9]), "+f"(d[10]), "+f"(d[11]), "+f"(d[12]), "+f"(d[13]), "+f"(d[14]), "+f"(d[15]), "+f"(d[16]), "+f"(d[17]),
      "+f"(d[18]), "+f"(d[19]), "+f"(d[20]), "+f"(d[21]), "+f"(d[22]), "+f"(d[23]), "+f"(d[24]), "+f"(d[25]), "+f"(d[26]),
      "+f"(d[27]), "+f"(d[28]), "+f"(d[29]), "+f"(d[30]), "+f"(d[31]), "+f"(d[32]), "+f"(d[33]), "+f"(d[34]), "+f"(d[35]),
      "+f"(d[36]), "+f"(d[37]), "+f"(d[38]), "+f"(d[39]), "+f"(d[40]), "+f"(d[41]), "+f"(d[42]), "+f"(d[43]), "+f"(d[44]),
      "+f"(d[45]), "+f"(d[46]), "+f"(d[47]), "+f"(d[48]), "+f"(d[49]), "+f"(d[50]), "+f"(d[51]), "+f"(d[52]), "+f"(d[53]),
      "+f"(d[54]), "+f"(d[55]), "+f"(d[56]), "+f"(d[57]), "+f"(d[58]), "+f"(d[59]), "+f"(d[60]), "+f"(d[61]), "+f"(d[62]),
      "+f"(d[63]), "+f"(d[64]), "+f"(d[65]), "+f"(d[66]), "+f"(d[67]), "+f"(d[68]), "+f"(d[69]), "+f"(d[70]), "+f"(d[71])
    : "r"(a[0]), "r"(a[1]), "r"(a[2]), "r"(a[3]), "r"(blo));
}
__device__ __forceinline__ void wgmma_n72(float* d, uint32_t alo, uint32_t ahi, uint32_t blo) {
  asm volatile("{\n.reg .b64 da, db;\nmov.b64 da, {%36, %37};\nmov.b64 db, {%38, 8};\n"
    "wgmma.mma_async.sync.aligned.m64n72k16.f32.bf16.bf16 "
    "{%0, %1, %2, %3, %4, %5, %6, %7, %8, %9, %10, %11, %12, %13, %14, %15, %16, %17, %18, %19, %20, %21, %22, %23, %24, %25, %26, %27, %28, %29, %30, %31, %32, %33, %34, %35}, da, db, 1, 1, 1, 0, 1;\n}\n"
    : "+f"(d[0]), "+f"(d[1]), "+f"(d[2]), "+f"(d[3]), "+f"(d[4]), "+f"(d[5]), "+f"(d[6]), "+f"(d[7]), "+f"(d[8]),
      "+f"(d[9]), "+f"(d[10]), "+f"(d[11]), "+f"(d[12]), "+f"(d[13]), "+f"(d[14]), "+f"(d[15]), "+f"(d[16]), "+f"(d[17]),
      "+f"(d[18]), "+f"(d[19]), "+f"(d[20]), "+f"(d[21]), "+f"(d[22]), "+f"(d[23]), "+f"(d[24]), "+f"(d[25]), "+f"(d[26]),
      "+f"(d[27]), "+f"(d[28]), "+f"(d[29]), "+f"(d[30]), "+f"(d[31]), "+f"(d[32]), "+f"(d[33]), "+f"(d[34]), "+f"(d[35])
    : "r"(alo), "r"(ahi), "r"(blo));
}
__device__ __forceinline__ void wgmma_n72_set(float* d, const uint32_t* a, uint32_t blo) {
  asm volatile("{\n.reg .b64 db;\nmov.b64 db, {%40, 2};\n"
    "wgmma.mma_async.sync.aligned.m64n72k16.f32.bf16.bf16 "
    "{%0, %1, %2, %3, %4, %5, %6, %7, %8, %9, %10, %11, %12, %13, %14, %15, %16, %17, %18, %19, %20, %21, %22, %23, %24, %25, %26, %27, %28, %29, %30, %31, %32, %33, %34, %35}, {%36, %37, %38, %39}, db, 0, -1, 1, 1;\n}\n"
    : "=f"(d[0]), "=f"(d[1]), "=f"(d[2]), "=f"(d[3]), "=f"(d[4]), "=f"(d[5]), "=f"(d[6]), "=f"(d[7]), "=f"(d[8]),
      "=f"(d[9]), "=f"(d[10]), "=f"(d[11]), "=f"(d[12]), "=f"(d[13]), "=f"(d[14]), "=f"(d[15]), "=f"(d[16]), "=f"(d[17]),
      "=f"(d[18]), "=f"(d[19]), "=f"(d[20]), "=f"(d[21]), "=f"(d[22]), "=f"(d[23]), "=f"(d[24]), "=f"(d[25]), "=f"(d[26]),
      "=f"(d[27]), "=f"(d[28]), "=f"(d[29]), "=f"(d[30]), "=f"(d[31]), "=f"(d[32]), "=f"(d[33]), "=f"(d[34]), "=f"(d[35])
    : "r"(a[0]), "r"(a[1]), "r"(a[2]), "r"(a[3]), "r"(blo));
}
__device__ __forceinline__ void wgmma_n72_add(float* d, const uint32_t* a, uint32_t blo) {
  asm volatile("{\n.reg .b64 db;\nmov.b64 db, {%40, 2};\n"
    "wgmma.mma_async.sync.aligned.m64n72k16.f32.bf16.bf16 "
    "{%0, %1, %2, %3, %4, %5, %6, %7, %8, %9, %10, %11, %12, %13, %14, %15, %16, %17, %18, %19, %20, %21, %22, %23, %24, %25, %26, %27, %28, %29, %30, %31, %32, %33, %34, %35}, {%36, %37, %38, %39}, db, 1, -1, 1, 1;\n}\n"
    : "+f"(d[0]), "+f"(d[1]), "+f"(d[2]), "+f"(d[3]), "+f"(d[4]), "+f"(d[5]), "+f"(d[6]), "+f"(d[7]), "+f"(d[8]),
      "+f"(d[9]), "+f"(d[10]), "+f"(d[11]), "+f"(d[12]), "+f"(d[13]), "+f"(d[14]), "+f"(d[15]), "+f"(d[16]), "+f"(d[17]),
      "+f"(d[18]), "+f"(d[19]), "+f"(d[20]), "+f"(d[21]), "+f"(d[22]), "+f"(d[23]), "+f"(d[24]), "+f"(d[25]), "+f"(d[26]),
      "+f"(d[27]), "+f"(d[28]), "+f"(d[29]), "+f"(d[30]), "+f"(d[31]), "+f"(d[32]), "+f"(d[33]), "+f"(d[34]), "+f"(d[35])
    : "r"(a[0]), "r"(a[1]), "r"(a[2]), "r"(a[3]), "r"(blo));
}
__device__ __forceinline__ void q_tail(float* d, uint32_t* v, uint32_t ahi, const uint32_t* dsc, const uint32_t* bar, const uint32_t* adr) {
  asm volatile(
    "{\n.reg .pred p<2>, q;\n.reg .b64 da, db;\n.reg .u32 n;\n"
    "mbarrier.test_wait.parity.shared::cta.b64 p0, [%116], %117;\n"
    "mbarrier.test_wait.parity.shared::cta.b64 p1, [%118], %119;\n"
    "ld.volatile.shared.u32 %108, [%120];\n"
    "mov.b64 da, {%110, %109};\nmov.b64 db, {%111, 8};\n"
    "wgmma.mma_async.sync.aligned.m64n144k16.f32.bf16.bf16 {%36, %37, %38, %39, %40, %41, %42, %43, %44, %45, %46, %47, %48, %49, %50, %51, %52, %53, %54, %55, %56, %57, %58, %59, %60, %61, %62, %63, %64, %65, %66, %67, %68, %69, %70, %71, %72, %73, %74, %75, %76, %77, %78, %79, %80, %81, %82, %83, %84, %85, %86, %87, %88, %89, %90, %91, %92, %93, %94, %95, %96, %97, %98, %99, %100, %101, %102, %103, %104, %105, %106, %107}, da, db, 1, 1, 1, 0, 1;\n"
    "mov.b64 da, {%112, %109};\nmov.b64 db, {%113, 8};\n"
    "wgmma.mma_async.sync.aligned.m64n72k16.f32.bf16.bf16 {%0, %1, %2, %3, %4, %5, %6, %7, %8, %9, %10, %11, %12, %13, %14, %15, %16, %17, %18, %19, %20, %21, %22, %23, %24, %25, %26, %27, %28, %29, %30, %31, %32, %33, %34, %35}, da, db, 1, 1, 1, 0, 1;\n"
    "mov.b64 da, {%114, %109};\nmov.b64 db, {%115, 8};\n"
    "wgmma.mma_async.sync.aligned.m64n144k16.f32.bf16.bf16 {%36, %37, %38, %39, %40, %41, %42, %43, %44, %45, %46, %47, %48, %49, %50, %51, %52, %53, %54, %55, %56, %57, %58, %59, %60, %61, %62, %63, %64, %65, %66, %67, %68, %69, %70, %71, %72, %73, %74, %75, %76, %77, %78, %79, %80, %81, %82, %83, %84, %85, %86, %87, %88, %89, %90, %91, %92, %93, %94, %95, %96, %97, %98, %99, %100, %101, %102, %103, %104, %105, %106, %107}, da, db, 1, 1, 1, 0, 1;\n"
    "wgmma.commit_group.sync.aligned;\n"
    "@p0 bra.uni D0;\nmov.u32 n, 0;\nW0:\nmbarrier.try_wait.parity.shared::cta.b64 q, [%116], %117;\n@q bra.uni R0;\nadd.u32 n, n, 1;\nsetp.lt.u32 q, n, 8192;\n@q bra.uni W0;\nR0:\n"
    "D0:\n"
    "@p1 bra.uni D1;\nmov.u32 n, 0;\nW1:\nmbarrier.try_wait.parity.shared::cta.b64 q, [%118], %119;\n@q bra.uni R1;\nadd.u32 n, n, 1;\nsetp.lt.u32 q, n, 8192;\n@q bra.uni W1;\nR1:\n"
    "ld.volatile.shared.u32 %108, [%120];\n"
    "D1:\n"
    "}\n"
    : "+f"(d[0]), "+f"(d[1]), "+f"(d[2]), "+f"(d[3]), "+f"(d[4]), "+f"(d[5]), "+f"(d[6]), "+f"(d[7]), "+f"(d[8]),
      "+f"(d[9]), "+f"(d[10]), "+f"(d[11]), "+f"(d[12]), "+f"(d[13]), "+f"(d[14]), "+f"(d[15]), "+f"(d[16]), "+f"(d[17]),
      "+f"(d[18]), "+f"(d[19]), "+f"(d[20]), "+f"(d[21]), "+f"(d[22]), "+f"(d[23]), "+f"(d[24]), "+f"(d[25]), "+f"(d[26]),
      "+f"(d[27]), "+f"(d[28]), "+f"(d[29]), "+f"(d[30]), "+f"(d[31]), "+f"(d[32]), "+f"(d[33]), "+f"(d[34]), "+f"(d[35]),
      "+f"(d[36]), "+f"(d[37]), "+f"(d[38]), "+f"(d[39]), "+f"(d[40]), "+f"(d[41]), "+f"(d[42]), "+f"(d[43]), "+f"(d[44]),
      "+f"(d[45]), "+f"(d[46]), "+f"(d[47]), "+f"(d[48]), "+f"(d[49]), "+f"(d[50]), "+f"(d[51]), "+f"(d[52]), "+f"(d[53]),
      "+f"(d[54]), "+f"(d[55]), "+f"(d[56]), "+f"(d[57]), "+f"(d[58]), "+f"(d[59]), "+f"(d[60]), "+f"(d[61]), "+f"(d[62]),
      "+f"(d[63]), "+f"(d[64]), "+f"(d[65]), "+f"(d[66]), "+f"(d[67]), "+f"(d[68]), "+f"(d[69]), "+f"(d[70]), "+f"(d[71]),
      "+f"(d[72]), "+f"(d[73]), "+f"(d[74]), "+f"(d[75]), "+f"(d[76]), "+f"(d[77]), "+f"(d[78]), "+f"(d[79]), "+f"(d[80]),
      "+f"(d[81]), "+f"(d[82]), "+f"(d[83]), "+f"(d[84]), "+f"(d[85]), "+f"(d[86]), "+f"(d[87]), "+f"(d[88]), "+f"(d[89]),
      "+f"(d[90]), "+f"(d[91]), "+f"(d[92]), "+f"(d[93]), "+f"(d[94]), "+f"(d[95]), "+f"(d[96]), "+f"(d[97]), "+f"(d[98]),
      "+f"(d[99]), "+f"(d[100]), "+f"(d[101]), "+f"(d[102]), "+f"(d[103]), "+f"(d[104]), "+f"(d[105]), "+f"(d[106]), "+f"(d[107]),
      "=&r"(v[0])
    : "r"(ahi), "r"(dsc[0]), "r"(dsc[1]), "r"(dsc[2]), "r"(dsc[3]), "r"(dsc[4]), "r"(dsc[5]), "r"(bar[0]), "r"(bar[1]), "r"(bar[2]), "r"(bar[3]), "r"(adr[0]) : "memory");
}
__device__ __forceinline__ void kv_tail(float* d, uint32_t* v, uint32_t ahi, const uint32_t* dsc, const uint32_t* bar, const uint32_t* adr) {
  asm volatile(
    "{\n.reg .pred p<3>, q;\n.reg .b64 da, db;\n.reg .u32 n;\n"
    "mbarrier.test_wait.parity.shared::cta.b64 p0, [%79], %80;\n"
    "mbarrier.test_wait.parity.shared::cta.b64 p1, [%81], %82;\n"
    "mbarrier.test_wait.parity.shared::cta.b64 p2, [%83], %84;\n"
    "ld.volatile.shared.u32 %72, [%85];\n"
    "ld.volatile.shared.u32 %73, [%86];\n"
    "mov.b64 da, {%75, %74};\nmov.b64 db, {%76, 8};\n"
    "wgmma.mma_async.sync.aligned.m64n144k16.f32.bf16.bf16 {%0, %1, %2, %3, %4, %5, %6, %7, %8, %9, %10, %11, %12, %13, %14, %15, %16, %17, %18, %19, %20, %21, %22, %23, %24, %25, %26, %27, %28, %29, %30, %31, %32, %33, %34, %35, %36, %37, %38, %39, %40, %41, %42, %43, %44, %45, %46, %47, %48, %49, %50, %51, %52, %53, %54, %55, %56, %57, %58, %59, %60, %61, %62, %63, %64, %65, %66, %67, %68, %69, %70, %71}, da, db, 1, 1, 1, 0, 1;\n"
    "mov.b64 da, {%77, %74};\nmov.b64 db, {%78, 8};\n"
    "wgmma.mma_async.sync.aligned.m64n144k16.f32.bf16.bf16 {%0, %1, %2, %3, %4, %5, %6, %7, %8, %9, %10, %11, %12, %13, %14, %15, %16, %17, %18, %19, %20, %21, %22, %23, %24, %25, %26, %27, %28, %29, %30, %31, %32, %33, %34, %35, %36, %37, %38, %39, %40, %41, %42, %43, %44, %45, %46, %47, %48, %49, %50, %51, %52, %53, %54, %55, %56, %57, %58, %59, %60, %61, %62, %63, %64, %65, %66, %67, %68, %69, %70, %71}, da, db, 1, 1, 1, 0, 1;\n"
    "wgmma.commit_group.sync.aligned;\n"
    "@p0 bra.uni D0;\nmov.u32 n, 0;\nW0:\nmbarrier.try_wait.parity.shared::cta.b64 q, [%79], %80;\n@q bra.uni R0;\nadd.u32 n, n, 1;\nsetp.lt.u32 q, n, 8192;\n@q bra.uni W0;\nR0:\n"
    "D0:\n"
    "@p1 bra.uni D1;\nmov.u32 n, 0;\nW1:\nmbarrier.try_wait.parity.shared::cta.b64 q, [%81], %82;\n@q bra.uni R1;\nadd.u32 n, n, 1;\nsetp.lt.u32 q, n, 8192;\n@q bra.uni W1;\nR1:\n"
    "ld.volatile.shared.u32 %72, [%85];\n"
    "D1:\n"
    "@p2 bra.uni D2;\nmov.u32 n, 0;\nW2:\nmbarrier.try_wait.parity.shared::cta.b64 q, [%83], %84;\n@q bra.uni R2;\nadd.u32 n, n, 1;\nsetp.lt.u32 q, n, 8192;\n@q bra.uni W2;\nR2:\n"
    "ld.volatile.shared.u32 %73, [%86];\n"
    "D2:\n"
    "}\n"
    : "+f"(d[36]), "+f"(d[37]), "+f"(d[38]), "+f"(d[39]), "+f"(d[40]), "+f"(d[41]), "+f"(d[42]), "+f"(d[43]), "+f"(d[44]),
      "+f"(d[45]), "+f"(d[46]), "+f"(d[47]), "+f"(d[48]), "+f"(d[49]), "+f"(d[50]), "+f"(d[51]), "+f"(d[52]), "+f"(d[53]),
      "+f"(d[54]), "+f"(d[55]), "+f"(d[56]), "+f"(d[57]), "+f"(d[58]), "+f"(d[59]), "+f"(d[60]), "+f"(d[61]), "+f"(d[62]),
      "+f"(d[63]), "+f"(d[64]), "+f"(d[65]), "+f"(d[66]), "+f"(d[67]), "+f"(d[68]), "+f"(d[69]), "+f"(d[70]), "+f"(d[71]),
      "+f"(d[72]), "+f"(d[73]), "+f"(d[74]), "+f"(d[75]), "+f"(d[76]), "+f"(d[77]), "+f"(d[78]), "+f"(d[79]), "+f"(d[80]),
      "+f"(d[81]), "+f"(d[82]), "+f"(d[83]), "+f"(d[84]), "+f"(d[85]), "+f"(d[86]), "+f"(d[87]), "+f"(d[88]), "+f"(d[89]),
      "+f"(d[90]), "+f"(d[91]), "+f"(d[92]), "+f"(d[93]), "+f"(d[94]), "+f"(d[95]), "+f"(d[96]), "+f"(d[97]), "+f"(d[98]),
      "+f"(d[99]), "+f"(d[100]), "+f"(d[101]), "+f"(d[102]), "+f"(d[103]), "+f"(d[104]), "+f"(d[105]), "+f"(d[106]), "+f"(d[107]),
      "=&r"(v[0]), "=&r"(v[1])
    : "r"(ahi), "r"(dsc[0]), "r"(dsc[1]), "r"(dsc[2]), "r"(dsc[3]), "r"(bar[0]), "r"(bar[1]), "r"(bar[2]), "r"(bar[3]), "r"(bar[4]), "r"(bar[5]), "r"(adr[0]), "r"(adr[1]) : "memory");
}
__device__ __forceinline__ void kv_last(float* d, uint32_t* v, uint32_t ahi, const uint32_t* dsc, const uint32_t* bar, const uint32_t* adr) {
  asm volatile(
    "{\n.reg .pred p<1>, q;\n.reg .b64 da, db;\n.reg .u32 n;\n"
    "mbarrier.test_wait.parity.shared::cta.b64 p0, [%81], %82;\n"
    "mov.b64 da, {%73, %72};\nmov.b64 db, {%74, 8};\n"
    "wgmma.mma_async.sync.aligned.m64n144k16.f32.bf16.bf16 {%0, %1, %2, %3, %4, %5, %6, %7, %8, %9, %10, %11, %12, %13, %14, %15, %16, %17, %18, %19, %20, %21, %22, %23, %24, %25, %26, %27, %28, %29, %30, %31, %32, %33, %34, %35, %36, %37, %38, %39, %40, %41, %42, %43, %44, %45, %46, %47, %48, %49, %50, %51, %52, %53, %54, %55, %56, %57, %58, %59, %60, %61, %62, %63, %64, %65, %66, %67, %68, %69, %70, %71}, da, db, 1, 1, 1, 0, 1;\n"
    "mov.b64 da, {%75, %72};\nmov.b64 db, {%76, 8};\n"
    "wgmma.mma_async.sync.aligned.m64n144k16.f32.bf16.bf16 {%0, %1, %2, %3, %4, %5, %6, %7, %8, %9, %10, %11, %12, %13, %14, %15, %16, %17, %18, %19, %20, %21, %22, %23, %24, %25, %26, %27, %28, %29, %30, %31, %32, %33, %34, %35, %36, %37, %38, %39, %40, %41, %42, %43, %44, %45, %46, %47, %48, %49, %50, %51, %52, %53, %54, %55, %56, %57, %58, %59, %60, %61, %62, %63, %64, %65, %66, %67, %68, %69, %70, %71}, da, db, 1, 1, 1, 0, 1;\n"
    "mov.b64 da, {%77, %72};\nmov.b64 db, {%78, 8};\n"
    "wgmma.mma_async.sync.aligned.m64n144k16.f32.bf16.bf16 {%0, %1, %2, %3, %4, %5, %6, %7, %8, %9, %10, %11, %12, %13, %14, %15, %16, %17, %18, %19, %20, %21, %22, %23, %24, %25, %26, %27, %28, %29, %30, %31, %32, %33, %34, %35, %36, %37, %38, %39, %40, %41, %42, %43, %44, %45, %46, %47, %48, %49, %50, %51, %52, %53, %54, %55, %56, %57, %58, %59, %60, %61, %62, %63, %64, %65, %66, %67, %68, %69, %70, %71}, da, db, 1, 1, 1, 0, 1;\n"
    "mov.b64 da, {%79, %72};\nmov.b64 db, {%80, 8};\n"
    "wgmma.mma_async.sync.aligned.m64n144k16.f32.bf16.bf16 {%0, %1, %2, %3, %4, %5, %6, %7, %8, %9, %10, %11, %12, %13, %14, %15, %16, %17, %18, %19, %20, %21, %22, %23, %24, %25, %26, %27, %28, %29, %30, %31, %32, %33, %34, %35, %36, %37, %38, %39, %40, %41, %42, %43, %44, %45, %46, %47, %48, %49, %50, %51, %52, %53, %54, %55, %56, %57, %58, %59, %60, %61, %62, %63, %64, %65, %66, %67, %68, %69, %70, %71}, da, db, 1, 1, 1, 0, 1;\n"
    "wgmma.commit_group.sync.aligned;\n"
    "@p0 bra.uni D0;\nmov.u32 n, 0;\nW0:\nmbarrier.try_wait.parity.shared::cta.b64 q, [%81], %82;\n@q bra.uni R0;\nadd.u32 n, n, 1;\nsetp.lt.u32 q, n, 8192;\n@q bra.uni W0;\nR0:\n"
    "D0:\n"
    "}\n"
    : "+f"(d[36]), "+f"(d[37]), "+f"(d[38]), "+f"(d[39]), "+f"(d[40]), "+f"(d[41]), "+f"(d[42]), "+f"(d[43]), "+f"(d[44]),
      "+f"(d[45]), "+f"(d[46]), "+f"(d[47]), "+f"(d[48]), "+f"(d[49]), "+f"(d[50]), "+f"(d[51]), "+f"(d[52]), "+f"(d[53]),
      "+f"(d[54]), "+f"(d[55]), "+f"(d[56]), "+f"(d[57]), "+f"(d[58]), "+f"(d[59]), "+f"(d[60]), "+f"(d[61]), "+f"(d[62]),
      "+f"(d[63]), "+f"(d[64]), "+f"(d[65]), "+f"(d[66]), "+f"(d[67]), "+f"(d[68]), "+f"(d[69]), "+f"(d[70]), "+f"(d[71]),
      "+f"(d[72]), "+f"(d[73]), "+f"(d[74]), "+f"(d[75]), "+f"(d[76]), "+f"(d[77]), "+f"(d[78]), "+f"(d[79]), "+f"(d[80]),
      "+f"(d[81]), "+f"(d[82]), "+f"(d[83]), "+f"(d[84]), "+f"(d[85]), "+f"(d[86]), "+f"(d[87]), "+f"(d[88]), "+f"(d[89]),
      "+f"(d[90]), "+f"(d[91]), "+f"(d[92]), "+f"(d[93]), "+f"(d[94]), "+f"(d[95]), "+f"(d[96]), "+f"(d[97]), "+f"(d[98]),
      "+f"(d[99]), "+f"(d[100]), "+f"(d[101]), "+f"(d[102]), "+f"(d[103]), "+f"(d[104]), "+f"(d[105]), "+f"(d[106]), "+f"(d[107])
    : "r"(ahi), "r"(dsc[0]), "r"(dsc[1]), "r"(dsc[2]), "r"(dsc[3]), "r"(dsc[4]), "r"(dsc[5]), "r"(dsc[6]), "r"(dsc[7]), "r"(bar[0]), "r"(bar[1]) : "memory");
}
__device__ __forceinline__ void o_tail(float* d, uint32_t* v, uint32_t ahi, const uint32_t* dsc, const uint32_t* bar, const uint32_t* adr) {
  asm volatile(
    "{\n.reg .pred p<1>, q;\n.reg .b64 da, db;\n.reg .u32 n;\n"
    "mbarrier.test_wait.parity.shared::cta.b64 p0, [%42], %43;\n"
    "ld.volatile.shared.u32 %36, [%44];\n"
    "mov.b64 da, {%38, %37};\nmov.b64 db, {%39, 8};\n"
    "wgmma.mma_async.sync.aligned.m64n72k16.f32.bf16.bf16 {%0, %1, %2, %3, %4, %5, %6, %7, %8, %9, %10, %11, %12, %13, %14, %15, %16, %17, %18, %19, %20, %21, %22, %23, %24, %25, %26, %27, %28, %29, %30, %31, %32, %33, %34, %35}, da, db, 1, 1, 1, 0, 1;\n"
    "mov.b64 da, {%40, %37};\nmov.b64 db, {%41, 8};\n"
    "wgmma.mma_async.sync.aligned.m64n72k16.f32.bf16.bf16 {%0, %1, %2, %3, %4, %5, %6, %7, %8, %9, %10, %11, %12, %13, %14, %15, %16, %17, %18, %19, %20, %21, %22, %23, %24, %25, %26, %27, %28, %29, %30, %31, %32, %33, %34, %35}, da, db, 1, 1, 1, 0, 1;\n"
    "wgmma.commit_group.sync.aligned;\n"
    "@p0 bra.uni D0;\nmov.u32 n, 0;\nW0:\nmbarrier.try_wait.parity.shared::cta.b64 q, [%42], %43;\n@q bra.uni R0;\nadd.u32 n, n, 1;\nsetp.lt.u32 q, n, 8192;\n@q bra.uni W0;\nR0:\n"
    "ld.volatile.shared.u32 %36, [%44];\n"
    "D0:\n"
    "}\n"
    : "+f"(d[0]), "+f"(d[1]), "+f"(d[2]), "+f"(d[3]), "+f"(d[4]), "+f"(d[5]), "+f"(d[6]), "+f"(d[7]), "+f"(d[8]),
      "+f"(d[9]), "+f"(d[10]), "+f"(d[11]), "+f"(d[12]), "+f"(d[13]), "+f"(d[14]), "+f"(d[15]), "+f"(d[16]), "+f"(d[17]),
      "+f"(d[18]), "+f"(d[19]), "+f"(d[20]), "+f"(d[21]), "+f"(d[22]), "+f"(d[23]), "+f"(d[24]), "+f"(d[25]), "+f"(d[26]),
      "+f"(d[27]), "+f"(d[28]), "+f"(d[29]), "+f"(d[30]), "+f"(d[31]), "+f"(d[32]), "+f"(d[33]), "+f"(d[34]), "+f"(d[35]),
      "=&r"(v[0])
    : "r"(ahi), "r"(dsc[0]), "r"(dsc[1]), "r"(dsc[2]), "r"(dsc[3]), "r"(bar[0]), "r"(bar[1]), "r"(adr[0]) : "memory");
}
__device__ __forceinline__ void o_tail2(float* d, uint32_t* v, uint32_t ahi, const uint32_t* dsc, const uint32_t* bar, const uint32_t* adr) {
  asm volatile(
    "{\n.reg .pred p<2>, q;\n.reg .b64 da, db;\n.reg .u32 n;\n"
    "mbarrier.test_wait.parity.shared::cta.b64 p0, [%42], %43;\n"
    "mbarrier.test_wait.parity.shared::cta.b64 p1, [%44], %45;\n"
    "ld.volatile.shared.u32 %36, [%46];\n"
    "mov.b64 da, {%38, %37};\nmov.b64 db, {%39, 8};\n"
    "wgmma.mma_async.sync.aligned.m64n72k16.f32.bf16.bf16 {%0, %1, %2, %3, %4, %5, %6, %7, %8, %9, %10, %11, %12, %13, %14, %15, %16, %17, %18, %19, %20, %21, %22, %23, %24, %25, %26, %27, %28, %29, %30, %31, %32, %33, %34, %35}, da, db, 1, 1, 1, 0, 1;\n"
    "mov.b64 da, {%40, %37};\nmov.b64 db, {%41, 8};\n"
    "wgmma.mma_async.sync.aligned.m64n72k16.f32.bf16.bf16 {%0, %1, %2, %3, %4, %5, %6, %7, %8, %9, %10, %11, %12, %13, %14, %15, %16, %17, %18, %19, %20, %21, %22, %23, %24, %25, %26, %27, %28, %29, %30, %31, %32, %33, %34, %35}, da, db, 1, 1, 1, 0, 1;\n"
    "wgmma.commit_group.sync.aligned;\n"
    "@p0 bra.uni D0;\nmov.u32 n, 0;\nW0:\nmbarrier.try_wait.parity.shared::cta.b64 q, [%42], %43;\n@q bra.uni R0;\nadd.u32 n, n, 1;\nsetp.lt.u32 q, n, 8192;\n@q bra.uni W0;\nR0:\n"
    "D0:\n"
    "@p1 bra.uni D1;\nmov.u32 n, 0;\nW1:\nmbarrier.try_wait.parity.shared::cta.b64 q, [%44], %45;\n@q bra.uni R1;\nadd.u32 n, n, 1;\nsetp.lt.u32 q, n, 8192;\n@q bra.uni W1;\nR1:\n"
    "ld.volatile.shared.u32 %36, [%46];\n"
    "D1:\n"
    "}\n"
    : "+f"(d[0]), "+f"(d[1]), "+f"(d[2]), "+f"(d[3]), "+f"(d[4]), "+f"(d[5]), "+f"(d[6]), "+f"(d[7]), "+f"(d[8]),
      "+f"(d[9]), "+f"(d[10]), "+f"(d[11]), "+f"(d[12]), "+f"(d[13]), "+f"(d[14]), "+f"(d[15]), "+f"(d[16]), "+f"(d[17]),
      "+f"(d[18]), "+f"(d[19]), "+f"(d[20]), "+f"(d[21]), "+f"(d[22]), "+f"(d[23]), "+f"(d[24]), "+f"(d[25]), "+f"(d[26]),
      "+f"(d[27]), "+f"(d[28]), "+f"(d[29]), "+f"(d[30]), "+f"(d[31]), "+f"(d[32]), "+f"(d[33]), "+f"(d[34]), "+f"(d[35]),
      "=&r"(v[0])
    : "r"(ahi), "r"(dsc[0]), "r"(dsc[1]), "r"(dsc[2]), "r"(dsc[3]), "r"(bar[0]), "r"(bar[1]), "r"(bar[2]), "r"(bar[3]), "r"(adr[0]) : "memory");
}

DEVI void mbar_init(uint32_t b, int c) { asm volatile("mbarrier.init.shared::cta.b64 [%0], %1;" ::"r"(b), "r"(c)); }
DEVI void mbar_arrive(uint32_t b) { asm volatile("mbarrier.arrive.shared::cta.b64 _, [%0];" ::"r"(b) : "memory"); }
DEVI void mbar_expect(uint32_t b, uint32_t tx) {
  asm volatile("mbarrier.arrive.expect_tx.shared::cta.b64 _, [%0], %1;" ::"r"(b), "r"(tx) : "memory");
}
DEVI void mbar_wait(uint32_t b, uint32_t ph) {
  asm volatile(
      "{\n.reg .pred p;\n.reg .u32 n;\nmov.u32 n, 0;\n"
      "LW:\nmbarrier.try_wait.parity.shared::cta.b64 p, [%0], %1;\n"
      "@p bra LD;\nadd.u32 n, n, 1;\nsetp.lt.u32 p, n, 8192;\n@p bra LW;\nLD:\n}\n" ::"r"(b), "r"(ph)
      : "memory");
}
DEVI void mbar_wait2(uint32_t a, uint32_t pa, uint32_t b, uint32_t pb) {
  asm volatile(
      "{\n.reg .pred p, q;\n.reg .u32 n;\nmov.u32 n, 0;\n"
      "LW:\nmbarrier.try_wait.parity.shared::cta.b64 p, [%0], %1;\nmbarrier.try_wait.parity.shared::cta.b64 q, [%2], %3;\n"
      "and.pred p, p, q;\n@p bra LD;\nadd.u32 n, n, 1;\nsetp.lt.u32 p, n, 8192;\n@p bra LW;\nLD:\n}\n" ::"r"(a), "r"(pa), "r"(b), "r"(pb)
      : "memory");
}
DEVI bool elect() {
  uint32_t el;
  asm volatile("{\n.reg .pred p;\nelect.sync _|p, 0xffffffff;\nselp.u32 %0,1,0,p;\n}\n" : "=r"(el));
  return el;
}
DEVI void bulk_g2s(uint32_t dst, const void* src, uint32_t bytes, uint32_t bar) {
  asm volatile("cp.async.bulk.shared::cluster.global.mbarrier::complete_tx::bytes [%0], [%1], %2, [%3];" ::"r"(dst),
               "l"(src), "r"(bytes), "r"(bar)
               : "memory");
}
DEVI void bulk_g2s_pair(uint32_t dst, const void* src, uint32_t bytes, uint32_t bar) {
  asm volatile("cp.async.bulk.shared::cluster.global.mbarrier::complete_tx::bytes.multicast::cluster [%0], [%1], %2, [%3], %4;" ::"r"(dst),
               "l"(src), "r"(bytes), "r"(bar), "h"((uint16_t)3)
               : "memory");
}
DEVI void mbar_arrive_pair(uint32_t b) {
  asm volatile("mbarrier.arrive.shared::cta.b64 _, [%0];\nmbarrier.arrive.shared::cluster.b64 _, [%1];\n" ::"r"(b), "r"(b ^ 0x1000000u) : "memory");
}
DEVI void cluster_arrive() { asm volatile("barrier.cluster.arrive.relaxed.aligned;" ::: "memory"); }
DEVI void cluster_wait() { asm volatile("barrier.cluster.wait.aligned;" ::: "memory"); }
DEVI void tma3(uint32_t dst, const CUtensorMap* m, int c0, int c1, int c2, uint32_t bar) {
  asm volatile(
      "cp.async.bulk.tensor.3d.shared::cluster.global.mbarrier::complete_tx::bytes [%0], [%1, {%3,%4,%5}], [%2];" ::"r"(dst),
      "l"(m), "r"(bar), "r"(c0), "r"(c1), "r"(c2)
      : "memory");
}
DEVI constexpr uint32_t mkdesc(uint32_t addr, uint32_t lbo) { return ((addr & 0x3FFFF) >> 4) | ((lbo >> 4) << 16); }
DEVI void bar_sync(int id) { asm volatile("bar.sync %0, 128;" ::"r"(id) : "memory"); }
DEVI uint4 ld_msg(const void* p) {
  uint4 v;
  asm volatile("ld.relaxed.gpu.global.v4.u32 {%0,%1,%2,%3}, [%4];" : "=r"(v.x), "=r"(v.y), "=r"(v.z), "=r"(v.w) : "l"(p) : "memory");
  return v;
}
DEVI void st_msg(void* p, uint32_t a, uint32_t b, uint32_t c, uint32_t d) {
  asm volatile("st.relaxed.gpu.global.v4.u32 [%0], {%1,%2,%3,%4};" ::"l"(p), "r"(a), "r"(b), "r"(c), "r"(d) : "memory");
}
DEVI uint4 ld_gen(const void* p) {
  uint4 v;
  asm volatile("ld.relaxed.gpu.v4.u32 {%0,%1,%2,%3}, [%4];" : "=r"(v.x), "=r"(v.y), "=r"(v.z), "=r"(v.w) : "l"(p) : "memory");
  return v;
}
DEVI void st_gen(void* p, uint32_t a, uint32_t b, uint32_t c, uint32_t d) {
  asm volatile("st.relaxed.gpu.v4.u32 [%0], {%1,%2,%3,%4};" ::"l"(p), "r"(a), "r"(b), "r"(c), "r"(d) : "memory");
}
DEVI uint32_t ld_rlx(const void* p) {
  uint32_t v;
  asm volatile("ld.relaxed.gpu.global.u32 %0, [%1];" : "=r"(v) : "l"(p) : "memory");
  return v;
}
DEVI uint2 ld_rlx2(const void* p) {
  uint2 v;
  asm volatile("ld.relaxed.gpu.global.v2.u32 {%0,%1}, [%2];" : "=r"(v.x), "=r"(v.y) : "l"(p) : "memory");
  return v;
}
DEVI void st_rlx(void* p, uint32_t v) { asm volatile("st.relaxed.gpu.global.u32 [%0], %1;" ::"l"(p), "r"(v) : "memory"); }
#define spin_guard(n) if (++n > (1u << 16)) break
DEVI void wait_flags(const uint8_t* p, int word, uint32_t target) {
  uint32_t n = 0;
  p += 4 * word;
  _Pragma("unroll 1") while (__any_sync(0xffffffffu, (int)(ld_rlx(p) - target) < 0)) spin_guard(n);
  asm volatile("fence.acquire.gpu;" ::: "memory");
  asm volatile("fence.proxy.async.global;" ::: "memory");
}
DEVI void bulk_s2g(void* dst, uint32_t src, uint32_t bytes) {
  asm volatile("cp.async.bulk.global.shared::cta.bulk_group [%0], [%1], %2;" ::"l"(dst), "r"(src), "r"(bytes) : "memory");
}
#define ABL 0
DEVI void l2_prefetch(const void* p, uint32_t bytes) { if (!(ABL & 2)) asm volatile("cp.async.bulk.prefetch.L2.global [%0], %1;" ::"l"(p), "r"(bytes) : "memory"); }
DEVI void fence_async_smem() { asm volatile("fence.proxy.async.shared::cta;" ::: "memory"); }
DEVI void tma2(uint32_t dst, const CUtensorMap* m, int c0, int c1, uint32_t bar) {
  asm volatile("cp.async.bulk.tensor.2d.shared::cluster.global.mbarrier::complete_tx::bytes [%0], [%1, {%3,%4}], [%2];" ::"r"(dst),
               "l"(m), "r"(bar), "r"(c0), "r"(c1) : "memory");
}
DEVI void stsm4(uint32_t a, uint32_t r0, uint32_t r1, uint32_t r2, uint32_t r3) {
  asm volatile("stmatrix.sync.aligned.m8n8.x4.shared.b16 [%0], {%1,%2,%3,%4};" ::"r"(a), "r"(r0), "r"(r1), "r"(r2), "r"(r3) : "memory");
}
DEVI void stsm2(uint32_t a, uint32_t r0, uint32_t r1) {
  asm volatile("stmatrix.sync.aligned.m8n8.x2.shared.b16 [%0], {%1,%2};" ::"r"(a), "r"(r0), "r"(r1) : "memory");
}
DEVI uint32_t mbar_test(uint32_t b, uint32_t ph) {
  uint32_t ok;
  asm volatile("{\n.reg .pred p;\nmbarrier.test_wait.parity.shared::cta.b64 p, [%1], %2;\nselp.u32 %0,1,0,p;\n}\n"
               : "=r"(ok) : "r"(b), "r"(ph) : "memory");
  return ok;
}
DEVI void st_rlx2(void* p, uint32_t a, uint32_t b) {
  asm volatile("{\n.reg .b64 v;\nmov.b64 v, {%1,%2};\nst.relaxed.gpu.global.b64 [%0], v;\n}\n" ::"l"(p), "r"(a), "r"(b) : "memory");
}
DEVI float selp(int c, float a, float b) {
  float y;
  asm("{\n.reg .pred p;\nsetp.ne.s32 p, %3, 0;\nselp.f32 %0, %1, %2, p;\n}\n" : "=f"(y) : "f"(a), "f"(b), "r"(c));
  return y;
}
DEVI float ex2(float x) { float y; asm("ex2.approx.ftz.f32 %0, %1;" : "=f"(y) : "f"(x)); return y; }
DEVI float rcp(float x) { float y; asm("rcp.approx.ftz.f32 %0, %1;" : "=f"(y) : "f"(x)); return y; }
DEVI float sqrt_a(float x) { float y; asm("sqrt.approx.ftz.f32 %0, %1;" : "=f"(y) : "f"(x)); return y; }
DEVI void ldsm4t(uint32_t* r, uint32_t a) {
  asm volatile("ldmatrix.sync.aligned.m8n8.x4.trans.shared.b16 {%0,%1,%2,%3}, [%4];"
               : "=r"(r[0]), "=r"(r[1]), "=r"(r[2]), "=r"(r[3]) : "r"(a) : "memory");
}
DEVI void ldsm4(uint32_t* r, uint32_t a) {
  asm volatile("ldmatrix.sync.aligned.m8n8.x4.shared.b16 {%0,%1,%2,%3}, [%4];"
               : "=r"(r[0]), "=r"(r[1]), "=r"(r[2]), "=r"(r[3]) : "r"(a) : "memory");
}
DEVI uint32_t lds16(uint32_t a) {
  uint32_t v;
  asm volatile("ld.shared.u16 %0, [%1];" : "=r"(v) : "r"(a) : "memory");
  return v;
}
DEVI void sts16(uint32_t a, uint32_t x) { asm volatile("st.shared.u16 [%0], %1;" ::"r"(a), "r"(x) : "memory"); }
DEVI uint4 ldg128(const void* p) {
  uint4 v;
  asm volatile("ld.global.nc.v4.u32 {%0,%1,%2,%3}, [%4];" : "=r"(v.x), "=r"(v.y), "=r"(v.z), "=r"(v.w) : "l"(p));
  return v;
}
DEVI uint2 ldg64(const void* p) {
  uint2 v;
  asm volatile("ld.global.nc.v2.u32 {%0,%1}, [%2];" : "=r"(v.x), "=r"(v.y) : "l"(p));
  return v;
}
DEVI uint32_t ldg32(const void* p) {
  uint32_t v;
  asm volatile("ld.global.nc.u32 %0, [%1];" : "=r"(v) : "l"(p));
  return v;
}
DEVI uint4 ldcg128(const void* p) {
  uint4 v;
  asm volatile("ld.global.cg.v4.u32 {%0,%1,%2,%3}, [%4];" : "=r"(v.x), "=r"(v.y), "=r"(v.z), "=r"(v.w) : "l"(p) : "memory");
  return v;
}
DEVI uint2 ldcg64(const void* p) {
  uint2 v;
  asm volatile("ld.global.cg.v2.u32 {%0,%1}, [%2];" : "=r"(v.x), "=r"(v.y) : "l"(p) : "memory");
  return v;
}
DEVI uint32_t ldcg32(const void* p) {
  uint32_t v;
  asm volatile("ld.global.cg.u32 %0, [%1];" : "=r"(v) : "l"(p) : "memory");
  return v;
}
DEVI void stg128(void* p, uint32_t a, uint32_t b, uint32_t c, uint32_t d) {
  asm volatile("st.global.v4.u32 [%0], {%1,%2,%3,%4};" ::"l"(p), "r"(a), "r"(b), "r"(c), "r"(d) : "memory");
}
DEVI void stg32(void* p, uint32_t a) { asm volatile("st.global.u32 [%0], %1;" ::"l"(p), "r"(a) : "memory"); }
DEVI uint4 lds128(uint32_t a) {
  uint4 v;
  asm volatile("ld.shared.v4.u32 {%0,%1,%2,%3}, [%4];" : "=r"(v.x), "=r"(v.y), "=r"(v.z), "=r"(v.w) : "r"(a) : "memory");
  return v;
}
DEVI uint2 lds64(uint32_t a) {
  uint2 v;
  asm volatile("ld.shared.v2.u32 {%0,%1}, [%2];" : "=r"(v.x), "=r"(v.y) : "r"(a) : "memory");
  return v;
}
DEVI uint32_t lds32(uint32_t a) {
  uint32_t v;
  asm volatile("ld.shared.u32 %0, [%1];" : "=r"(v) : "r"(a) : "memory");
  return v;
}
DEVI void lds64f_if(bool p, float& a, float& b, uint32_t addr) {
  asm volatile("{\n.reg .pred p;\nsetp.ne.u32 p, %3, 0;\n@p ld.shared.v2.f32 {%0,%1}, [%2];\n}\n"
               : "+f"(a), "+f"(b) : "r"(addr), "r"((uint32_t)p) : "memory");
}
DEVI float ldsf(uint32_t a) { return __uint_as_float(lds32(a)); }
DEVI void sts128(uint32_t a, uint32_t x, uint32_t y, uint32_t z, uint32_t w) {
  asm volatile("st.shared.v4.u32 [%0], {%1,%2,%3,%4};" ::"r"(a), "r"(x), "r"(y), "r"(z), "r"(w) : "memory");
}
DEVI void sts64(uint32_t a, uint32_t x, uint32_t y) { asm volatile("st.shared.v2.u32 [%0], {%1,%2};" ::"r"(a), "r"(x), "r"(y) : "memory"); }
DEVI void sts32(uint32_t a, uint32_t x) { asm volatile("st.shared.u32 [%0], %1;" ::"r"(a), "r"(x) : "memory"); }
DEVI void stsf(uint32_t a, float x) { sts32(a, __float_as_uint(x)); }
DEVI uint32_t packbf(float lo, float hi) {
  uint32_t r;
  asm("cvt.rn.bf16x2.f32 %0, %1, %2;" : "=r"(r) : "f"(hi), "f"(lo));
  return r;
}
DEVI uint32_t nz(uint32_t w) { uint32_t y; asm("max.u32 %0, %1, 1;" : "=r"(y) : "r"(w)); return y; }
DEVI float blo(uint32_t w) { return __uint_as_float(w << 16); }
DEVI float bhi(uint32_t w) { return __uint_as_float(w & 0xffff0000u); }
DEVI float rbf(float x) { return __uint_as_float(packbf(0.f, x)); }
DEVI float shx(float v, int m) { return __shfl_xor_sync(0xffffffffu, v, m); }
DEVI float quad_sum(float v) { v += shx(v, 1); v += shx(v, 2); return v; }
DEVI uint32_t movm(uint32_t a) {
  uint32_t d;
  asm volatile("movmatrix.sync.aligned.m8n8.trans.b16 %0, %1;" : "=r"(d) : "r"(a));
  return d;
}
DEVI void mma16(float* d, uint32_t a0, uint32_t a1, uint32_t a2, uint32_t a3, uint32_t b0, uint32_t b1) {
  asm("mma.sync.aligned.m16n8k16.row.col.f32.bf16.bf16.f32 {%0,%1,%2,%3},{%4,%5,%6,%7},{%8,%9},{%0,%1,%2,%3};"
      : "+f"(d[0]), "+f"(d[1]), "+f"(d[2]), "+f"(d[3])
      : "r"(a0), "r"(a1), "r"(a2), "r"(a3), "r"(b0), "r"(b1));
}
DEVI void mma8z(float* d, uint32_t a0, uint32_t a1, uint32_t b0) {
  asm("mma.sync.aligned.m16n8k8.row.col.f32.bf16.bf16.f32 {%0,%1,%2,%3},{%4,%5},{%6},{%7,%7,%7,%7};"
      : "=f"(d[0]), "=f"(d[1]), "=f"(d[2]), "=f"(d[3])
      : "r"(a0), "r"(a1), "r"(b0), "f"(0.f));
}
DEVI void mma8(float* d, uint32_t a0, uint32_t a1, uint32_t b0) {
  asm("mma.sync.aligned.m16n8k8.row.col.f32.bf16.bf16.f32 {%0,%1,%2,%3},{%4,%5},{%6},{%0,%1,%2,%3};"
      : "+f"(d[0]), "+f"(d[1]), "+f"(d[2]), "+f"(d[3])
      : "r"(a0), "r"(a1), "r"(b0));
}
DEVI void mma16z(float* d, uint32_t a0, uint32_t a1, uint32_t a2, uint32_t a3, uint32_t b0, uint32_t b1) {
  asm("mma.sync.aligned.m16n8k16.row.col.f32.bf16.bf16.f32 {%0,%1,%2,%3},{%4,%5,%6,%7},{%8,%9},{%10,%10,%10,%10};"
      : "=f"(d[0]), "=f"(d[1]), "=f"(d[2]), "=f"(d[3])
      : "r"(a0), "r"(a1), "r"(a2), "r"(a3), "r"(b0), "r"(b1), "f"(0.f));
}
DEVI void mma16a(float* d, const uint32_t* a, uint32_t b0, uint32_t b1) { mma16(d, a[0], a[1], a[2], a[3], b0, b1); }
DEVI float ln_sd(float var) { return rbf(sqrt_a(rbf(rbf(var) + kEps))); }
DEVI int fkey(float f) { int i = __float_as_int(f); return i ^ ((i >> 31) & 0x7fffffff); }
DEVI float sigmoidf(float x) { return rcp(1.f + ex2(-1.4426950408889634f * x)); }

DEVI uint32_t probe_stage(uint32_t pa) { return lds32(pa); }
DEVI void check_stage(uint32_t pv, uint32_t fa, const uint8_t* src) {
  if (__any_sync(0xffffffffu, pv == 0)) {
    uint32_t n = 0, tid;
    asm volatile("mov.u32 %0, %%tid.x;" : "=r"(tid));
    const uint32_t fo = (tid & 96) * 8 + (tid & 16) * 64 + (tid & 15) * 16;
    fa += fo; src += fo;
#pragma unroll 1
    for (uint32_t o = 0; o < 8192;) {
      const uint4 v = ld_msg(src + o);
      sts128(fa + o, v.x, v.y, v.z, v.w);
      if (!__any_sync(0xffffffffu, min(min(v.x, v.y), min(v.z, v.w)) == 0) || ++n > (1u << 16)) o += 2048;
    }
    fence_async_smem();
    __syncwarp();
  }
}

struct Params {
  const uint8_t *x, *wqkv, *wo, *wr, *wg, *wu, *wd;
  uint8_t* out;
  Scratch* g;
};

struct Maps { CUtensorMap wq, x, wo, xr, wg, wu, out; };
#define QPRE 2
#define FDEPTH 2
#define PFSTART 700
#define PFPRE 0
#define PFPER 3
#define PFNS 200
#define XSTART 100
#define XSTEP 300
#define PKSTEP 350
#define WPOLL 300
#define CSROUND 0
#define XLROUND 0
#define CLNS 20
#define FSTART 4000
#define XLSTART 3000
#define WGAP0 0
#define XGAP 150
#define WEARLY 1

__global__ void __cluster_dims__(2, 1, 1) __launch_bounds__(512, 1) fused_kernel(const Params p, const __grid_constant__ Maps tm) {
  extern __shared__ __align__(1024) uint8_t smem_raw[];
  constexpr uint32_t sbd = 1024;
  int cta;
  uint32_t rank;
  {
    asm volatile("mov.u32 %0, %%cluster_ctarank;" : "=r"(rank));
    const int c = blockIdx.x >> 1, t = c - 4, u = c - 36, uq = (u * 37) >> 8;
    const int gpc = c < 4 ? 0 : c < 36 ? t & 7 : 1 + u - 7 * uq, idx = c < 4 ? 4 + c : c < 36 ? t >> 3 : 4 + uq;
    cta = __shfl_sync(0xffffffffu, (2 * gpc + (int)rank) * 8 + idx, 0);
  }
  const uint32_t sb = sbd | (rank << 24);
  if ((uint32_t)__cvta_generic_to_shared(smem_raw) != sb) return;
  const int m = cta >> 3, r = cta & 7;
  const int warp = __shfl_sync(0xffffffffu, (int)(threadIdx.x >> 5), 0);
  const int lane = threadIdx.x & 31;
  uint8_t* const gb = reinterpret_cast<uint8_t*>(p.g);
  auto pack = [&]() -> uint32_t {
    const uint32_t t0 = clock();
    const uint32_t tp = sb + SM_W + 3 * WSTAGE + warp * 2304, bar = sb + SM_PART + 8 * warp;
    uint8_t* flag = GA(flagP, (12 * r + warp) * 128 + 4 * m);
    if (warp > 1) {
      asm volatile("bar.sync 4, 512;" ::: "memory");
      cluster_arrive();
      while ((uint32_t)clock() - t0 < (warp - 1) * PKSTEP) {}
    }
    if (elect()) {
      mbar_init(bar, 1);
      asm volatile("fence.mbarrier_init.release.cluster;" ::: "memory");
      mbar_expect(bar, 2304);
      if (warp < 9) tma3(tp, &tm.wq, 72 * r, 64 * warp + 8 * (m >> 1), m & 1, bar);
      else tma2(tp, &tm.wo, 72 * r, 192 * (warp - 9) + 24 * (m >> 1) + 8 * (m & 1), bar);
    }
    __syncwarp();
    if (lane == 0) st_rlx(flag, 0);
    if (warp <= 1) { asm volatile("bar.sync 4, 512;" ::: "memory"); cluster_arrive(); }
    mbar_wait(sb + B_EP, 0);
    const uint32_t epoch = lds32(sb + SM_EP);
    uint8_t* dst = GC(wpack, (r * 12 + warp) * WSTAGE + (27 * (m >> 1) + 14 * (m & 1)) * 128 + lane * 16);
    mbar_wait(bar, 0);
#pragma unroll
    for (int i = 0; i < 4; i++) {
      const int u = 4 * i + (lane >> 3) + 5 * (m & 1);
      const uint4 x = lds128(tp + (lane & 7) * 144 + u * 16 + (u >= 9 ? 1008 : 0));
      if (u < 14 + 4 * (m & 1)) stg128(dst + 512 * i, nz(x.x), nz(x.y), nz(x.z), nz(x.w));
    }
    if (lane == 0) st_rlx(flag, epoch);
    fence_async_smem();
    __syncwarp();
    if (elect()) asm volatile("mbarrier.inval.shared::cta.b64 [%0];" ::"r"(bar) : "memory");
    cluster_wait();
    return epoch;
  };

  if (warp >= 12) {
    asm volatile("setmaxnreg.dec.sync.aligned.u32 24;");
    uint32_t e0 = 0;
    if (warp == 15) e0 = ld_rlx(GA(epoch, 32 * cta));
    if (elect()) {
#pragma unroll
      for (int i = 0; i < NBAR; i++)
        if (warp - 12 == (i * 4) / NBAR)
          mbar_init(sb + SM_BAR + 8 * i, i < 4 ? 1 : i < 8 ? 16 : i < 16 ? 2 : i == (B_PKF - SM_BAR) / 8 ? 8 : i < NBAR4 ? 4 : 1);
      asm volatile("fence.mbarrier_init.release.cluster;" ::: "memory");
    }
    __syncwarp();
    asm volatile("bar.sync 4, 512;" ::: "memory");
    cluster_arrive();
    if (warp == 12) {
      mbar_wait(sb + B_EP, 0);
      cluster_wait();
      const uint32_t epoch = lds32(sb + SM_EP);
      const uint32_t half = (m & 1) * (WSTAGE / 2);
      const uint8_t* src = GC(wpack, r * 12 * WSTAGE + half);
      __nanosleep(WPOLL);
#pragma unroll 1
      for (int g = 0; g < 24; g++) {
        const uint32_t slot = g & 3;
        if (g < 12) wait_flags(GA(flagP, (12 * r + g) * 128), lane & 15, epoch);
        if (g == 0) TRL(3, 0);
        if (g == 3) mbar_wait(sb + B_PKF, 0);
        if (g >= 4) mbar_wait(sb + B_WEMPTY + 8 * slot, ((g >> 2) - 1) & 1);
        if (elect()) {
          const uint32_t bar = sb + (g < 12 ? B_WL : B_WFULL) + 8 * slot;
          mbar_expect(bar, WSTAGE);
          bulk_g2s_pair(sb + SM_W + slot * WSTAGE + half, src + (g >= 12 ? g - 12 : g) * WSTAGE, WSTAGE / 2, bar);
        }
      }
    } else if (warp <= 14) {
      const int w = warp - 13;
      const uint32_t full = sb + B_XFULL + 32 * w, empty = sb + B_XEMPTY + 32 * w, ring = sb + SM_X + w * 4 * XSTAGE;
      mbar_wait(sb + B_EP, 0);
      cluster_wait();
      const uint32_t epoch = lds32(sb + SM_EP);
      if (lane < 4) st_rlx(GA(flagX, 128 * (2 * m + w) + 16 * r + 4 * lane), epoch * 4);
#pragma unroll 1
      for (int gemm = 0; gemm < 4; gemm++) {
        const uint8_t* src = GC(act, (gemm - 1) * ACT + (2 * m + w) * 73728);
        if (gemm & 1) {
          mbar_wait(empty, 0);
          if (elect()) {
            mbar_expect(sb + B_RES + 8 * w, 9216);
            if (gemm == 1) tma3(ring, &tm.xr, 72 * r, w, m * 64, sb + B_RES + 8 * w);
            else bulk_g2s(ring, GC(act, ACT + (2 * m + w) * 73728 + r * 9216), 9216, sb + B_RES + 8 * w);
          }
        }
        if (gemm > 0) {
          mbar_wait(gemm & 1 ? sb + B_RC + 8 * w : empty, gemm & 1 ? gemm >> 1 : 1);
          TRL(3, 11 + w * 4 + gemm);
          wait_flags(GA(flagX, 128 * (2 * m + w)), lane, epoch * 4 + gemm);
          TRL(3, 1 + w * 4 + gemm);
        }
        if (gemm & 1) {
          if (elect()) {
#pragma unroll
            for (int s = 0; s < 9; s++) {
              if (s >= 4) mbar_wait(empty + 8 * (s & 3), s == 4);
              mbar_expect(full + 8 * (s & 3), XSTAGE);
              bulk_g2s(ring + (s & 3) * XSTAGE, src + s * XSTAGE, XSTAGE, full + 8 * (s & 3));
              mbar_arrive(full + 8 * (s & 3));
            }
          }
          __syncwarp();
          continue;
        }
        bool gate = gemm == 2;
#pragma unroll 1
        for (int s = 0; s < (gemm == 2 ? 11 : 9); s++) {
          const uint32_t slot = s & 3;
          if (gemm == 0 && s < 4) __nanosleep(s ? XSTEP : XSTART);
          if (gemm == 2 && s > 0 && s < 4) __nanosleep(XGAP);
          if (s >= 4) mbar_wait(empty + 8 * slot, s >> 3);
          const bool hold = gate && s >= 4 && mbar_test(sb + B_WANT, 0);
          if (lane == 0 && !hold && (gemm != 2 || (s & ~1) != 2)) mbar_arrive(full + 8 * (gemm == 2 && s >= 4 ? (s - 2) & 3 : slot));
          if (s < 9 && elect()) {
            mbar_expect(full + 8 * slot, XSTAGE);
            if (gemm == 0) tma3(ring + slot * XSTAGE, &tm.x, s * 64, w, m * 64, full + 8 * slot);
            else bulk_g2s(ring + slot * XSTAGE, src + s * XSTAGE, XSTAGE, full + 8 * slot);
          }
          if (hold) {
            mbar_wait(sb + B_DONE, 0);
            gate = false;
            if (lane == 0) mbar_arrive(full + 8 * ((s - 2) & 3));
          }
        }
      }
    } else {
      const uint32_t epoch = e0 + 1;
      if (lane == 0) {
        sts32(sb + SM_EP, epoch);
        mbar_arrive(sb + B_EP);
      }
      __syncwarp();
      cluster_wait();
      int pi = lane;
      auto prefetch = [&]() {
        const uint8_t* pp = pi < 648 ? ((cta & 1) ? p.wu : p.wg) + (uint32_t)(((pi / 72) * 63 + (cta >> 1)) * 9216 + pi * 128)
                                     : p.wd + (uint32_t)((cta * 324 + pi - 648) * 128);
        if (pi < 972 && !(ABL & 2)) asm volatile("prefetch.global.L2 [%0];" ::"l"(pp));
        pi += 32;
      };
      __nanosleep(PFSTART);
#pragma unroll 1
      for (int i = 0; i < PFPRE; i++) { prefetch(); __nanosleep(PFNS); }
      uint32_t ph = 0;
#pragma unroll 1
      for (int g = 0; g < 12; g++) {
        const uint32_t slot = g & 3;
#pragma unroll 1
        for (int n = 0; n < 4096; n++) {
          mbar_wait(sb + B_WL + 8 * slot, (ph >> slot) & 1);
          ph ^= 1 << slot;
          const uint32_t a = sb + SM_W + slot * WSTAGE + lane * 128 + (lane & 3) * 32 + (lane >> 2) * 4;
          uint32_t mn = lds32(a + (lane < 24 ? 6 * 4096 : 0));
#pragma unroll
          for (int u = 0; u < 6; u++) mn = min(mn, lds32(a + u * 4096));
          if (!__any_sync(0xffffffffu, mn == 0) || (ABL & 32)) break;
          fence_async_smem();
          __syncwarp();
          if (elect()) {
            mbar_expect(sb + B_WL + 8 * slot, WSTAGE);
            bulk_g2s(sb + SM_W + slot * WSTAGE, GC(wpack, (r * 12 + g) * WSTAGE), WSTAGE, sb + B_WL + 8 * slot);
          }
        }
        if (lane == 0) mbar_arrive(sb + B_WFULL + 8 * slot);
#pragma unroll 1
        for (int i = 0; i < PFPER; i++) prefetch();
      }
      TRL(3, 22);
      mbar_wait(sb + B_FD, 0);
      TRL(3, 20);
      if (elect()) {
        mbar_expect(sb + B_WD, (ABL & 64) ? 0 : 41472);
#pragma unroll 4
        for (int i = 0; i < 36; i++)
          if (!(ABL & 64)) bulk_g2s(sb + SM_WD + i * WDP, p.wd + (uint32_t)(cta * 36 + i) * 1152u, 1152, sb + B_WD);
      }
      __syncwarp();
      TRL(3, 21);
      {
        const uint32_t epoch = e0, h = (lane >> 1) * 128 + (lane & 1) * 16;
        mbar_wait(sb + B_OS, 0);
#pragma unroll 1
        for (int i = cta; i < 1296; i += 128) { stg128(GC(wpack, i * 2048 + (lane & 6) * 16 + h), 0, 0, 0, 0); __nanosleep(CLNS); }
#pragma unroll 1
        for (int i = 0; i < 5; i++) {
          stg128(GC(halo, (cta * 5 + i) * 2048 + h), 0, 0, 0, 0);
          if (i < 4 || lane < 16) stg128(GC(candrow, cta * 2304 + i * 512 + lane * 16), 0, 0, 0, 0);
          stg128(GC(act, (cta * 27 + i) * 2048 + 96 + h), 0, 0, 0, 0);
          __nanosleep(CLNS);
        }
        mbar_wait(sb + B_OS, 1);
#pragma unroll 1
        for (int i = 5; i < 27; i++) { stg128(GC(act, (cta * 27 + i) * 2048 + 96 + h), 0, 0, 0, 0); __nanosleep(CLNS); }
      }
      TRL(3, 23);
    }
  } else if (warp >= 8) {
    asm volatile("setmaxnreg.inc.sync.aligned.u32 200;");
    const int sw = warp - 8, s = threadIdx.x - 256;
    const uint32_t t0 = clock();
    const uint32_t epoch = pack();
    TR(2, 0);
    auto ffn_round = [&](int u) {
      const uint32_t bar = sb + B_FF + 8 * (u % FDEPTH), dst = sb + SM_WD + (u % FDEPTH) * FSLOT;
      if (ABL & 4) { mbar_arrive(bar); return; }
      mbar_expect(bar, 12288);
      tma2(dst, &tm.wg, ((cta * 72) >> 5) << 4, 64 * u, bar);
      tma2(dst + FSLOT / 2, &tm.wu, ((cta * 72) >> 5) << 4, 64 * u, bar);
    };
    const int xi = 8 * r + 4 * (sw >> 1) + (lane >> 3);
    uint4 xv[9];
    uint32_t wr[9];
        {
          const uint8_t* xsrc = p.x + (uint32_t)((128 * m + 2 * xi + (sw & 1)) * 1152 + (lane & 7) * 16);
#pragma unroll
          for (int u = 0; u < 9; u++) xv[u] = ldg128(xsrc + u * 128);
#pragma unroll
          for (int u = 0; u < 9; u++) wr[u] = sw == 0 ? ldg32(p.wr + 128 * u + 4 * lane) : 0u;
        }
    {
      asm volatile("bar.sync 15, 384;" ::: "memory");
      const int u = (s >> 3) + 5 * (m & 1);
      uint4 v[9];
#pragma unroll
      for (int g = 0; g < 9; g++) v[g] = lds128(sb + SM_W + 3 * WSTAGE + g * 2304 + u * 16 + (u >= 9 ? 1008 : 0) + (s & 7) * 144);
      fence_async_smem();
      __syncwarp();
      if (lane == 0) mbar_arrive_pair(sb + B_PKF);
      float a[8] = {};
#pragma unroll
      for (int g = 0; g < 9; g++) {
        a[0] += blo(v[g].x); a[1] += bhi(v[g].x); a[2] += blo(v[g].y); a[3] += bhi(v[g].y);
        a[4] += blo(v[g].z); a[5] += bhi(v[g].z); a[6] += blo(v[g].w); a[7] += bhi(v[g].w);
      }
      const bool b4 = s & 4, b2 = s & 2;
      float b[4];
#pragma unroll
      for (int e = 0; e < 4; e++) b[e] = (b4 ? a[4 + e] : a[e]) + shx(b4 ? a[e] : a[4 + e], 4);
      float c0 = (b2 ? b[2] : b[0]) + shx(b2 ? b[0] : b[2], 2), c1 = (b2 ? b[3] : b[1]) + shx(b2 ? b[1] : b[3], 2);
      c0 += shx(c0, 1); c1 += shx(c1, 1);
      if (!(s & 1) && (s >> 3) < 14 - (m & 1))
        st_rlx2(GA(colpart, (8 * r + (m >> 1)) * 864 + 14 * (m & 1) * 32 + 4 * s), __float_as_uint(c0), (__float_as_uint(c1) & ~15u) | (epoch & 15));
      TR(2, 1);
    }
    if (sw == 0) {
      while ((uint32_t)clock() - t0 < FSTART) {}
      if (elect()) {
#pragma unroll
        for (int u = 0; u < FDEPTH; u++) ffn_round(u);
      }
      __syncwarp();
    }
        {
          float sum = 0.f;
#pragma unroll
          for (int u = 0; u < 9; u++)
            sum += (blo(xv[u].x) + bhi(xv[u].x)) + (blo(xv[u].y) + bhi(xv[u].y)) + (blo(xv[u].z) + bhi(xv[u].z)) + (blo(xv[u].w) + bhi(xv[u].w));
          sum += shx(sum, 1); sum += shx(sum, 2); sum += shx(sum, 4);
          const float mu = sum * (1.f / kD);
          float q = 0.f;
#pragma unroll
          for (int u = 0; u < 9; u++) {
            const uint32_t ww[4] = {xv[u].x, xv[u].y, xv[u].z, xv[u].w};
#pragma unroll
            for (int e = 0; e < 4; e++) {
              const float d0 = blo(ww[e]) - mu, d1 = bhi(ww[e]) - mu;
              q = fmaf(d0, d0, q); q = fmaf(d1, d1, q);
            }
          }
          q += shx(q, 1); q += shx(q, 2); q += shx(q, 4);
          const float rho = rcp(ln_sd(q * (1.f / kD)));
          if ((lane & 7) == 0) st_msg(GA(stats0, 16 * (128 * m + 64 * (sw & 1) + xi)), __float_as_uint(rho), __float_as_uint(mu), 0, epoch);
          if (sw == 0) {
            float wsum = 0.f;
#pragma unroll
            for (int u = 0; u < 9; u++) wsum += blo(wr[u]) + bhi(wr[u]);
#pragma unroll
            for (int o = 1; o < 32; o <<= 1) wsum += shx(wsum, o);
            if (lane == 0) stsf(sb + SM_WSUM, wsum);
          }
          TR(2, 3);
        }
    uint32_t WF[9][4][4];
    {
      const int g = lane >> 2, t = lane & 3;
      const uint32_t c0 = (cta * 72) & 31, ra = 2 * (lane & 6) + (lane & 1) + 2 * ((lane >> 4) ^ ((lane >> 2) & 1));
      const uint32_t fa = sb + SM_WD + (16 * sw + ra) * 128 + ((((c0 + 8) >> 4) + ((lane >> 3) & 1)) << 4);
      const uint32_t fa0 = fa ^ ((ra & 7) << 4), fa1 = (fa + 32) ^ ((ra & 7) << 4);
      const uint32_t rl = 2 * (g & 6) + (g & 1) + 2 * (g >> 2);
      const uint32_t fl = sb + SM_WD + 16 * sw * 128 + (t >> 1) * (FSLOT / 2) + c0 + 64 * (~cta & 1) + 4 * (t & 1);
      const uint32_t fl0 = (fl + rl * 128) ^ ((rl & 7) << 4), fl1 = (fl + (rl ^ 2) * 128) ^ (((rl ^ 2) & 7) << 4);
#pragma unroll
      for (int i = 0; i < 9; i++) {
        mbar_wait(sb + B_FF + 8 * (i % FDEPTH), (i / FDEPTH) & 1);
#pragma unroll
        for (int e = 0; e < 4; e++) ldsm4t(WF[i][e], ((e & 1) ? fa1 : fa0) + (e >> 1) * (FSLOT / 2) + (i % FDEPTH) * FSLOT);
        const uint32_t v0 = lds32(fl0 + (i % FDEPTH) * FSLOT), v1 = lds32(fl1 + (i % FDEPTH) * FSLOT);
        if (i + FDEPTH < 9 || i == 8) {
          fence_async_smem();
          bar_sync(3);
          if (sw == 0 && elect()) {
            if (i < 8) ffn_round(i + FDEPTH);
            else mbar_arrive(sb + B_FD);
          }
        }
        sts64(sb + SM_LEFT + i * 1024 + s * 8, movm(v0), movm(v1));
        if (i == CSROUND) {
          TR(2, 21);
          float c0, c1;
          uint4 s0;
          uint32_t nc = 0;
          _Pragma("unroll 1") while (true) {
            s0 = ld_msg(GA(stats0, 16 * (128 * m + s)));
            uint32_t bad = s0.w != epoch;
            c0 = 0.f; c1 = 0.f;
#pragma unroll
            for (int mm = 0; mm < 8; mm++) {
              const uint2 v = ld_rlx2(GA(colpart, 8 * 864 * r + 8 * min(s, 107)) + mm * 864);
              c0 += __uint_as_float(v.x); c1 += __uint_as_float(v.y & ~15u);
              bad |= v.y ^ epoch;
            }
            if (!__any_sync(0xffffffffu, bad & 15)) break;
            spin_guard(nc);
          }
          if (s < 108) {
            const uint32_t hi = packbf(c0, c1);
            sts32(sb + SM_COLSUM + 32 * (s >> 2) + 4 * (s & 3), hi);
            sts32(sb + SM_COLSUM + 32 * (s >> 2) + 4 * (s & 3) + 16, packbf(c0 - blo(hi), c1 - bhi(hi)));
          }
          sts32(sb + SM_ROWC + 4 * s, s0.x);
          sts64(sb + SM_ROWM + 8 * s, s0.y, __float_as_uint(1.f));
          fence_async_smem();
          __syncwarp();
          if (lane == 0) mbar_arrive(sb + B_COLSUM);
          TR(2, 13);
        }
      }
      TR(2, 4);
    }
    {
      const uint32_t y = epoch * 2 - 1;
      st_msg(GA(ypart, (s >> 1) * 4096 + cta * 32 + (s & 1) * 16), y, y, y, y);
      if (s < 16) {
        st_msg(GA(ypart, (64 + (s >> 1)) * 4096 + cta * 32 + (s & 1) * 16), y, y, y, y);
        st_rlx(GA(fixmsg, 1024 * r + 64 * m + 4 * s), epoch - 1);
      }
      if (s < 64 && cta < 72) st_rlx(GA(x2msg, (s >> 3) * 2304 + 32 * cta + 4 * (s & 7)), epoch - 1);
    }
#pragma unroll 1
    for (int L = 0; L < 2; L++) {
      const uint32_t tag = epoch * 2 + L;
      int s0 = __shfl_sync(0xffffffffu, (int)threadIdx.x + L, threadIdx.x & 31) - L - 256;
#define RELANE asm volatile("" : "+r"(s0)); const int s = s0, lane = s & 31, g = lane >> 2, t = lane & 3; (void)g; (void)t
      RELANE;
      const uint8_t* crow = GC(candrow, L * 128 * 1152);
      const uint8_t* cptr = GA(cand, (8 * L + r) * 2048 + 16 * s);
      asm volatile("" : "+l"(crow), "+l"(cptr));
      mbar_wait2(sb + B_WD, 0, sb + B_EPI, L);
      uint32_t win;
      {
        uint32_t c, n = 0;
        _Pragma("unroll 1") while (true) {
          c = ld_rlx(cptr) ^ (epoch & 0x7f);
          if (!__any_sync(0xffffffffu, c & 0x7f)) break;
          spin_guard(n);
        }
        const int wm = __reduce_max_sync(0xffffffffu, (int)(c | s));
        if (lane == 0) sts32(sb + SM_RED + 4 * sw, wm);
        bar_sync(3);
        const uint4 v = lds128(sb + SM_RED);
        win = max(max((int)v.x, (int)v.y), max((int)v.z, (int)v.w));
      }
      crow += (win & 127) * 1152;
      if (s == 0) {
        if (L == 0 && WEARLY) mbar_arrive(sb + B_WANT);
        sts32(sb + SM_SEL + 4 * L, win & 0x7ff);
        mbar_arrive(sb + B_IDX + 8 * L);
      }
      TR(2, 5 + 10 * L);
      uint2 xw[9];
      {
        if (sw < 3) {
          uint4 v;
          uint32_t n = 0;
          _Pragma("unroll 1") while (true) {
            v = ld_msg(crow + 16 * min(s, 71));
            if (!__any_sync(0xffffffffu, min(min(v.x, v.y), min(v.z, v.w)) == 0)) break;
            spin_guard(n);
          }
          if (s < 72) sts128(sb + SM_PART + 16 * s, v.x, v.y, v.z, v.w);
        }
        bar_sync(3);
#pragma unroll
        for (int i = 0; i < 9; i++) xw[i] = lds64(sb + SM_PART + 128 * i + 32 * sw + 8 * t);
      }
      if (L == 0 && !WEARLY && s == 0) mbar_arrive(sb + B_WANT);
      TR(2, 6 + 10 * L);
      {
        float a[4][4] = {}, al[4] = {};
#pragma unroll
        for (int i = 0; i < 9; i++) {
          const uint2 wl = lds64(sb + SM_LEFT + s * 8 + i * 1024);
#pragma unroll
          for (int e = 0; e < 4; e++) mma16a(a[e], WF[i][e], xw[i].x, xw[i].y);
          mma8(al, wl.x, wl.y, (g & 1) ? xw[i].y : xw[i].x);
        }
        bar_sync(3);
        const uint32_t pp = sb + SM_PART + ((t >> 1) * 36 + 16 * (t & 1) + g + 4 * (cta & 1)) * 16 + 4 * sw;
        stsf(pp, selp(t & 2, selp(t & 1, a[3][0], a[2][0]), selp(t & 1, a[1][0], a[0][0])));
        stsf(pp + 128, selp(t & 2, selp(t & 1, a[3][2], a[2][2]), selp(t & 1, a[1][2], a[0][2])));
        stsf(sb + SM_PART + ((g >> 2) * 36 + 32 * (~cta & 1) + (g & 3)) * 16 + 4 * sw, al[0] + al[3]);
      }
      {
        RELANE;
        const uint32_t wa = sb + SM_WD + 288 * sw + ((lane >> 3) & 1) * 16 + ((lane & 7) + 8 * (lane >> 4)) * WDP;
        const uint32_t wb = sb + SM_WD + 288 * sw + ((lane >> 3) & 1) * 16 + (32 + (lane & 3)) * WDP;
        uint32_t f[4][4];
#pragma unroll
        for (int u = 0; u < 4; u++) ldsm4t(f[u], wa + 32 * (u & 1) + (u >> 1) * 16 * WDP);
        bar_sync(3);
        {
          float hv[2];
#pragma unroll
          for (int e = 0; e < 2; e++) {
            const uint32_t pp = sb + SM_PART + 16 * (e ? 32 + t : lane);
            const uint4 pg = lds128(pp), pu = lds128(pp + 576);
            const float gp = rbf((__uint_as_float(pg.x) + __uint_as_float(pg.y)) + (__uint_as_float(pg.z) + __uint_as_float(pg.w)));
            const float u = rbf((__uint_as_float(pu.x) + __uint_as_float(pu.y)) + (__uint_as_float(pu.z) + __uint_as_float(pu.w)));
            hv[e] = rbf(gp * sigmoidf(gp)) * u;
          }
          const uint32_t hh = packbf(hv[0], hv[1]);
          sts16(sb + SM_H + 80 * sw + 2 * lane, hh);
          sts16(sb + SM_H + 80 * sw + 64 + 2 * t, hh >> 16);
          __syncwarp();
        }
        TR(2, 7 + 10 * L);
        uint32_t hp[5];
#pragma unroll
        for (int i = 0; i < 4; i++) hp[i] = lds32(sb + SM_H + 80 * sw + 16 * i + 4 * t);
        hp[4] = lds32(sb + SM_H + 80 * sw + 64 + 4 * (t & 1));
        float Y[4] = {}, Z[4] = {}, C[4] = {};
        {
          uint32_t e0[4], e1[4], e2[4];
          const uint32_t wq = wb + 32 * (((lane >> 2) & 1) + 2 * (lane >> 4));
          ldsm4t(e0, wq); ldsm4t(e1, wq + 128); ldsm4t(e2, wb + 256);
          mma16a(Y, e0, g == (t >> 1) ? hp[4] : 0u, g == 2 + (t >> 1) ? hp[4] : 0u);
          mma16a(Z, e1, g == 4 + (t >> 1) ? hp[4] : 0u, g == 6 + (t >> 1) ? hp[4] : 0u);
          mma8(C, e2[0], e2[1], t < 2 ? hp[4] : 0u);
        }
#pragma unroll
        for (int u = 0; u < 4; u++) {
          const uint32_t wn = wa + 64 * (u + 1);
          const bool p0 = g == 2 * u, p1 = g == 2 * u + 1;
          mma16a(Y, f[0], p0 ? hp[0] : 0u, p0 ? hp[1] : 0u);
          mma16a(Z, f[1], p1 ? hp[0] : 0u, p1 ? hp[1] : 0u);
          ldsm4t(f[0], wn);
          if (u < 3) ldsm4t(f[1], wn + 32);
          mma16a(Y, f[2], p0 ? hp[2] : 0u, p0 ? hp[3] : 0u);
          mma16a(Z, f[3], p1 ? hp[2] : 0u, p1 ? hp[3] : 0u);
          ldsm4t(f[2], wn + 16 * WDP);
          if (u < 3) ldsm4t(f[3], wn + 32 + 16 * WDP);
        }
        mma16a(C, f[0], hp[0], hp[1]);
        mma16a(C, f[2], hp[2], hp[3]);
#pragma unroll
        for (int e = 0; e < 4; e++) Y[e] += Z[e];
        const uint32_t t4 = tag & 15;
        {
          uint8_t* yo = GA(ypart, (18 * sw + 4 * t) * 4096 + cta * 32 + 4 * g);
#pragma unroll
          for (int e = 0; e < 4; e++) st_rlx(yo + (2 * (e & 1) + (e >> 1)) * 4096, (__float_as_uint(Y[e]) & ~15u) | t4);
          if (t < 2) st_rlx(yo + (16 - 3 * t) * 4096, (__float_as_uint(t ? C[2] : C[0]) & ~15u) | t4);
          if (L == 0 && lane == 0) mbar_arrive(sb + B_DONE);
        }
      }
      TR(2, 8 + 10 * L);
      if (cta < 72) {
        RELANE;
        const uint32_t xn = ld_rlx(GC(candrow, (L * 128 + (win & 127)) * 1152 + 16 * cta + 2 * ((s & 6) ^ (2 * (cta & 1)))));
        const uint4 cm = ld_msg(GA(cand, (8 * L + r) * 2048 + 16 * (win & 127)));
        const uint8_t* yp = GA(ypart, cta * 4096 + s * 16);
        uint4 u0, u1;
        uint32_t n = 0;
        _Pragma("unroll 1") while (true) {
          u0 = ld_msg(yp);
          u1 = ld_msg(yp + 2048);
          const uint32_t t4 = tag & 15;
          u0.x ^= t4; u0.y ^= t4; u0.z ^= t4; u0.w ^= t4; u1.x ^= t4; u1.y ^= t4; u1.z ^= t4; u1.w ^= t4;
          if (!__any_sync(0xffffffffu, (u0.x | u0.y | u0.z | u0.w | u1.x | u1.y | u1.z | u1.w) & 15)) break;
          spin_guard(n);
        }
        const float a0 = __uint_as_float(u0.x) + __uint_as_float(u1.x), a1 = __uint_as_float(u0.y) + __uint_as_float(u1.y);
        const float a2 = __uint_as_float(u0.z) + __uint_as_float(u1.z), a3 = __uint_as_float(u0.w) + __uint_as_float(u1.w);
        const bool b4 = lane & 4, b2 = lane & 2;
        const float c0 = (b4 ? a2 : a0) + shx(b4 ? a0 : a2, 4), c1 = (b4 ? a3 : a1) + shx(b4 ? a1 : a3, 4);
        float d = (b2 ? c1 : c0) + shx(b2 ? c0 : c1, 2);
        d += shx(d, 8);
        if (!(lane & 8)) stsf(sb + SM_RED + 32 * (4 * (lane & 1) + ((lane >> 1) & 3)) + 8 * sw + 4 * (lane >> 4), d);
        bar_sync(3);
        if (s < 64) {
          const uint4 p0 = lds128(sb + SM_RED + 32 * (s & 7)), p1 = lds128(sb + SM_RED + 32 * (s & 7) + 16);
          const float y = rbf(((__uint_as_float(p0.x) + __uint_as_float(p0.y)) + (__uint_as_float(p0.z) + __uint_as_float(p0.w))) +
                              ((__uint_as_float(p1.x) + __uint_as_float(p1.y)) + (__uint_as_float(p1.z) + __uint_as_float(p1.w))));
          const uint32_t v = packbf(0.f, fmaf((s & 1) ? bhi(xn) : blo(xn), __uint_as_float(cm.z), __uint_as_float(cm.w)) + rbf(y * __uint_as_float(cm.y)));
          if (L == 0) st_rlx(GA(x2msg, (s >> 3) * 2304 + 32 * cta + 4 * (s & 7)), v | (epoch & 0xffff));
          const int tok = 128 * ((win >> 3) & 15) + 2 * (16 * (win & 3) + ((win >> 7) & 15)) + ((win >> 2) & 1);
          if (L == 1 && s < 8) *reinterpret_cast<uint16_t*>(p.out + (uint32_t)(tok * 1152 + 16 * cta + 2 * s)) = (uint16_t)(v >> 16);
        }
      }
      TR(2, 9 + 10 * L);
      if (L == 0 && m < 14) {
        RELANE;
        const int c = min(2 * m + ((s >> 3) & 1), 26);
        const uint8_t* wsrc = GC(wpack, r * 12 * WSTAGE + (s >> 4) * 3456 + c * 128 + (s & 7) * 16);
        const int k0 = 8 * (s >> 4) + (s & 7);
        uint4 wv[5];
#pragma unroll
        for (int i = 0; i < 5; i++) wv[i] = ldcg128(wsrc + i * WSTAGE);
        uint32_t xv[9];
        {
          uint32_t n = 0;
          _Pragma("unroll 1") while (true) {
            uint32_t bad = 0;
#pragma unroll
            for (int i = 0; i < 9; i++) { xv[i] = ld_rlx(GA(x2msg, r * 2304 + 4 * k0) + 256 * i); bad |= xv[i] ^ epoch; }
            if (!__any_sync(0xffffffffu, bad & 0xffff)) break;
            spin_guard(n);
          }
        }
        TR(2, 10);
        float a[8], z = 0.f;
#pragma unroll
        for (int e = 0; e < 8; e++) a[e] = 0.f;
#pragma unroll
        for (int i = 0; i < 9; i++) {
          const float xx = bhi(xv[i]);
          const uint4 w4 = wv[i % 5];
          if (i < 4) wv[i] = ldcg128(wsrc + (i + 5) * WSTAGE);
          z = fmaf(xx, (lane & 8) ? xx : 1.f, z);
          a[0] = fmaf(xx, blo(w4.x), a[0]); a[1] = fmaf(xx, bhi(w4.x), a[1]);
          a[2] = fmaf(xx, blo(w4.y), a[2]); a[3] = fmaf(xx, bhi(w4.y), a[3]);
          a[4] = fmaf(xx, blo(w4.z), a[4]); a[5] = fmaf(xx, bhi(w4.z), a[5]);
          a[6] = fmaf(xx, blo(w4.w), a[6]); a[7] = fmaf(xx, bhi(w4.w), a[7]);
        }
        const bool b4 = lane & 4, b2 = lane & 2, b1 = lane & 1;
        float b[4];
#pragma unroll
        for (int e = 0; e < 4; e++) b[e] = (b4 ? a[4 + e] : a[e]) + shx(b4 ? a[e] : a[4 + e], 4);
        z += shx(z, 4);
        const float c0 = (b2 ? b[2] : b[0]) + shx(b2 ? b[0] : b[2], 2);
        const float c1 = (b2 ? b[3] : b[1]) + shx(b2 ? b[1] : b[3], 2);
        z += shx(z, 2);
        float d = (b1 ? c1 : c0) + shx(b1 ? c0 : c1, 1);
        z += shx(z, 1);
        d += shx(d, 16);
        z += shx(z, 16);
        if (lane < 16) stsf(sb + SM_GEMV + 16 * lane + 4 * sw, d);
        if ((lane & 23) == 0) stsf(sb + SM_GEMV + 256 + 2 * lane + 4 * sw, z);
        bar_sync(3);
        if (s < 16) {
          const uint4 pd = lds128(sb + SM_GEMV + 16 * s), p1 = lds128(sb + SM_GEMV + 256), p2 = lds128(sb + SM_GEMV + 272);
          const float acc = (__uint_as_float(pd.x) + __uint_as_float(pd.y)) + (__uint_as_float(pd.z) + __uint_as_float(pd.w));
          const float m1 = ((__uint_as_float(p1.x) + __uint_as_float(p1.y)) + (__uint_as_float(p1.z) + __uint_as_float(p1.w))) * (1.f / kD);
          const float m2 = ((__uint_as_float(p2.x) + __uint_as_float(p2.y)) + (__uint_as_float(p2.z) + __uint_as_float(p2.w))) * (1.f / kD);
          const float cs = blo(lds16(sb + SM_COLSUM + 32 * c + 2 * (s & 7))) + blo(lds16(sb + SM_COLSUM + 32 * c + 2 * (s & 7) + 16));
          const float v = (acc - m1 * cs) * rcp(ln_sd(fmaxf(m2 - m1 * m1, 0.f)));
          st_rlx(GA(fixmsg, 1024 * r + 64 * m + 4 * s), __float_as_uint(rbf(v)) | (epoch & 0xffff));
        }
        TR(2, 11);
      }
      {
        if (L == 0 && (int)((win >> 3) & 15) == m) {
          RELANE;
          if (s < 72) {
            const uint8_t* fp = s < 54 ? GA(fixmsg, 1024 * r + 16 * s) : GA(x2msg, r * (2304 + 288) + 16 * (s - 54));
            uint4 v;
            uint32_t n = 0;
            _Pragma("unroll 1") while (true) {
              v = ld_msg(fp);
              if ((((v.x ^ epoch) | (v.y ^ epoch) | (v.z ^ epoch) | (v.w ^ epoch)) & 0xffff) == 0) break;
              spin_guard(n);
            }
            sts128(sb + SM_FIXQ + 16 * s, v.x & 0xffff0000u, v.y & 0xffff0000u, v.z & 0xffff0000u, v.w & 0xffff0000u);
          }
          __syncwarp();
          if (lane == 0) mbar_arrive(sb + B_FIX);
          TR(2, 12);
        }
      }
    }
    if (s == 0) st_rlx(GA(epoch, 32 * cta), epoch);
  } else {
    asm volatile("setmaxnreg.inc.sync.aligned.u32 144;");
    const int w = warp >> 2, j = warp & 3;
    const uint32_t xfull = sb + B_XFULL + 32 * w, xempty = sb + B_XEMPTY + 32 * w, xring = sb + SM_X + w * 4 * XSTAGE;
    if (threadIdx.x >= 128 && threadIdx.x < 188) { sts128(sb + SM_COLSUM + 16 * (threadIdx.x - 128), 0, 0, 0, 0); fence_async_smem(); }
    {
      const uint32_t epoch = pack();
      asm volatile("bar.arrive 15, 384;" ::: "memory");
      TRW(24);
      if (!(ABL & 8)) {
        if (lane < 16) st_msg(GA(statsP, (2 * m + w) * 8192 + r * 1024 + (16 * j + lane) * 16), 0, 0, 0, 0);
        if (lane < 2) st_msg(GA(cand, (8 * lane + r) * 2048 + 16 * (8 * m + warp)), ~epoch, 0, 0, 0);
        if (j == 3) {
#pragma unroll
          for (int u = 0; u < 10; u++) st_msg(GC(halo, (4 * cta + w) * 2560 + lane * 16) + (u / 5) * 5120 + (u % 5) * 512, 0, 0, 0, 0);
        }
        __syncwarp();
      }
      TRW(11);
    }
    const uint32_t mw = 2 * m + w, cid = 8 * m + warp;
    const uint32_t rowc = sb + SM_ROWC + 64 * warp, rowm = sb + SM_ROWM + 128 * warp;
#pragma unroll 1
    for (int L = 0; L < 2; L++) {
      int ln0 = __shfl_sync(0xffffffffu, lane + L, lane) - L;
#define RELANE2 asm volatile("" : "+r"(ln0)); const int ln = ln0, g = ln >> 2, t = ln & 3; \
      const uint32_t pa = xring + j * 256 + (ln & 7) * 1028 + ((ln >> 3) & 1) * 128 + 96; (void)pa
      uint32_t P[27][2], H[20];
      const uint8_t* hl;
      auto halo = [&]() {
#pragma unroll
        for (int u = 0; u < 5; u++) {
          const uint4 v = ld_gen(hl + u * 512);
          H[4 * u] = v.x; H[4 * u + 1] = v.y; H[4 * u + 2] = v.z; H[4 * u + 3] = v.w;
        }
      };
      {
        RELANE2;
        const uint32_t epoch = __shfl_sync(0xffffffffu, lds32(sb + SM_EP), 0);
        int selrow = -1;
        bool tgtwg = false;
        float d[108];
        uint32_t am[4];
        auto split_mean = [&](float m0, float m1) {
          const uint32_t h0 = packbf(m0, m0), h1 = packbf(m1, m1);
          const float l0 = m0 - bhi(h0), l1 = m1 - bhi(h1);
          am[0] = t ? 0u : h0; am[1] = t ? 0u : h1; am[2] = t ? 0u : packbf(l0, l0); am[3] = t ? 0u : packbf(l1, l1);
        };
        const uint32_t cdesc = mkdesc(sbd + SM_COLSUM, 0);
        am[0] = am[1] = am[2] = am[3] = 0;
        if (L == 1) split_mean(ldsf(rowm + 8 * g), ldsf(rowm + 8 * g + 64));
        asm volatile("wgmma.fence.sync.aligned;" ::: "memory");
        wgmma_n144_set(d + 36, am, cdesc + 18);
        wgmma_n72_set(d, am, cdesc);
        asm volatile("wgmma.commit_group.sync.aligned;" ::: "memory");
        const uint32_t adesc = mkdesc(sbd + SM_X + w * 4 * XSTAGE, 1024), ahi = L == 0 ? 0x40000040u : 8u, astep = L == 0 ? 2 : 128;
        const uint32_t bdesc = mkdesc(sbd + SM_W, 3456);
        const uint8_t* xsrc = GC(act, ACT + mw * 73728);
        mbar_wait2(sb + B_WFULL, L, xfull, 0);
        if (L == 1) check_stage(probe_stage(pa), xring, xsrc);
        TRW(0 + 12 * L);
#pragma unroll 1
        for (int s = 0; s < 7; s++) {
          TRQ(s + 9 * L);
          const uint32_t da = adesc + (s & 3) * (XSTAGE >> 4), db = bdesc + (s & 3) * (WSTAGE >> 4);
          const uint32_t nx = (s + 1) & 3, px = ((s + 1) >> 2) & 1;
          asm volatile("wgmma.fence.sync.aligned;" ::: "memory");
          wgmma_n72(d, da, ahi, db);
          wgmma_n144(d + 36, da, ahi, db + (1152 >> 4));
          wgmma_n72(d, da + astep, ahi, db + (6912 >> 4));
          asm volatile("wgmma.commit_group.sync.aligned;" ::: "memory");
          asm volatile("wgmma.wait_group.sync.aligned 1;" ::: "memory");
          if (s > 0 && ln == 0) {
            mbar_arrive_pair(sb + B_WEMPTY + 8 * ((s - 1) & 3));
            mbar_arrive(xempty + 8 * ((s - 1) & 3));
          }
          wgmma_n144(d + 36, da + astep, ahi, db + ((6912 + 1152) >> 4));
          wgmma_n72(d, da + 2 * astep, ahi, db + 2 * (6912 >> 4));
          uint32_t pv;
          const uint32_t dsc[6] = {da + 2 * astep, db + ((2 * 6912 + 1152) >> 4), da + 3 * astep, db + 3 * (6912 >> 4),
                                   da + 3 * astep, db + ((3 * 6912 + 1152) >> 4)};
          const uint32_t bar[4] = {sb + B_WFULL + 8 * nx, px ^ L, xfull + 8 * nx, px}, adr = pa + nx * XSTAGE;
          q_tail(d, &pv, ahi, dsc, bar, &adr);
          if (L == 1) check_stage(pv, xring + nx * XSTAGE, xsrc + (s + 1) * XSTAGE);
        }
        TRQ(7 + 9 * L);
        const uint32_t da7 = adesc + 3 * (XSTAGE >> 4), db7 = bdesc + 3 * (WSTAGE >> 4);
        asm volatile("wgmma.fence.sync.aligned;" ::: "memory");
        wgmma_n144(d + 36, da7, ahi, db7 + (1152 >> 4));
        wgmma_n144(d + 36, da7 + astep, ahi, db7 + ((6912 + 1152) >> 4));
        asm volatile("wgmma.commit_group.sync.aligned;" ::: "memory");
        asm volatile("wgmma.wait_group.sync.aligned 1;" ::: "memory");
        if (ln == 0) { mbar_arrive_pair(sb + B_WEMPTY + 16); mbar_arrive(xempty + 16); }
        {
          uint32_t v[2];
          const uint32_t dsc[4] = {da7 + 2 * astep, db7 + ((2 * 6912 + 1152) >> 4), da7 + 3 * astep, db7 + ((3 * 6912 + 1152) >> 4)};
          const uint32_t bar[6] = {sb + B_WFULL, (uint32_t)L, xfull, 0, sb + (L ? B_IDX : B_COLSUM), 0}, adr[2] = {pa, sb + SM_SEL + (ln >> 5)};
          kv_tail(d, v, ahi, dsc, bar, adr);
          if (L == 1) {
            if ((v[1] & 127) == cid) selrow = v[1] >> 7;
            tgtwg = ((v[1] & 127) >> 2) == (cid >> 2);
            check_stage(v[0], xring, xsrc + 8 * XSTAGE);
          }
        }
        TRQ(8 + 9 * L);
        const float m0 = ldsf(rowm + 8 * g), m1 = ldsf(rowm + 8 * g + 64);
        {
          uint32_t dsc[8];
#pragma unroll
          for (int kk = 0; kk < 4; kk++) { dsc[2 * kk] = adesc + kk * astep; dsc[2 * kk + 1] = bdesc + ((kk * 6912 + 1152) >> 4); }
          const uint32_t bar[2] = {xempty + 16, 1};
          asm volatile("wgmma.fence.sync.aligned;" ::: "memory");
          kv_last(d, nullptr, ahi, dsc, bar, nullptr);
        }
        if (L == 0) {
          split_mean(m0, m1);
          asm volatile("wgmma.fence.sync.aligned;" ::: "memory");
          wgmma_n144_add(d + 36, am, cdesc + 18);
          wgmma_n72_add(d, am, cdesc);
          asm volatile("wgmma.commit_group.sync.aligned;" ::: "memory");
        }
        auto qstep = [&](int k) {
          wgmma_n72(d, (k < 4 ? da7 : adesc) + (k & 3) * astep, ahi, (k < 4 ? db7 : bdesc) + (k & 3) * (6912 >> 4));
        };
#pragma unroll
        for (int k = 0; k < QPRE; k++) qstep(k);
        asm volatile("wgmma.commit_group.sync.aligned;" ::: "memory");
        if (tgtwg) {
          asm volatile("wgmma.fence.sync.aligned;" ::: "memory");
#pragma unroll
          for (int k = QPRE; k < 8; k++) qstep(k);
          asm volatile("wgmma.commit_group.sync.aligned;" ::: "memory");
        }
        asm volatile("wgmma.wait_group.sync.aligned 1;" ::: "memory");
#pragma unroll
        for (int i = 36; i < 108; i++) asm volatile("" : "+f"(d[i])::"memory");
        if (selrow >= 0) {
          mbar_wait(sb + B_FIX, 0);
          stsf(rowc + 4 * selrow, 1.f);
#pragma unroll
          for (int q = 18; q < 54; q++) lds64f_if(selrow == g + 8 * (q & 1), d[2 * q], d[2 * q + 1], sb + SM_FIXQ + 32 * (q >> 1) + 8 * t);
          __syncwarp();
        }
#pragma unroll
        for (int q = 26; q >= 9; q--) { P[q][1] = packbf(d[4 * q + 2], d[4 * q + 3]); P[q][0] = packbf(d[4 * q], d[4 * q + 1]); }
#pragma unroll
        for (int q = 26; q >= 18; q--) P[q][1] = movm(P[q][1]);
        const uint2 ck1 = lds64(rowc + 32 + 8 * t);
        uint8_t* ha = (j < 3 ? smem_raw + (SM_X + (4 * w + 2) * XSTAGE + j * 2560) : GC(halo, (4 * cta + 2 * L + w) * 2560)) + ln * 16;
        P[9][1] = nz(P[9][1]); P[13][1] = nz(P[13][1]); P[17][1] = nz(P[17][1]);
        st_gen(ha, P[9][1], P[10][1], P[11][1], P[12][1]);
        st_gen(ha + 512, P[13][1], P[14][1], P[15][1], P[16][1]);
        st_gen(ha + 2048, nz(ck1.y), P[24][1], P[25][1], P[26][1]);
        st_gen(ha + 1536, nz(ck1.x), P[21][1], P[22][1], P[23][1]);
        st_gen(ha + 1024, P[17][1], P[18][1], P[19][1], P[20][1]);
#pragma unroll
        for (int q = 9; q < 27; q++) asm volatile("" : "+r"(P[q][0]));
        if (j < 3) asm volatile("bar.arrive %0, 64;" ::"r"(5 + warp) : "memory");
        mbar_wait(sb + B_EP, 0);
#pragma unroll
        for (int q = 26; q >= 18; q--) P[q][0] = movm(P[q][0]);
        if (!tgtwg)
        {
          asm volatile("wgmma.fence.sync.aligned;" ::: "memory");
#pragma unroll
          for (int k = QPRE; k < 8; k++) qstep(k);
          asm volatile("wgmma.commit_group.sync.aligned;" ::: "memory");
        }
        hl = (j > 0 || m == 0 ? smem_raw + (SM_X + (4 * w + 2) * XSTAGE + max(j - 1, 0) * 2560)
                              : GC(halo, (4 * (cta - 8) + 2 * L + w) * 2560)) + ln * 16;
        if (j > 0) asm volatile("bar.sync %0, 64;" ::"r"(4 + warp) : "memory");
        asm volatile("wgmma.wait_group.sync.aligned 0;" ::: "memory");
#pragma unroll
        for (int i = 0; i < 36; i++) asm volatile("" : "+f"(d[i])::"memory");
        TRW(1 + 12 * L);
        if (selrow >= 0) {
#pragma unroll
          for (int q = 0; q < 18; q++) lds64f_if(selrow == g + 8 * (q & 1), d[2 * q], d[2 * q + 1], sb + SM_FIXQ + 32 * (q >> 1) + 8 * t);
        }
#pragma unroll
        for (int q = 0; q < 9; q++) { P[q][0] = packbf(d[4 * q], d[4 * q + 1]); P[q][1] = packbf(d[4 * q + 2], d[4 * q + 3]); }
      }
      TRW(2 + 12 * L);
      const uint32_t epoch = lds32(sb + SM_EP);
      uint8_t* fptr = GA(flagX, 128 * mw + 16 * r + 4 * j + ln0);
      {
        RELANE2;
        halo();
        if (ln == 0) { mbar_arrive(xempty + 24); mbar_arrive(xempty); }
        const bool le0 = 2 * t <= g, le1 = 2 * t + 1 <= g;
        uint32_t A0[4][2], A2[4][2];
        float s0[4][4], s1[4][4];
#pragma unroll
        for (int h = 0; h < 4; h++) {
          const int T = 2 * h;
          A0[h][0] = t >= h ? P[T][0] : 0u; A0[h][1] = t >= h ? P[T][1] : 0u;
          A2[h][0] = t <= h ? P[T + 2][0] : 0u; A2[h][1] = t <= h ? P[T + 2][1] : 0u;
          mma8z(s0[h], A2[h][0], A2[h][1], P[9 + T + 2][0]);
          mma8z(s1[h], A2[h][0], A2[h][1], P[9 + T + 2][1]);
        }
#pragma unroll
        for (int h = 0; h < 4; h++) {
          const int T = 2 * h;
          mma16(s0[h], A0[h][0], A0[h][1], P[T + 1][0], P[T + 1][1], P[9 + T][0], P[9 + T + 1][0]);
          mma16(s1[h], A0[h][0], A0[h][1], P[T + 1][0], P[T + 1][1], P[9 + T][1], P[9 + T + 1][1]);
        }
        const uint2 ck0 = lds64(rowc + 8 * t), ck1 = lds64(rowc + 32 + 8 * t);
        const float sc = 0.23570226039551584f * 1.4426950408889634f;
        const float cq0 = ldsf(rowc + 4 * g) * sc, cq1 = ldsf(rowc + 32 + 4 * g) * sc;
        uint8_t* ob = GC(act, 2 * L * ACT + mw * 73728 + r * 9216 + j * 256 + ln * 4);
        float l[2][4][2], ks[2][2], mx[2][4];
        ks[1][0] = __uint_as_float(le0 ? ck1.x : ck0.x); ks[1][1] = __uint_as_float(le1 ? ck1.y : ck0.y);
#pragma unroll
        for (int h = 0; h < 4; h++) {
          l[1][h][0] = (le0 ? s1[h][2] : s0[h][2]) * (cq1 * ks[1][0]); l[1][h][1] = (le1 ? s1[h][3] : s0[h][3]) * (cq1 * ks[1][1]);
          asm volatile("" : "+f"(l[1][h][0]), "+f"(l[1][h][1]));
        }
        asm volatile("" : "+l"(fptr), "+l"(ob));
        {
          uint32_t n = 0;
          _Pragma("unroll 1") while (__any_sync(0xffffffffu, min(min(min(H[0], H[4]), min(H[8], H[12])), H[16]) == 0)) {
            halo();
            spin_guard(n);
          }
        }
        if (ln == 0) mbar_arrive_pair(sb + B_WEMPTY + 24);
        TRW(3 + 12 * L);
        {
          float sm[4][4];
#pragma unroll
          for (int h = 0; h < 4; h++) mma8z(sm[h], A2[h][0], A2[h][1], H[2 * h + 2]);
#pragma unroll
          for (int h = 0; h < 4; h++) mma16(sm[h], A0[h][0], A0[h][1], P[2 * h + 1][0], P[2 * h + 1][1], H[2 * h], H[2 * h + 1]);
          ks[0][0] = __uint_as_float(le0 ? ck0.x : H[12]); ks[0][1] = __uint_as_float(le1 ? ck0.y : H[16]);
          const bool nohalo = (m == 0 && j == 0);
          const float b0 = (nohalo && !le0) ? -INFINITY : 0.f, b1 = (nohalo && !le1) ? -INFINITY : 0.f;
#pragma unroll
          for (int h = 0; h < 4; h++) {
            l[0][h][0] = fmaf(le0 ? s0[h][0] : sm[h][0], cq0 * ks[0][0], b0);
            l[0][h][1] = fmaf(le1 ? s0[h][1] : sm[h][1], cq0 * ks[0][1], b1);
          }
        }
#pragma unroll
        for (int i = 7; i >= 0; i--) mx[i >> 2][i & 3] = fmaxf(l[i >> 2][i & 3][0], l[i >> 2][i & 3][1]);
#pragma unroll
        for (int x = 1; x <= 2; x <<= 1) {
#pragma unroll
          for (int i = 7; i >= 0; i--) mx[i >> 2][i & 3] = fmaxf(mx[i >> 2][i & 3], shx(mx[i >> 2][i & 3], x));
        }
        const uint32_t mle = (le0 ? 0xffffu : 0u) | (le1 ? 0xffff0000u : 0u);
        uint32_t pp[2][4], pc[2][4];
#pragma unroll
        for (int i = 3; i >= 0; i--) {
          const int e = i >> 1, h = 2 * (i & 1);
          const float p0 = ex2(l[e][h][0] - mx[e][h]), p1 = ex2(l[e][h][1] - mx[e][h]);
          const float p2 = ex2(l[e][h + 1][0] - mx[e][h + 1]), p3 = ex2(l[e][h + 1][1] - mx[e][h + 1]);
          float sum[4];
          mma8z(sum, packbf(p0, p1), packbf(p2, p3), 0x3f803f80u);
          const float inv = rcp(sum[0] * sum[2]);
          const float ia = inv * sum[2], ib = inv * sum[0];
          const uint32_t u0 = packbf(p0 * ks[e][0] * ia, p1 * ks[e][1] * ia), u1 = packbf(p2 * ks[e][0] * ib, p3 * ks[e][1] * ib);
          pp[e][h] = u0 & ~mle; pc[e][h] = u0 & mle; pp[e][h + 1] = u1 & ~mle; pc[e][h + 1] = u1 & mle;
        }
#pragma unroll
        for (int e = 1; e >= 0; e--) {
#pragma unroll
          for (int q = 8; q >= 0; q--) {
            const int h = q < 4 ? 0 : q == 4 ? 1 : 2;
            float a[4];
            mma16z(a, pp[e][h], pp[e][h + 1], pc[e][h], pc[e][h + 1], e ? P[18 + q][0] : H[9 + q + q / 3], P[18 + q][e]);
            const bool second = q == 2 * h + 2 ? t > h : q > 2 * h + 2;
            st_rlx(ob + q * 1024 + e * 128, nz(packbf(second ? a[2] : a[0], second ? a[3] : a[1])));
          }
        }
        if (ln == 0) st_rlx(fptr, epoch * 4 + 1 + 2 * L);
        TRW(4 + 12 * L);
      }
      RELANE2;
      float d[36];
      uint32_t WB[9];
      {
        uint32_t R[10][2];
        const uint32_t qs = L == 0 ? 16 : 1024, ra = xring + (16 * j + (ln & 15)) * (L == 0 ? 144 : 16) + (ln >> 4) * qs;
        mbar_wait(sb + B_RES + 8 * w, L);
#pragma unroll
        for (int q = 0; q < 10; q += 2) ldsm4(&R[q][0], ra + q * qs);
        fence_async_smem();
        __syncwarp();
        if (ln == 0) mbar_arrive(sb + B_RC + 8 * w);
#pragma unroll
        for (int q = 0; q < 9; q++) WB[q] = ldg32(p.wr + (uint32_t)(r * 144 + 4 * t) + 16 * q);
#pragma unroll
        for (int h = 0; h < 2; h++) {
          const uint2 mf = lds64(rowm + 8 * g + 64 * h);
          const float f = __uint_as_float(mf.y), k = -__uint_as_float(mf.x) * f;
#pragma unroll
          for (int q = 0; q < 9; q++) { d[4 * q + 2 * h] = fmaf(blo(R[q][h]), f, k); d[4 * q + 2 * h + 1] = fmaf(bhi(R[q][h]), f, k); }
        }
        const uint32_t sel = lds32(sb + SM_SEL);
        if (L == 1 && (sel & 127) == cid) {
          const int selrow = sel >> 7;
#pragma unroll
          for (int q = 0; q < 18; q++) lds64f_if(selrow == g + 8 * (q & 1), d[2 * q], d[2 * q + 1], sb + SM_X2R + 32 * (q >> 1) + 8 * t);
        }
#pragma unroll
        for (int q = 0; q < 9; q++) WB[q] = (g & 1) ? WB[q] : 0x3f803f80u;
        __syncwarp();
      }
      uint8_t* xb = GC(act, ACT + mw * 73728 + r * 9216 + j * 256 + ln * 4);
      uint8_t* sst = GA(statsP, mw * 8192 + r * 1024 + (16 * j + g + 8 * t) * 16);
      const uint8_t* sld = GA(statsP, mw * 8192 + (ln >> 4) * 4096 + (16 * j + (ln & 15)) * 16);
      uint8_t* cptr = GA(cand, (8 * L + r) * 2048 + 16 * cid);
      uint8_t* crow = GC(candrow, (128 * L + cid) * 1152 + 144 * r + 4 * t);
      uint32_t tag = epoch * 2 + L, ktag = ((ln & 15) << 7) | (epoch & 0x7f);
      float wsum = ldsf(sb + SM_WSUM);
      float pivot = __uint_as_float(ld_rlx(GA(stats0, 16 * (16 * cid + (ln & 15)) + 4))) + (L ? ldsf(rowm + 8 * (ln & 15)) : 0.f);
      asm volatile("" : "+l"(xb), "+l"(sst), "+l"(sld), "+l"(cptr), "+l"(crow), "+r"(tag), "+r"(ktag), "+f"(wsum), "+f"(pivot));
      TRW(5 + 12 * L);
      {
        constexpr uint32_t bdesc = mkdesc(sbd + SM_W + WSTAGE, 1152);
        uint32_t adesc[3];
#pragma unroll
        for (int i = 0; i < 3; i++) adesc[i] = __shfl_sync(0xffffffffu, mkdesc(sbd + SM_X + w * 4 * XSTAGE, 1024) + (ln >> 2), i);
#pragma unroll
        for (int i = 0; i < 36; i++) asm volatile("" : "+f"(d[i])::"memory");
        const bool lead = warp == 0 && ln == 0;
        const uint8_t* osrc = GC(act, 2 * L * ACT + mw * 73728);
        mbar_wait2(sb + B_WFULL + 8, L, xfull, 1);
        check_stage(probe_stage(pa), xring, osrc);
        TRW(6 + 12 * L);
#pragma unroll
        for (int s = 0; s < 9; s++) {
          TRQ(18 + s);
          const uint32_t da = adesc[s >> 2] + (s & 3) * (XSTAGE >> 4), db = bdesc + s * (9216 >> 4);
          const uint32_t nx = (s + 1) & 3;
          asm volatile("wgmma.fence.sync.aligned;" ::: "memory");
          wgmma_n72(d, da, 8u, db);
          wgmma_n72(d, da + 128, 8u, db + (2304 >> 4));
          asm volatile("wgmma.commit_group.sync.aligned;" ::: "memory");
          if (s > 0) {
            asm volatile("wgmma.wait_group.sync.aligned 1;" ::: "memory");
            if (ln == 0) {
              mbar_arrive(xempty + 8 * ((s - 1) & 3));
              if ((s == 1 || s == 3 || s == 6) && L == 0) mbar_arrive_pair(sb + B_WEMPTY + (s / 3) * 8);
            }
          }
          const uint32_t px = (((s + 1) >> 2) + (nx == 0)) & 1;
#define EPIS 5
          if ((s == 0 || s == EPIS) && lead) mbar_arrive(sb + (s ? B_EPI : B_OS));
          if (s < 8) {
            uint32_t pv;
            const uint32_t dsc[4] = {da + 256, db + (4608 >> 4), da + 384, db + (6912 >> 4)};
            const uint32_t bar[4] = {sb + B_WFULL + 8 + 8 * ((s + 1) / 3), (uint32_t)L, xfull + 8 * nx, px}, adr = pa + nx * XSTAGE;
            o_tail2(d, &pv, 8u, dsc, bar, &adr);
            check_stage(pv, xring + nx * XSTAGE, osrc + (s + 1) * XSTAGE);
          } else {
            wgmma_n72(d, da + 256, 8u, db + (4608 >> 4));
            wgmma_n72(d, da + 384, 8u, db + (6912 >> 4));
            asm volatile("wgmma.commit_group.sync.aligned;" ::: "memory");
          }
        }
        asm volatile("wgmma.wait_group.sync.aligned 0;" ::: "memory");
#pragma unroll
        for (int i = 0; i < 36; i++) asm volatile("" : "+f"(d[i])::"memory");
        if (ln == 0) { if (L == 0) mbar_arrive_pair(sb + B_WEMPTY + 24); mbar_arrive(xempty); }
      }
      TRW(7 + 12 * L);
      uint32_t R[9][2];
#pragma unroll
      for (int q = 0; q < 9; q++) { R[q][0] = packbf(d[4 * q], d[4 * q + 1]); R[q][1] = packbf(d[4 * q + 2], d[4 * q + 3]); }
      {
        float sa[4], sc[4];
        mma16z(sa, R[0][0], R[0][1], R[1][0], R[1][1], WB[0], WB[1]);
        mma16z(sc, R[2][0], R[2][1], R[3][0], R[3][1], WB[2], WB[3]);
        mma16(sa, R[4][0], R[4][1], R[5][0], R[5][1], WB[4], WB[5]);
        mma16(sc, R[6][0], R[6][1], R[7][0], R[7][1], WB[6], WB[7]);
        mma8(sa, R[8][0], R[8][1], WB[8]);
        float qq[4] = {0.f, 0.f, 0.f, 0.f};
#pragma unroll
        for (int q = 0; q < 36; q++) qq[q & 3] = fmaf(d[q], d[q], qq[q & 3]);
        const float qa = qq[0] + qq[1], qc = qq[2] + qq[3];
        const bool odd = t & 1;
        float q2 = (odd ? qc : qa) + shx(odd ? qa : qc, 1);
        q2 += shx(q2, 2);
        if (t < 2)
          st_msg(sst, __float_as_uint(odd ? sa[2] + sc[2] : sa[0] + sc[0]), __float_as_uint(q2),
                 __float_as_uint(odd ? sa[3] + sc[3] : sa[1] + sc[1]), tag);
      }
      if (L == 0) {
#pragma unroll
        for (int q = 0; q < 9; q++) { st_rlx(xb + q * 1024, nz(R[q][0])); st_rlx(xb + q * 1024 + 128, nz(R[q][1])); }
        if (ln == 0) st_rlx(fptr, epoch * 4 + 2);
      }
      if (EPIS == 10 && warp == 0 && ln == 0) mbar_arrive(sb + B_EPI);
      TRW(8 + 12 * L);
      {
        uint4 u[4];
        uint32_t n = 0;
        _Pragma("unroll 1") while (true) {
#pragma unroll
          for (int i = 0; i < 4; i++) u[i] = ld_msg(sld + 1024 * i);
          if (!__any_sync(0xffffffffu, (u[0].w ^ tag) | (u[1].w ^ tag) | (u[2].w ^ tag) | (u[3].w ^ tag))) break;
          spin_guard(n);
        }
        TRW(9 + 12 * L);
        float s1 = (__uint_as_float(u[0].x) + __uint_as_float(u[1].x)) + (__uint_as_float(u[2].x) + __uint_as_float(u[3].x));
        float s2 = (__uint_as_float(u[0].y) + __uint_as_float(u[1].y)) + (__uint_as_float(u[2].y) + __uint_as_float(u[3].y));
        float s3 = (__uint_as_float(u[0].z) + __uint_as_float(u[1].z)) + (__uint_as_float(u[2].z) + __uint_as_float(u[3].z));
        s1 += shx(s1, 16); s2 += shx(s2, 16); s3 += shx(s3, 16);
        const float mu = s1 * (1.f / kD);
        const float var = fmaxf(fmaf(s2, 1.f / kD, -mu * mu), 0.f);
        const float sd = ln_sd(var), rho = rcp(sd);
        const float rr = (s3 - mu * wsum) * rho;
        const int key = __reduce_max_sync(0xffffffffu, (int)((fkey(rr) & ~0x7ff) | ktag));
        const int best = (key >> 7) & 15;
        if (ln == best) st_msg(cptr, key, __float_as_uint(rbf(sigmoidf(rbf(rr)))), __float_as_uint(1.f + sd), __float_as_uint(L ? pivot + mu : 0.f));
        const float rb = __shfl_sync(0xffffffffu, rho, best), nb = __shfl_sync(0xffffffffu, -mu * rho, best);
        if ((best & 7) == g) {
          const bool hi = best >= 8;
#pragma unroll
          for (int q = 0; q < 9; q++)
            st_rlx(crow + (((q ^ r) & 1) * (4 - 8 * (t & 1))) + 16 * q, nz(packbf(fmaf(hi ? d[4 * q + 2] : d[4 * q], rb, nb), fmaf(hi ? d[4 * q + 3] : d[4 * q + 1], rb, nb))));
        }
        const float f = 1.f + rho, k = pivot - mu * rho;
        sts32(rowc + 4 * (ln & 15), __float_as_uint(f * rcp(ln_sd(var * f * f))));
        sts64(rowm + 8 * (ln & 15), __float_as_uint(L == 0 ? mu : k), __float_as_uint(f));
        __syncwarp();
      }
      if (EPIS == 11 && warp == 0 && ln == 0) mbar_arrive(sb + B_EPI);
      TRW(10 + 12 * L);
      if (L == 1) {
#pragma unroll
        for (int h = 0; h < 2; h++) {
          const uint2 kf = lds64(rowm + 8 * g + 64 * h);
          const float k = __uint_as_float(kf.x), f = __uint_as_float(kf.y);
#pragma unroll
          for (int q = 0; q < 9; q++) R[q][h] = packbf(fmaf(d[4 * q + 2 * h], f, k), fmaf(d[4 * q + 2 * h + 1], f, k));
        }
        mbar_wait(xempty + 16, 1);
        const uint32_t st = xring + XSTAGE + (16 * j + (ln & 15)) * 144;
#pragma unroll
        for (int q = 0; q < 8; q += 2) stsm4(st + (ln >> 4) * 16 + q * 16, R[q][0], R[q][1], R[q + 1][0], R[q + 1][1]);
        stsm2(st + 128, R[8][0], R[8][1]);
        fence_async_smem();
        __syncwarp();
        mbar_wait(sb + B_IDX + 8, 0);
        const uint32_t sel = lds32(sb + SM_SEL + 4);
        if ((sel & 127) != cid) {
          if (elect())
            asm volatile("cp.async.bulk.tensor.3d.global.shared::cta.bulk_group [%0, {%2,%3,%4}], [%1];" ::"l"(&tm.out),
                         "r"(xring + XSTAGE + 16 * j * 144), "r"(72 * r), "r"(w), "r"(64 * m + 16 * j) : "memory");
        } else if (ln < 16 && ln != (sel >> 7)) {
          bulk_s2g(p.out + (uint32_t)((128 * m + 2 * (16 * j + ln) + w) * 1152 + r * 144), st, 144);
        }
        asm volatile("cp.async.bulk.commit_group;" ::: "memory");
        asm volatile("cp.async.bulk.wait_group.read 0;" ::: "memory");
        TRW(11 + 12 * L);
        TRDUMP(w);
      }
    }
  }
}

typedef CUresult (*EncodeFn)(CUtensorMap*, CUtensorMapDataType, cuuint32_t, void*, const cuuint64_t*, const cuuint64_t*,
                             const cuuint32_t*, const cuuint32_t*, CUtensorMapInterleave, CUtensorMapSwizzle,
                             CUtensorMapL2promotion, CUtensorMapFloatOOBfill);

}

extern "C" void kernel_launch(void* const* d_in, const int* in_sizes, int n_in, void* d_out, int out_size) {
  static EncodeFn enc = nullptr;
  static Scratch* scratch = nullptr;
  if (!enc) {
    cudaDriverEntryPointQueryResult q;
    cudaGetDriverEntryPoint("cuTensorMapEncodeTiled", (void**)&enc, cudaEnableDefault, &q);
    cudaGetSymbolAddress((void**)&scratch, g_s);
    cudaFuncSetAttribute(fused_kernel, cudaFuncAttributeMaxDynamicSharedMemorySize, 232448);
  }
  Maps tm;
  auto mk = [&](CUtensorMap* t, void* ptr, int rank, const cuuint64_t* dims, const cuuint64_t* strides, const cuuint32_t* box,
                CUtensorMapSwizzle sw, CUtensorMapL2promotion pr) {
    const cuuint32_t es[4] = {1, 1, 1, 1};
    enc(t, CU_TENSOR_MAP_DATA_TYPE_BFLOAT16, rank, ptr, dims, strides, box, es, CU_TENSOR_MAP_INTERLEAVE_NONE, sw, pr,
        CU_TENSOR_MAP_FLOAT_OOB_FILL_NONE);
  };
  { const cuuint64_t d[3] = {576, 2, 1024}, st[2] = {1152, 2304}; const cuuint32_t bx[3] = {64, 1, 64};
    mk(&tm.x, d_in[0], 3, d, st, bx, CU_TENSOR_MAP_SWIZZLE_128B, CU_TENSOR_MAP_L2_PROMOTION_NONE);
    const cuuint32_t br[3] = {72, 1, 64};
    mk(&tm.xr, d_in[0], 3, d, st, br, CU_TENSOR_MAP_SWIZZLE_NONE, CU_TENSOR_MAP_L2_PROMOTION_NONE);
    const cuuint32_t bo[3] = {72, 1, 16};
    mk(&tm.out, d_out, 3, d, st, bo, CU_TENSOR_MAP_SWIZZLE_NONE, CU_TENSOR_MAP_L2_PROMOTION_NONE); }
  { const cuuint64_t d[3] = {576, 576, 3}, st[2] = {3456, 1152}; const cuuint32_t bx[3] = {72, 8, 2};
    mk(&tm.wq, d_in[1], 3, d, st, bx, CU_TENSOR_MAP_SWIZZLE_NONE, CU_TENSOR_MAP_L2_PROMOTION_NONE); }
  { const cuuint64_t d[2] = {576, 576}, st[1] = {1152}; const cuuint32_t bx[2] = {72, 16};
    mk(&tm.wo, d_in[2], 2, d, st, bx, CU_TENSOR_MAP_SWIZZLE_NONE, CU_TENSOR_MAP_L2_PROMOTION_NONE); }
  { const cuuint64_t d[2] = {4608, 576}, st[1] = {9216}; const cuuint32_t bx[2] = {48, 64};
    mk(&tm.wg, d_in[5], 2, d, st, bx, CU_TENSOR_MAP_SWIZZLE_128B, CU_TENSOR_MAP_L2_PROMOTION_L2_128B);
    mk(&tm.wu, d_in[6], 2, d, st, bx, CU_TENSOR_MAP_SWIZZLE_128B, CU_TENSOR_MAP_L2_PROMOTION_L2_128B); }
  Params p;
  p.x = (const uint8_t*)d_in[0]; p.wqkv = (const uint8_t*)d_in[1]; p.wo = (const uint8_t*)d_in[2];
  p.wr = (const uint8_t*)d_in[4]; p.wg = (const uint8_t*)d_in[5]; p.wu = (const uint8_t*)d_in[6]; p.wd = (const uint8_t*)d_in[7];
  p.out = (uint8_t*)d_out;
  p.g = scratch;
  fused_kernel<<<128, 512, 232448>>>(p, tm);
}
```

```cpp
#include <cuda_runtime.h>
#include <cuda_bf16.h>
#include <cuda.h>
#include <stdint.h>
#include <stddef.h>

#define DEVI __device__ __forceinline__

namespace {

constexpr int kD = 576, kF = 4608;
constexpr uint32_t WSTAGE = 27648, XSTAGE = 8192;
constexpr float kEps = 1e-5f;

constexpr uint32_t WDP = 1168;
constexpr uint32_t SM_W = 0;
constexpr uint32_t SM_X = 110592;
constexpr uint32_t SM_WD = 176128;
constexpr uint32_t SM_LEFT = SM_WD + 36 * WDP;
constexpr uint32_t SM_COLSUM = SM_LEFT + 9216;
constexpr uint32_t SM_ROWC = SM_COLSUM + 960;
constexpr uint32_t SM_ROWM = SM_ROWC + 512;
constexpr uint32_t SM_PART = SM_ROWM + 1024;
constexpr uint32_t SM_FIXQ = SM_PART;
constexpr uint32_t SM_X2R = SM_PART + 864;
constexpr uint32_t SM_H = SM_PART + 1152;
constexpr uint32_t SM_GEMV = SM_H;
constexpr uint32_t SM_RED = SM_H + 320;
constexpr uint32_t SM_SEL = SM_RED + 256;
constexpr uint32_t SM_EP = SM_SEL + 8, SM_WSUM = SM_SEL + 12;
constexpr uint32_t SM_BAR = SM_SEL + 16;
constexpr uint32_t B_WFULL = SM_BAR, B_WEMPTY = B_WFULL + 32, B_XFULL = B_WEMPTY + 32, B_XEMPTY = B_XFULL + 64;
constexpr uint32_t B_RC = B_XEMPTY + 64;
constexpr uint32_t B_COLSUM = B_RC + 16, B_PKF = B_COLSUM + 8, B_FIX = B_PKF + 8, B_DONE = B_FIX + 8;
constexpr uint32_t B_FF = B_DONE + 8;
constexpr uint32_t B_IDX = B_FF + 24;
constexpr uint32_t B_WD = B_IDX + 16, B_WANT = B_WD + 8, B_EPI = B_WANT + 8, B_EP = B_EPI + 8, B_OS = B_EP + 8, B_FD = B_OS + 8;
constexpr uint32_t B_WL = B_FD + 8;
constexpr uint32_t B_RES = B_WL + 32;
constexpr uint32_t SM_TOTAL = B_RES + 16;
constexpr int NBAR = (SM_TOTAL - SM_BAR) / 8, NBAR4 = (B_FF - SM_BAR) / 8;
constexpr uint32_t FSLOT = 16384;
static_assert(SM_TOTAL + 256 <= 232448, "smem");

struct __align__(1024) Checked {
  uint32_t candrow[2][128][288];
  uint4 halo[128][2][2][5][32];
  uint8_t wpack[8][12 * WSTAGE];
  uint8_t act[3][16][2][73728];
};
struct __align__(1024) Scratch {
  uint4 cand[2][8][128];
  uint4 ypart[72][128][2];
  uint32_t x2msg[8][576];
  uint32_t fixmsg[8][256];
  uint32_t flagP[8][12][32];
  uint32_t flagX[16][2][32];
  uint32_t epoch[128][8];
  uint4 stats0[16][2][64];
  uint4 statsP[16][2][8][64];
  float colpart[8][8][216];
  Checked chk[2];
};
__device__ Scratch g_s;
#define GA(member, off) (gb + offsetof(Scratch, member) + (uint32_t)(off))
#define GC(member, off) (gb + offsetof(Scratch, chk) + offsetof(Checked, member) + (uint32_t)((off) + (epoch & 1) * (uint32_t)sizeof(Checked)))
constexpr uint32_t ACT = 16 * 2 * 73728;

#define TR(role, i)
#define TRL(role, i)
#define TRDUMP(role)
#define TRW(i)
#define TRZ(i)
#define TRQ(i)

__device__ __forceinline__ void wgmma_n144(float* d, uint32_t alo, uint32_t ahi, uint32_t blo) {
  asm volatile("{\n.reg .b64 da, db;\nmov.b64 da, {%72, %73};\nmov.b64 db, {%74, 8};\n"
    "wgmma.mma_async.sync.aligned.m64n144k16.f32.bf16.bf16 "
    "{%0, %1, %2, %3, %4, %5, %6, %7, %8, %9, %10, %11, %12, %13, %14, %15, %16, %17, %18, %19, %20, %21, %22, %23, %24, %25, %26, %27, %28, %29, %30, %31, %32, %33, %34, %35, %36, %37, %38, %39, %40, %41, %42, %43, %44, %45, %46, %47, %48, %49, %50, %51, %52, %53, %54, %55, %56, %57, %58, %59, %60, %61, %62, %63, %64, %65, %66, %67, %68, %69, %70, %71}, da, db, 1, 1, 1, 0, 1;\n}\n"
    : "+f"(d[0]), "+f"(d[1]), "+f"(d[2]), "+f"(d[3]), "+f"(d[4]), "+f"(d[5]), "+f"(d[6]), "+f"(d[7]), "+f"(d[8]),
      "+f"(d[9]), "+f"(d[10]), "+f"(d[11]), "+f"(d[12]), "+f"(d[13]), "+f"(d[14]), "+f"(d[15]), "+f"(d[16]), "+f"(d[17]),
      "+f"(d[18]), "+f"(d[19]), "+f"(d[20]), "+f"(d[21]), "+f"(d[22]), "+f"(d[23]), "+f"(d[24]), "+f"(d[25]), "+f"(d[26]),
      "+f"(d[27]), "+f"(d[28]), "+f"(d[29]), "+f"(d[30]), "+f"(d[31]), "+f"(d[32]), "+f"(d[33]), "+f"(d[34]), "+f"(d[35]),
      "+f"(d[36]), "+f"(d[37]), "+f"(d[38]), "+f"(d[39]), "+f"(d[40]), "+f"(d[41]), "+f"(d[42]), "+f"(d[43]), "+f"(d[44]),
      "+f"(d[45]), "+f"(d[46]), "+f"(d[47]), "+f"(d[48]), "+f"(d[49]), "+f"(d[50]), "+f"(d[51]), "+f"(d[52]), "+f"(d[53]),
      "+f"(d[54]), "+f"(d[55]), "+f"(d[56]), "+f"(d[57]), "+f"(d[58]), "+f"(d[59]), "+f"(d[60]), "+f"(d[61]), "+f"(d[62]),
      "+f"(d[63]), "+f"(d[64]), "+f"(d[65]), "+f"(d[66]), "+f"(d[67]), "+f"(d[68]), "+f"(d[69]), "+f"(d[70]), "+f"(d[71])
    : "r"(alo), "r"(ahi), "r"(blo));
}
__device__ __forceinline__ void wgmma_n144_set(float* d, const uint32_t* a, uint32_t blo) {
  asm volatile("{\n.reg .b64 db;\nmov.b64 db, {%76, 2};\n"
    "wgmma.mma_async.sync.aligned.m64n144k16.f32.bf16.bf16 "
    "{%0, %1, %2, %3, %4, %5, %6, %7, %8, %9, %10, %11, %12, %13, %14, %15, %16, %17, %18, %19, %20, %21, %22, %23, %24, %25, %26, %27, %28, %29, %30, %31, %32, %33, %34, %35, %36, %37, %38, %39, %40, %41, %42, %43, %44, %45, %46, %47, %48, %49, %50, %51, %52, %53, %54, %55, %56, %57, %58, %59, %60, %61, %62, %63, %64, %65, %66, %67, %68, %69, %70, %71}, {%72, %73, %74, %75}, db, 0, -1, 1, 1;\n}\n"
    : "=f"(d[0]), "=f"(d[1]), "=f"(d[2]), "=f"(d[3]), "=f"(d[4]), "=f"(d[5]), "=f"(d[6]), "=f"(d[7]), "=f"(d[8]),
      "=f"(d[9]), "=f"(d[10]), "=f"(d[11]), "=f"(d[12]), "=f"(d[13]), "=f"(d[14]), "=f"(d[15]), "=f"(d[16]), "=f"(d[17]),
      "=f"(d[18]), "=f"(d[19]), "=f"(d[20]), "=f"(d[21]), "=f"(d[22]), "=f"(d[23]), "=f"(d[24]), "=f"(d[25]), "=f"(d[26]),
      "=f"(d[27]), "=f"(d[28]), "=f"(d[29]), "=f"(d[30]), "=f"(d[31]), "=f"(d[32]), "=f"(d[33]), "=f"(d[34]), "=f"(d[35]),
      "=f"(d[36]), "=f"(d[37]), "=f"(d[38]), "=f"(d[39]), "=f"(d[40]), "=f"(d[41]), "=f"(d[42]), "=f"(d[43]), "=f"(d[44]),
      "=f"(d[45]), "=f"(d[46]), "=f"(d[47]), "=f"(d[48]), "=f"(d[49]), "=f"(d[50]), "=f"(d[51]), "=f"(d[52]), "=f"(d[53]),
      "=f"(d[54]), "=f"(d[55]), "=f"(d[56]), "=f"(d[57]), "=f"(d[58]), "=f"(d[59]), "=f"(d[60]), "=f"(d[61]), "=f"(d[62]),
      "=f"(d[63]), "=f"(d[64]), "=f"(d[65]), "=f"(d[66]), "=f"(d[67]), "=f"(d[68]), "=f"(d[69]), "=f"(d[70]), "=f"(d[71])
    : "r"(a[0]), "r"(a[1]), "r"(a[2]), "r"(a[3]), "r"(blo));
}
__device__ __forceinline__ void wgmma_n144_add(float* d, const uint32_t* a, uint32_t blo) {
  asm volatile("{\n.reg .b64 db;\nmov.b64 db, {%76, 2};\n"
    "wgmma.mma_async.sync.aligned.m64n144k16.f32.bf16.bf16 "
    "{%0, %1, %2, %3, %4, %5, %6, %7, %8, %9, %10, %11, %12, %13, %14, %15, %16, %17, %18, %19, %20, %21, %22, %23, %24, %25, %26, %27, %28, %29, %30, %31, %32, %33, %34, %35, %36, %37, %38, %39, %40, %41, %42, %43, %44, %45, %46, %47, %48, %49, %50, %51, %52, %53, %54, %55, %56, %57, %58, %59, %60, %61, %62, %63, %64, %65, %66, %67, %68, %69, %70, %71}, {%72, %73, %74, %75}, db, 1, -1, 1, 1;\n}\n"
    : "+f"(d[0]), "+f"(d[1]), "+f"(d[2]), "+f"(d[3]), "+f"(d[4]), "+f"(d[5]), "+f"(d[6]), "+f"(d[7]), "+f"(d[8]),
      "+f"(d[9]), "+f"(d[10]), "+f"(d[11]), "+f"(d[12]), "+f"(d[13]), "+f"(d[14]), "+f"(d[15]), "+f"(d[16]), "+f"(d[17]),
      "+f"(d[18]), "+f"(d[19]), "+f"(d[20]), "+f"(d[21]), "+f"(d[22]), "+f"(d[23]), "+f"(d[24]), "+f"(d[25]), "+f"(d[26]),
      "+f"(d[27]), "+f"(d[28]), "+f"(d[29]), "+f"(d[30]), "+f"(d[31]), "+f"(d[32]), "+f"(d[33]), "+f"(d[34]), "+f"(d[35]),
      "+f"(d[36]), "+f"(d[37]), "+f"(d[38]), "+f"(d[39]), "+f"(d[40]), "+f"(d[41]), "+f"(d[42]), "+f"(d[43]), "+f"(d[44]),
      "+f"(d[45]), "+f"(d[46]), "+f"(d[47]), "+f"(d[48]), "+f"(d[49]), "+f"(d[50]), "+f"(d[51]), "+f"(d[52]), "+f"(d[53]),
      "+f"(d[54]), "+f"(d[55]), "+f"(d[56]), "+f"(d[57]), "+f"(d[58]), "+f"(d[59]), "+f"(d[60]), "+f"(d[61]), "+f"(d[62]),
      "+f"(d[63]), "+f"(d[64]), "+f"(d[65]), "+f"(d[66]), "+f"(d[67]), "+f"(d[68]), "+f"(d[69]), "+f"(d[70]), "+f"(d[71])
    : "r"(a[0]), "r"(a[1]), "r"(a[2]), "r"(a[3]), "r"(blo));
}
__device__ __forceinline__ void wgmma_n72(float* d, uint32_t alo, uint32_t ahi, uint32_t blo) {
  asm volatile("{\n.reg .b64 da, db;\nmov.b64 da, {%36, %37};\nmov.b64 db, {%38, 8};\n"
    "wgmma.mma_async.sync.aligned.m64n72k16.f32.bf16.bf16 "
    "{%0, %1, %2, %3, %4, %5, %6, %7, %8, %9, %10, %11, %12, %13, %14, %15, %16, %17, %18, %19, %20, %21, %22, %23, %24, %25, %26, %27, %28, %29, %30, %31, %32, %33, %34, %35}, da, db, 1, 1, 1, 0, 1;\n}\n"
    : "+f"(d[0]), "+f"(d[1]), "+f"(d[2]), "+f"(d[3]), "+f"(d[4]), "+f"(d[5]), "+f"(d[6]), "+f"(d[7]), "+f"(d[8]),
      "+f"(d[9]), "+f"(d[10]), "+f"(d[11]), "+f"(d[12]), "+f"(d[13]), "+f"(d[14]), "+f"(d[15]), "+f"(d[16]), "+f"(d[17]),
      "+f"(d[18]), "+f"(d[19]), "+f"(d[20]), "+f"(d[21]), "+f"(d[22]), "+f"(d[23]), "+f"(d[24]), "+f"(d[25]), "+f"(d[26]),
      "+f"(d[27]), "+f"(d[28]), "+f"(d[29]), "+f"(d[30]), "+f"(d[31]), "+f"(d[32]), "+f"(d[33]), "+f"(d[34]), "+f"(d[35])
    : "r"(alo), "r"(ahi), "r"(blo));
}
__device__ __forceinline__ void wgmma_n72_set(float* d, const uint32_t* a, uint32_t blo) {
  asm volatile("{\n.reg .b64 db;\nmov.b64 db, {%40, 2};\n"
    "wgmma.mma_async.sync.aligned.m64n72k16.f32.bf16.bf16 "
    "{%0, %1, %2, %3, %4, %5, %6, %7, %8, %9, %10, %11, %12, %13, %14, %15, %16, %17, %18, %19, %20, %21, %22, %23, %24, %25, %26, %27, %28, %29, %30, %31, %32, %33, %34, %35}, {%36, %37, %38, %39}, db, 0, -1, 1, 1;\n}\n"
    : "=f"(d[0]), "=f"(d[1]), "=f"(d[2]), "=f"(d[3]), "=f"(d[4]), "=f"(d[5]), "=f"(d[6]), "=f"(d[7]), "=f"(d[8]),
      "=f"(d[9]), "=f"(d[10]), "=f"(d[11]), "=f"(d[12]), "=f"(d[13]), "=f"(d[14]), "=f"(d[15]), "=f"(d[16]), "=f"(d[17]),
      "=f"(d[18]), "=f"(d[19]), "=f"(d[20]), "=f"(d[21]), "=f"(d[22]), "=f"(d[23]), "=f"(d[24]), "=f"(d[25]), "=f"(d[26]),
      "=f"(d[27]), "=f"(d[28]), "=f"(d[29]), "=f"(d[30]), "=f"(d[31]), "=f"(d[32]), "=f"(d[33]), "=f"(d[34]), "=f"(d[35])
    : "r"(a[0]), "r"(a[1]), "r"(a[2]), "r"(a[3]), "r"(blo));
}
__device__ __forceinline__ void wgmma_n72_add(float* d, const uint32_t* a, uint32_t blo) {
  asm volatile("{\n.reg .b64 db;\nmov.b64 db, {%40, 2};\n"
    "wgmma.mma_async.sync.aligned.m64n72k16.f32.bf16.bf16 "
    "{%0, %1, %2, %3, %4, %5, %6, %7, %8, %9, %10, %11, %12, %13, %14, %15, %16, %17, %18, %19, %20, %21, %22, %23, %24, %25, %26, %27, %28, %29, %30, %31, %32, %33, %34, %35}, {%36, %37, %38, %39}, db, 1, -1, 1, 1;\n}\n"
    : "+f"(d[0]), "+f"(d[1]), "+f"(d[2]), "+f"(d[3]), "+f"(d[4]), "+f"(d[5]), "+f"(d[6]), "+f"(d[7]), "+f"(d[8]),
      "+f"(d[9]), "+f"(d[10]), "+f"(d[11]), "+f"(d[12]), "+f"(d[13]), "+f"(d[14]), "+f"(d[15]), "+f"(d[16]), "+f"(d[17]),
      "+f"(d[18]), "+f"(d[19]), "+f"(d[20]), "+f"(d[21]), "+f"(d[22]), "+f"(d[23]), "+f"(d[24]), "+f"(d[25]), "+f"(d[26]),
      "+f"(d[27]), "+f"(d[28]), "+f"(d[29]), "+f"(d[30]), "+f"(d[31]), "+f"(d[32]), "+f"(d[33]), "+f"(d[34]), "+f"(d[35])
    : "r"(a[0]), "r"(a[1]), "r"(a[2]), "r"(a[3]), "r"(blo));
}
__device__ __forceinline__ void q_tail(float* d, uint32_t* v, uint32_t ahi, const uint32_t* dsc, const uint32_t* bar, const uint32_t* adr) {
  asm volatile(
    "{\n.reg .pred p<2>, q;\n.reg .b64 da, db;\n.reg .u32 n;\n"
    "mbarrier.test_wait.parity.shared::cta.b64 p0, [%116], %117;\n"
    "mbarrier.test_wait.parity.shared::cta.b64 p1, [%118], %119;\n"
    "ld.volatile.shared.u32 %108, [%120];\n"
    "mov.b64 da, {%110, %109};\nmov.b64 db, {%111, 8};\n"
    "wgmma.mma_async.sync.aligned.m64n144k16.f32.bf16.bf16 {%36, %37, %38, %39, %40, %41, %42, %43, %44, %45, %46, %47, %48, %49, %50, %51, %52, %53, %54, %55, %56, %57, %58, %59, %60, %61, %62, %63, %64, %65, %66, %67, %68, %69, %70, %71, %72, %73, %74, %75, %76, %77, %78, %79, %80, %81, %82, %83, %84, %85, %86, %87, %88, %89, %90, %91, %92, %93, %94, %95, %96, %97, %98, %99, %100, %101, %102, %103, %104, %105, %106, %107}, da, db, 1, 1, 1, 0, 1;\n"
    "mov.b64 da, {%112, %109};\nmov.b64 db, {%113, 8};\n"
    "wgmma.mma_async.sync.aligned.m64n72k16.f32.bf16.bf16 {%0, %1, %2, %3, %4, %5, %6, %7, %8, %9, %10, %11, %12, %13, %14, %15, %16, %17, %18, %19, %20, %21, %22, %23, %24, %25, %26, %27, %28, %29, %30, %31, %32, %33, %34, %35}, da, db, 1, 1, 1, 0, 1;\n"
    "mov.b64 da, {%114, %109};\nmov.b64 db, {%115, 8};\n"
    "wgmma.mma_async.sync.aligned.m64n144k16.f32.bf16.bf16 {%36, %37, %38, %39, %40, %41, %42, %43, %44, %45, %46, %47, %48, %49, %50, %51, %52, %53, %54, %55, %56, %57, %58, %59, %60, %61, %62, %63, %64, %65, %66, %67, %68, %69, %70, %71, %72, %73, %74, %75, %76, %77, %78, %79, %80, %81, %82, %83, %84, %85, %86, %87, %88, %89, %90, %91, %92, %93, %94, %95, %96, %97, %98, %99, %100, %101, %102, %103, %104, %105, %106, %107}, da, db, 1, 1, 1, 0, 1;\n"
    "wgmma.commit_group.sync.aligned;\n"
    "@p0 bra.uni D0;\nmov.u32 n, 0;\nW0:\nmbarrier.try_wait.parity.shared::cta.b64 q, [%116], %117;\n@q bra.uni R0;\nadd.u32 n, n, 1;\nsetp.lt.u32 q, n, 8192;\n@q bra.uni W0;\nR0:\n"
    "D0:\n"
    "@p1 bra.uni D1;\nmov.u32 n, 0;\nW1:\nmbarrier.try_wait.parity.shared::cta.b64 q, [%118], %119;\n@q bra.uni R1;\nadd.u32 n, n, 1;\nsetp.lt.u32 q, n, 8192;\n@q bra.uni W1;\nR1:\n"
    "ld.volatile.shared.u32 %108, [%120];\n"
    "D1:\n"
    "}\n"
    : "+f"(d[0]), "+f"(d[1]), "+f"(d[2]), "+f"(d[3]), "+f"(d[4]), "+f"(d[5]), "+f"(d[6]), "+f"(d[7]), "+f"(d[8]),
      "+f"(d[9]), "+f"(d[10]), "+f"(d[11]), "+f"(d[12]), "+f"(d[13]), "+f"(d[14]), "+f"(d[15]), "+f"(d[16]), "+f"(d[17]),
      "+f"(d[18]), "+f"(d[19]), "+f"(d[20]), "+f"(d[21]), "+f"(d[22]), "+f"(d[23]), "+f"(d[24]), "+f"(d[25]), "+f"(d[26]),
      "+f"(d[27]), "+f"(d[28]), "+f"(d[29]), "+f"(d[30]), "+f"(d[31]), "+f"(d[32]), "+f"(d[33]), "+f"(d[34]), "+f"(d[35]),
      "+f"(d[36]), "+f"(d[37]), "+f"(d[38]), "+f"(d[39]), "+f"(d[40]), "+f"(d[41]), "+f"(d[42]), "+f"(d[43]), "+f"(d[44]),
      "+f"(d[45]), "+f"(d[46]), "+f"(d[47]), "+f"(d[48]), "+f"(d[49]), "+f"(d[50]), "+f"(d[51]), "+f"(d[52]), "+f"(d[53]),
      "+f"(d[54]), "+f"(d[55]), "+f"(d[56]), "+f"(d[57]), "+f"(d[58]), "+f"(d[59]), "+f"(d[60]), "+f"(d[61]), "+f"(d[62]),
      "+f"(d[63]), "+f"(d[64]), "+f"(d[65]), "+f"(d[66]), "+f"(d[67]), "+f"(d[68]), "+f"(d[69]), "+f"(d[70]), "+f"(d[71]),
      "+f"(d[72]), "+f"(d[73]), "+f"(d[74]), "+f"(d[75]), "+f"(d[76]), "+f"(d[77]), "+f"(d[78]), "+f"(d[79]), "+f"(d[80]),
      "+f"(d[81]), "+f"(d[82]), "+f"(d[83]), "+f"(d[84]), "+f"(d[85]), "+f"(d[86]), "+f"(d[87]), "+f"(d[88]), "+f"(d[89]),
      "+f"(d[90]), "+f"(d[91]), "+f"(d[92]), "+f"(d[93]), "+f"(d[94]), "+f"(d[95]), "+f"(d[96]), "+f"(d[97]), "+f"(d[98]),
      "+f"(d[99]), "+f"(d[100]), "+f"(d[101]), "+f"(d[102]), "+f"(d[103]), "+f"(d[104]), "+f"(d[105]), "+f"(d[106]), "+f"(d[107]),
      "=&r"(v[0])
    : "r"(ahi), "r"(dsc[0]), "r"(dsc[1]), "r"(dsc[2]), "r"(dsc[3]), "r"(dsc[4]), "r"(dsc[5]), "r"(bar[0]), "r"(bar[1]), "r"(bar[2]), "r"(bar[3]), "r"(adr[0]) : "memory");
}
__device__ __forceinline__ void kv_tail(float* d, uint32_t* v, uint32_t ahi, const uint32_t* dsc, const uint32_t* bar, const uint32_t* adr) {
  asm volatile(
    "{\n.reg .pred p<3>, q;\n.reg .b64 da, db;\n.reg .u32 n;\n"
    "mbarrier.test_wait.parity.shared::cta.b64 p0, [%79], %80;\n"
    "mbarrier.test_wait.parity.shared::cta.b64 p1, [%81], %82;\n"
    "mbarrier.test_wait.parity.shared::cta.b64 p2, [%83], %84;\n"
    "ld.volatile.shared.u32 %72, [%85];\n"
    "ld.volatile.shared.u32 %73, [%86];\n"
    "mov.b64 da, {%75, %74};\nmov.b64 db, {%76, 8};\n"
    "wgmma.mma_async.sync.aligned.m64n144k16.f32.bf16.bf16 {%0, %1, %2, %3, %4, %5, %6, %7, %8, %9, %10, %11, %12, %13, %14, %15, %16, %17, %18, %19, %20, %21, %22, %23, %24, %25, %26, %27, %28, %29, %30, %31, %32, %33, %34, %35, %36, %37, %38, %39, %40, %41, %42, %43, %44, %45, %46, %47, %48, %49, %50, %51, %52, %53, %54, %55, %56, %57, %58, %59, %60, %61, %62, %63, %64, %65, %66, %67, %68, %69, %70, %71}, da, db, 1, 1, 1, 0, 1;\n"
    "mov.b64 da, {%77, %74};\nmov.b64 db, {%78, 8};\n"
    "wgmma.mma_async.sync.aligned.m64n144k16.f32.bf16.bf16 {%0, %1, %2, %3, %4, %5, %6, %7, %8, %9, %10, %11, %12, %13, %14, %15, %16, %17, %18, %19, %20, %21, %22, %23, %24, %25, %26, %27, %28, %29, %30, %31, %32, %33, %34, %35, %36, %37, %38, %39, %40, %41, %42, %43, %44, %45, %46, %47, %48, %49, %50, %51, %52, %53, %54, %55, %56, %57, %58, %59, %60, %61, %62, %63, %64, %65, %66, %67, %68, %69, %70, %71}, da, db, 1, 1, 1, 0, 1;\n"
    "wgmma.commit_group.sync.aligned;\n"
    "@p0 bra.uni D0;\nmov.u32 n, 0;\nW0:\nmbarrier.try_wait.parity.shared::cta.b64 q, [%79], %80;\n@q bra.uni R0;\nadd.u32 n, n, 1;\nsetp.lt.u32 q, n, 8192;\n@q bra.uni W0;\nR0:\n"
    "D0:\n"
    "@p1 bra.uni D1;\nmov.u32 n, 0;\nW1:\nmbarrier.try_wait.parity.shared::cta.b64 q, [%81], %82;\n@q bra.uni R1;\nadd.u32 n, n, 1;\nsetp.lt.u32 q, n, 8192;\n@q bra.uni W1;\nR1:\n"
    "ld.volatile.shared.u32 %72, [%85];\n"
    "D1:\n"
    "@p2 bra.uni D2;\nmov.u32 n, 0;\nW2:\nmbarrier.try_wait.parity.shared::cta.b64 q, [%83], %84;\n@q bra.uni R2;\nadd.u32 n, n, 1;\nsetp.lt.u32 q, n, 8192;\n@q bra.uni W2;\nR2:\n"
    "ld.volatile.shared.u32 %73, [%86];\n"
    "D2:\n"
    "}\n"
    : "+f"(d[36]), "+f"(d[37]), "+f"(d[38]), "+f"(d[39]), "+f"(d[40]), "+f"(d[41]), "+f"(d[42]), "+f"(d[43]), "+f"(d[44]),
      "+f"(d[45]), "+f"(d[46]), "+f"(d[47]), "+f"(d[48]), "+f"(d[49]), "+f"(d[50]), "+f"(d[51]), "+f"(d[52]), "+f"(d[53]),
      "+f"(d[54]), "+f"(d[55]), "+f"(d[56]), "+f"(d[57]), "+f"(d[58]), "+f"(d[59]), "+f"(d[60]), "+f"(d[61]), "+f"(d[62]),
      "+f"(d[63]), "+f"(d[64]), "+f"(d[65]), "+f"(d[66]), "+f"(d[67]), "+f"(d[68]), "+f"(d[69]), "+f"(d[70]), "+f"(d[71]),
      "+f"(d[72]), "+f"(d[73]), "+f"(d[74]), "+f"(d[75]), "+f"(d[76]), "+f"(d[77]), "+f"(d[78]), "+f"(d[79]), "+f"(d[80]),
      "+f"(d[81]), "+f"(d[82]), "+f"(d[83]), "+f"(d[84]), "+f"(d[85]), "+f"(d[86]), "+f"(d[87]), "+f"(d[88]), "+f"(d[89]),
      "+f"(d[90]), "+f"(d[91]), "+f"(d[92]), "+f"(d[93]), "+f"(d[94]), "+f"(d[95]), "+f"(d[96]), "+f"(d[97]), "+f"(d[98]),
      "+f"(d[99]), "+f"(d[100]), "+f"(d[101]), "+f"(d[102]), "+f"(d[103]), "+f"(d[104]), "+f"(d[105]), "+f"(d[106]), "+f"(d[107]),
      "=&r"(v[0]), "=&r"(v[1])
    : "r"(ahi), "r"(dsc[0]), "r"(dsc[1]), "r"(dsc[2]), "r"(dsc[3]), "r"(bar[0]), "r"(bar[1]), "r"(bar[2]), "r"(bar[3]), "r"(bar[4]), "r"(bar[5]), "r"(adr[0]), "r"(adr[1]) : "memory");
}
__device__ __forceinline__ void kv_last(float* d, uint32_t* v, uint32_t ahi, const uint32_t* dsc, const uint32_t* bar, const uint32_t* adr) {
  asm volatile(
    "{\n.reg .pred p<1>, q;\n.reg .b64 da, db;\n.reg .u32 n;\n"
    "mbarrier.test_wait.parity.shared::cta.b64 p0, [%81], %82;\n"
    "mov.b64 da, {%73, %72};\nmov.b64 db, {%74, 8};\n"
    "wgmma.mma_async.sync.aligned.m64n144k16.f32.bf16.bf16 {%0, %1, %2, %3, %4, %5, %6, %7, %8, %9, %10, %11, %12, %13, %14, %15, %16, %17, %18, %19, %20, %21, %22, %23, %24, %25, %26, %27, %28, %29, %30, %31, %32, %33, %34, %35, %36, %37, %38, %39, %40, %41, %42, %43, %44, %45, %46, %47, %48, %49, %50, %51, %52, %53, %54, %55, %56, %57, %58, %59, %60, %61, %62, %63, %64, %65, %66, %67, %68, %69, %70, %71}, da, db, 1, 1, 1, 0, 1;\n"
    "mov.b64 da, {%75, %72};\nmov.b64 db, {%76, 8};\n"
    "wgmma.mma_async.sync.aligned.m64n144k16.f32.bf16.bf16 {%0, %1, %2, %3, %4, %5, %6, %7, %8, %9, %10, %11, %12, %13, %14, %15, %16, %17, %18, %19, %20, %21, %22, %23, %24, %25, %26, %27, %28, %29, %30, %31, %32, %33, %34, %35, %36, %37, %38, %39, %40, %41, %42, %43, %44, %45, %46, %47, %48, %49, %50, %51, %52, %53, %54, %55, %56, %57, %58, %59, %60, %61, %62, %63, %64, %65, %66, %67, %68, %69, %70, %71}, da, db, 1, 1, 1, 0, 1;\n"
    "mov.b64 da, {%77, %72};\nmov.b64 db, {%78, 8};\n"
    "wgmma.mma_async.sync.aligned.m64n144k16.f32.bf16.bf16 {%0, %1, %2, %3, %4, %5, %6, %7, %8, %9, %10, %11, %12, %13, %14, %15, %16, %17, %18, %19, %20, %21, %22, %23, %24, %25, %26, %27, %28, %29, %30, %31, %32, %33, %34, %35, %36, %37, %38, %39, %40, %41, %42, %43, %44, %45, %46, %47, %48, %49, %50, %51, %52, %53, %54, %55, %56, %57, %58, %59, %60, %61, %62, %63, %64, %65, %66, %67, %68, %69, %70, %71}, da, db, 1, 1, 1, 0, 1;\n"
    "mov.b64 da, {%79, %72};\nmov.b64 db, {%80, 8};\n"
    "wgmma.mma_async.sync.aligned.m64n144k16.f32.bf16.bf16 {%0, %1, %2, %3, %4, %5, %6, %7, %8, %9, %10, %11, %12, %13, %14, %15, %16, %17, %18, %19, %20, %21, %22, %23, %24, %25, %26, %27, %28, %29, %30, %31, %32, %33, %34, %35, %36, %37, %38, %39, %40, %41, %42, %43, %44, %45, %46, %47, %48, %49, %50, %51, %52, %53, %54, %55, %56, %57, %58, %59, %60, %61, %62, %63, %64, %65, %66, %67, %68, %69, %70, %71}, da, db, 1, 1, 1, 0, 1;\n"
    "wgmma.commit_group.sync.aligned;\n"
    "@p0 bra.uni D0;\nmov.u32 n, 0;\nW0:\nmbarrier.try_wait.parity.shared::cta.b64 q, [%81], %82;\n@q bra.uni R0;\nadd.u32 n, n, 1;\nsetp.lt.u32 q, n, 8192;\n@q bra.uni W0;\nR0:\n"
    "D0:\n"
    "}\n"
    : "+f"(d[36]), "+f"(d[37]), "+f"(d[38]), "+f"(d[39]), "+f"(d[40]), "+f"(d[41]), "+f"(d[42]), "+f"(d[43]), "+f"(d[44]),
      "+f"(d[45]), "+f"(d[46]), "+f"(d[47]), "+f"(d[48]), "+f"(d[49]), "+f"(d[50]), "+f"(d[51]), "+f"(d[52]), "+f"(d[53]),
      "+f"(d[54]), "+f"(d[55]), "+f"(d[56]), "+f"(d[57]), "+f"(d[58]), "+f"(d[59]), "+f"(d[60]), "+f"(d[61]), "+f"(d[62]),
      "+f"(d[63]), "+f"(d[64]), "+f"(d[65]), "+f"(d[66]), "+f"(d[67]), "+f"(d[68]), "+f"(d[69]), "+f"(d[70]), "+f"(d[71]),
      "+f"(d[72]), "+f"(d[73]), "+f"(d[74]), "+f"(d[75]), "+f"(d[76]), "+f"(d[77]), "+f"(d[78]), "+f"(d[79]), "+f"(d[80]),
      "+f"(d[81]), "+f"(d[82]), "+f"(d[83]), "+f"(d[84]), "+f"(d[85]), "+f"(d[86]), "+f"(d[87]), "+f"(d[88]), "+f"(d[89]),
      "+f"(d[90]), "+f"(d[91]), "+f"(d[92]), "+f"(d[93]), "+f"(d[94]), "+f"(d[95]), "+f"(d[96]), "+f"(d[97]), "+f"(d[98]),
      "+f"(d[99]), "+f"(d[100]), "+f"(d[101]), "+f"(d[102]), "+f"(d[103]), "+f"(d[104]), "+f"(d[105]), "+f"(d[106]), "+f"(d[107])
    : "r"(ahi), "r"(dsc[0]), "r"(dsc[1]), "r"(dsc[2]), "r"(dsc[3]), "r"(dsc[4]), "r"(dsc[5]), "r"(dsc[6]), "r"(dsc[7]), "r"(bar[0]), "r"(bar[1]) : "memory");
}
__device__ __forceinline__ void o_tail(float* d, uint32_t* v, uint32_t ahi, const uint32_t* dsc, const uint32_t* bar, const uint32_t* adr) {
  asm volatile(
    "{\n.reg .pred p<1>, q;\n.reg .b64 da, db;\n.reg .u32 n;\n"
    "mbarrier.test_wait.parity.shared::cta.b64 p0, [%42], %43;\n"
    "ld.volatile.shared.u32 %36, [%44];\n"
    "mov.b64 da, {%38, %37};\nmov.b64 db, {%39, 8};\n"
    "wgmma.mma_async.sync.aligned.m64n72k16.f32.bf16.bf16 {%0, %1, %2, %3, %4, %5, %6, %7, %8, %9, %10, %11, %12, %13, %14, %15, %16, %17, %18, %19, %20, %21, %22, %23, %24, %25, %26, %27, %28, %29, %30, %31, %32, %33, %34, %35}, da, db, 1, 1, 1, 0, 1;\n"
    "mov.b64 da, {%40, %37};\nmov.b64 db, {%41, 8};\n"
    "wgmma.mma_async.sync.aligned.m64n72k16.f32.bf16.bf16 {%0, %1, %2, %3, %4, %5, %6, %7, %8, %9, %10, %11, %12, %13, %14, %15, %16, %17, %18, %19, %20, %21, %22, %23, %24, %25, %26, %27, %28, %29, %30, %31, %32, %33, %34, %35}, da, db, 1, 1, 1, 0, 1;\n"
    "wgmma.commit_group.sync.aligned;\n"
    "@p0 bra.uni D0;\nmov.u32 n, 0;\nW0:\nmbarrier.try_wait.parity.shared::cta.b64 q, [%42], %43;\n@q bra.uni R0;\nadd.u32 n, n, 1;\nsetp.lt.u32 q, n, 8192;\n@q bra.uni W0;\nR0:\n"
    "ld.volatile.shared.u32 %36, [%44];\n"
    "D0:\n"
    "}\n"
    : "+f"(d[0]), "+f"(d[1]), "+f"(d[2]), "+f"(d[3]), "+f"(d[4]), "+f"(d[5]), "+f"(d[6]), "+f"(d[7]), "+f"(d[8]),
      "+f"(d[9]), "+f"(d[10]), "+f"(d[11]), "+f"(d[12]), "+f"(d[13]), "+f"(d[14]), "+f"(d[15]), "+f"(d[16]), "+f"(d[17]),
      "+f"(d[18]), "+f"(d[19]), "+f"(d[20]), "+f"(d[21]), "+f"(d[22]), "+f"(d[23]), "+f"(d[24]), "+f"(d[25]), "+f"(d[26]),
      "+f"(d[27]), "+f"(d[28]), "+f"(d[29]), "+f"(d[30]), "+f"(d[31]), "+f"(d[32]), "+f"(d[33]), "+f"(d[34]), "+f"(d[35]),
      "=&r"(v[0])
    : "r"(ahi), "r"(dsc[0]), "r"(dsc[1]), "r"(dsc[2]), "r"(dsc[3]), "r"(bar[0]), "r"(bar[1]), "r"(adr[0]) : "memory");
}
__device__ __forceinline__ void o_tail2(float* d, uint32_t* v, uint32_t ahi, const uint32_t* dsc, const uint32_t* bar, const uint32_t* adr) {
  asm volatile(
    "{\n.reg .pred p<2>, q;\n.reg .b64 da, db;\n.reg .u32 n;\n"
    "mbarrier.test_wait.parity.shared::cta.b64 p0, [%42], %43;\n"
    "mbarrier.test_wait.parity.shared::cta.b64 p1, [%44], %45;\n"
    "ld.volatile.shared.u32 %36, [%46];\n"
    "mov.b64 da, {%38, %37};\nmov.b64 db, {%39, 8};\n"
    "wgmma.mma_async.sync.aligned.m64n72k16.f32.bf16.bf16 {%0, %1, %2, %3, %4, %5, %6, %7, %8, %9, %10, %11, %12, %13, %14, %15, %16, %17, %18, %19, %20, %21, %22, %23, %24, %25, %26, %27, %28, %29, %30, %31, %32, %33, %34, %35}, da, db, 1, 1, 1, 0, 1;\n"
    "mov.b64 da, {%40, %37};\nmov.b64 db, {%41, 8};\n"
    "wgmma.mma_async.sync.aligned.m64n72k16.f32.bf16.bf16 {%0, %1, %2, %3, %4, %5, %6, %7, %8, %9, %10, %11, %12, %13, %14, %15, %16, %17, %18, %19, %20, %21, %22, %23, %24, %25, %26, %27, %28, %29, %30, %31, %32, %33, %34, %35}, da, db, 1, 1, 1, 0, 1;\n"
    "wgmma.commit_group.sync.aligned;\n"
    "@p0 bra.uni D0;\nmov.u32 n, 0;\nW0:\nmbarrier.try_wait.parity.shared::cta.b64 q, [%42], %43;\n@q bra.uni R0;\nadd.u32 n, n, 1;\nsetp.lt.u32 q, n, 8192;\n@q bra.uni W0;\nR0:\n"
    "D0:\n"
    "@p1 bra.uni D1;\nmov.u32 n, 0;\nW1:\nmbarrier.try_wait.parity.shared::cta.b64 q, [%44], %45;\n@q bra.uni R1;\nadd.u32 n, n, 1;\nsetp.lt.u32 q, n, 8192;\n@q bra.uni W1;\nR1:\n"
    "ld.volatile.shared.u32 %36, [%46];\n"
    "D1:\n"
    "}\n"
    : "+f"(d[0]), "+f"(d[1]), "+f"(d[2]), "+f"(d[3]), "+f"(d[4]), "+f"(d[5]), "+f"(d[6]), "+f"(d[7]), "+f"(d[8]),
      "+f"(d[9]), "+f"(d[10]), "+f"(d[11]), "+f"(d[12]), "+f"(d[13]), "+f"(d[14]), "+f"(d[15]), "+f"(d[16]), "+f"(d[17]),
      "+f"(d[18]), "+f"(d[19]), "+f"(d[20]), "+f"(d[21]), "+f"(d[22]), "+f"(d[23]), "+f"(d[24]), "+f"(d[25]), "+f"(d[26]),
      "+f"(d[27]), "+f"(d[28]), "+f"(d[29]), "+f"(d[30]), "+f"(d[31]), "+f"(d[32]), "+f"(d[33]), "+f"(d[34]), "+f"(d[35]),
      "=&r"(v[0])
    : "r"(ahi), "r"(dsc[0]), "r"(dsc[1]), "r"(dsc[2]), "r"(dsc[3]), "r"(bar[0]), "r"(bar[1]), "r"(bar[2]), "r"(bar[3]), "r"(adr[0]) : "memory");
}

DEVI void mbar_init(uint32_t b, int c) { asm volatile("mbarrier.init.shared::cta.b64 [%0], %1;" ::"r"(b), "r"(c)); }
DEVI void mbar_arrive(uint32_t b) { asm volatile("mbarrier.arrive.shared::cta.b64 _, [%0];" ::"r"(b) : "memory"); }
DEVI void mbar_expect(uint32_t b, uint32_t tx) {
  asm volatile("mbarrier.arrive.expect_tx.shared::cta.b64 _, [%0], %1;" ::"r"(b), "r"(tx) : "memory");
}
DEVI void mbar_wait(uint32_t b, uint32_t ph) {
  asm volatile(
      "{\n.reg .pred p;\n.reg .u32 n;\nmov.u32 n, 0;\n"
      "LW:\nmbarrier.try_wait.parity.shared::cta.b64 p, [%0], %1;\n"
      "@p bra LD;\nadd.u32 n, n, 1;\nsetp.lt.u32 p, n, 8192;\n@p bra LW;\nLD:\n}\n" ::"r"(b), "r"(ph)
      : "memory");
}
DEVI void mbar_wait2(uint32_t a, uint32_t pa, uint32_t b, uint32_t pb) {
  asm volatile(
      "{\n.reg .pred p, q;\n.reg .u32 n;\nmov.u32 n, 0;\n"
      "LW:\nmbarrier.try_wait.parity.shared::cta.b64 p, [%0], %1;\nmbarrier.try_wait.parity.shared::cta.b64 q, [%2], %3;\n"
      "and.pred p, p, q;\n@p bra LD;\nadd.u32 n, n, 1;\nsetp.lt.u32 p, n, 8192;\n@p bra LW;\nLD:\n}\n" ::"r"(a), "r"(pa), "r"(b), "r"(pb)
      : "memory");
}
DEVI bool elect() {
  uint32_t el;
  asm volatile("{\n.reg .pred p;\nelect.sync _|p, 0xffffffff;\nselp.u32 %0,1,0,p;\n}\n" : "=r"(el));
  return el;
}
DEVI void bulk_g2s(uint32_t dst, const void* src, uint32_t bytes, uint32_t bar) {
  asm volatile("cp.async.bulk.shared::cluster.global.mbarrier::complete_tx::bytes [%0], [%1], %2, [%3];" ::"r"(dst),
               "l"(src), "r"(bytes), "r"(bar)
               : "memory");
}
DEVI void bulk_g2s_pair(uint32_t dst, const void* src, uint32_t bytes, uint32_t bar) {
  asm volatile("cp.async.bulk.shared::cluster.global.mbarrier::complete_tx::bytes.multicast::cluster [%0], [%1], %2, [%3], %4;" ::"r"(dst),
               "l"(src), "r"(bytes), "r"(bar), "h"((uint16_t)3)
               : "memory");
}
DEVI void mbar_arrive_pair(uint32_t b) {
  asm volatile("mbarrier.arrive.shared::cta.b64 _, [%0];\nmbarrier.arrive.shared::cluster.b64 _, [%1];\n" ::"r"(b), "r"(b ^ 0x1000000u) : "memory");
}
DEVI void cluster_arrive() { asm volatile("barrier.cluster.arrive.relaxed.aligned;" ::: "memory"); }
DEVI void cluster_wait() { asm volatile("barrier.cluster.wait.aligned;" ::: "memory"); }
DEVI void tma3(uint32_t dst, const CUtensorMap* m, int c0, int c1, int c2, uint32_t bar) {
  asm volatile(
      "cp.async.bulk.tensor.3d.shared::cluster.global.mbarrier::complete_tx::bytes [%0], [%1, {%3,%4,%5}], [%2];" ::"r"(dst),
      "l"(m), "r"(bar), "r"(c0), "r"(c1), "r"(c2)
      : "memory");
}
DEVI constexpr uint32_t mkdesc(uint32_t addr, uint32_t lbo) { return ((addr & 0x3FFFF) >> 4) | ((lbo >> 4) << 16); }
DEVI void bar_sync(int id) { asm volatile("bar.sync %0, 128;" ::"r"(id) : "memory"); }
DEVI uint4 ld_msg(const void* p) {
  uint4 v;
  asm volatile("ld.relaxed.gpu.global.v4.u32 {%0,%1,%2,%3}, [%4];" : "=r"(v.x), "=r"(v.y), "=r"(v.z), "=r"(v.w) : "l"(p) : "memory");
  return v;
}
DEVI void st_msg(void* p, uint32_t a, uint32_t b, uint32_t c, uint32_t d) {
  asm volatile("st.relaxed.gpu.global.v4.u32 [%0], {%1,%2,%3,%4};" ::"l"(p), "r"(a), "r"(b), "r"(c), "r"(d) : "memory");
}
DEVI uint4 ld_gen(const void* p) {
  uint4 v;
  asm volatile("ld.relaxed.gpu.v4.u32 {%0,%1,%2,%3}, [%4];" : "=r"(v.x), "=r"(v.y), "=r"(v.z), "=r"(v.w) : "l"(p) : "memory");
  return v;
}
DEVI void st_gen(void* p, uint32_t a, uint32_t b, uint32_t c, uint32_t d) {
  asm volatile("st.relaxed.gpu.v4.u32 [%0], {%1,%2,%3,%4};" ::"l"(p), "r"(a), "r"(b), "r"(c), "r"(d) : "memory");
}
DEVI uint32_t ld_rlx(const void* p) {
  uint32_t v;
  asm volatile("ld.relaxed.gpu.global.u32 %0, [%1];" : "=r"(v) : "l"(p) : "memory");
  return v;
}
DEVI uint2 ld_rlx2(const void* p) {
  uint2 v;
  asm volatile("ld.relaxed.gpu.global.v2.u32 {%0,%1}, [%2];" : "=r"(v.x), "=r"(v.y) : "l"(p) : "memory");
  return v;
}
DEVI void st_rlx(void* p, uint32_t v) { asm volatile("st.relaxed.gpu.global.u32 [%0], %1;" ::"l"(p), "r"(v) : "memory"); }
#define spin_guard(n) if (++n > (1u << 16)) break
DEVI void wait_flags(const uint8_t* p, int word, uint32_t target) {
  uint32_t n = 0;
  p += 4 * word;
  _Pragma("unroll 1") while (__any_sync(0xffffffffu, (int)(ld_rlx(p) - target) < 0)) spin_guard(n);
  asm volatile("fence.acquire.gpu;" ::: "memory");
  asm volatile("fence.proxy.async.global;" ::: "memory");
}
DEVI void bulk_s2g(void* dst, uint32_t src, uint32_t bytes) {
  asm volatile("cp.async.bulk.global.shared::cta.bulk_group [%0], [%1], %2;" ::"l"(dst), "r"(src), "r"(bytes) : "memory");
}
#define ABL 0
DEVI void l2_prefetch(const void* p, uint32_t bytes) { if (!(ABL & 2)) asm volatile("cp.async.bulk.prefetch.L2.global [%0], %1;" ::"l"(p), "r"(bytes) : "memory"); }
DEVI void fence_async_smem() { asm volatile("fence.proxy.async.shared::cta;" ::: "memory"); }
DEVI void tma2(uint32_t dst, const CUtensorMap* m, int c0, int c1, uint32_t bar) {
  asm volatile("cp.async.bulk.tensor.2d.shared::cluster.global.mbarrier::complete_tx::bytes [%0], [%1, {%3,%4}], [%2];" ::"r"(dst),
               "l"(m), "r"(bar), "r"(c0), "r"(c1) : "memory");
}
DEVI void stsm4(uint32_t a, uint32_t r0, uint32_t r1, uint32_t r2, uint32_t r3) {
  asm volatile("stmatrix.sync.aligned.m8n8.x4.shared.b16 [%0], {%1,%2,%3,%4};" ::"r"(a), "r"(r0), "r"(r1), "r"(r2), "r"(r3) : "memory");
}
DEVI void stsm2(uint32_t a, uint32_t r0, uint32_t r1) {
  asm volatile("stmatrix.sync.aligned.m8n8.x2.shared.b16 [%0], {%1,%2};" ::"r"(a), "r"(r0), "r"(r1) : "memory");
}
DEVI uint32_t mbar_test(uint32_t b, uint32_t ph) {
  uint32_t ok;
  asm volatile("{\n.reg .pred p;\nmbarrier.test_wait.parity.shared::cta.b64 p, [%1], %2;\nselp.u32 %0,1,0,p;\n}\n"
               : "=r"(ok) : "r"(b), "r"(ph) : "memory");
  return ok;
}
DEVI void st_rlx2(void* p, uint32_t a, uint32_t b) {
  asm volatile("{\n.reg .b64 v;\nmov.b64 v, {%1,%2};\nst.relaxed.gpu.global.b64 [%0], v;\n}\n" ::"l"(p), "r"(a), "r"(b) : "memory");
}
DEVI float selp(int c, float a, float b) {
  float y;
  asm("{\n.reg .pred p;\nsetp.ne.s32 p, %3, 0;\nselp.f32 %0, %1, %2, p;\n}\n" : "=f"(y) : "f"(a), "f"(b), "r"(c));
  return y;
}
DEVI float ex2(float x) { float y; asm("ex2.approx.ftz.f32 %0, %1;" : "=f"(y) : "f"(x)); return y; }
DEVI float rcp(float x) { float y; asm("rcp.approx.ftz.f32 %0, %1;" : "=f"(y) : "f"(x)); return y; }
DEVI float sqrt_a(float x) { float y; asm("sqrt.approx.ftz.f32 %0, %1;" : "=f"(y) : "f"(x)); return y; }
DEVI void ldsm4t(uint32_t* r, uint32_t a) {
  asm volatile("ldmatrix.sync.aligned.m8n8.x4.trans.shared.b16 {%0,%1,%2,%3}, [%4];"
               : "=r"(r[0]), "=r"(r[1]), "=r"(r[2]), "=r"(r[3]) : "r"(a) : "memory");
}
DEVI void ldsm4(uint32_t* r, uint32_t a) {
  asm volatile("ldmatrix.sync.aligned.m8n8.x4.shared.b16 {%0,%1,%2,%3}, [%4];"
               : "=r"(r[0]), "=r"(r[1]), "=r"(r[2]), "=r"(r[3]) : "r"(a) : "memory");
}
DEVI uint32_t lds16(uint32_t a) {
  uint32_t v;
  asm volatile("ld.shared.u16 %0, [%1];" : "=r"(v) : "r"(a) : "memory");
  return v;
}
DEVI void sts16(uint32_t a, uint32_t x) { asm volatile("st.shared.u16 [%0], %1;" ::"r"(a), "r"(x) : "memory"); }
DEVI uint4 ldg128(const void* p) {
  uint4 v;
  asm volatile("ld.global.nc.v4.u32 {%0,%1,%2,%3}, [%4];" : "=r"(v.x), "=r"(v.y), "=r"(v.z), "=r"(v.w) : "l"(p));
  return v;
}
DEVI uint2 ldg64(const void* p) {
  uint2 v;
  asm volatile("ld.global.nc.v2.u32 {%0,%1}, [%2];" : "=r"(v.x), "=r"(v.y) : "l"(p));
  return v;
}
DEVI uint32_t ldg32(const void* p) {
  uint32_t v;
  asm volatile("ld.global.nc.u32 %0, [%1];" : "=r"(v) : "l"(p));
  return v;
}
DEVI uint4 ldcg128(const void* p) {
  uint4 v;
  asm volatile("ld.global.cg.v4.u32 {%0,%1,%2,%3}, [%4];" : "=r"(v.x), "=r"(v.y), "=r"(v.z), "=r"(v.w) : "l"(p) : "memory");
  return v;
}
DEVI uint2 ldcg64(const void* p) {
  uint2 v;
  asm volatile("ld.global.cg.v2.u32 {%0,%1}, [%2];" : "=r"(v.x), "=r"(v.y) : "l"(p) : "memory");
  return v;
}
DEVI uint32_t ldcg32(const void* p) {
  uint32_t v;
  asm volatile("ld.global.cg.u32 %0, [%1];" : "=r"(v) : "l"(p) : "memory");
  return v;
}
DEVI void stg128(void* p, uint32_t a, uint32_t b, uint32_t c, uint32_t d) {
  asm volatile("st.global.v4.u32 [%0], {%1,%2,%3,%4};" ::"l"(p), "r"(a), "r"(b), "r"(c), "r"(d) : "memory");
}
DEVI void stg32(void* p, uint32_t a) { asm volatile("st.global.u32 [%0], %1;" ::"l"(p), "r"(a) : "memory"); }
DEVI uint4 lds128(uint32_t a) {
  uint4 v;
  asm volatile("ld.shared.v4.u32 {%0,%1,%2,%3}, [%4];" : "=r"(v.x), "=r"(v.y), "=r"(v.z), "=r"(v.w) : "r"(a) : "memory");
  return v;
}
DEVI uint2 lds64(uint32_t a) {
  uint2 v;
  asm volatile("ld.shared.v2.u32 {%0,%1}, [%2];" : "=r"(v.x), "=r"(v.y) : "r"(a) : "memory");
  return v;
}
DEVI uint32_t lds32(uint32_t a) {
  uint32_t v;
  asm volatile("ld.shared.u32 %0, [%1];" : "=r"(v) : "r"(a) : "memory");
  return v;
}
DEVI void lds64f_if(bool p, float& a, float& b, uint32_t addr) {
  asm volatile("{\n.reg .pred p;\nsetp.ne.u32 p, %3, 0;\n@p ld.shared.v2.f32 {%0,%1}, [%2];\n}\n"
               : "+f"(a), "+f"(b) : "r"(addr), "r"((uint32_t)p) : "memory");
}
DEVI float ldsf(uint32_t a) { return __uint_as_float(lds32(a)); }
DEVI void sts128(uint32_t a, uint32_t x, uint32_t y, uint32_t z, uint32_t w) {
  asm volatile("st.shared.v4.u32 [%0], {%1,%2,%3,%4};" ::"r"(a), "r"(x), "r"(y), "r"(z), "r"(w) : "memory");
}
DEVI void sts64(uint32_t a, uint32_t x, uint32_t y) { asm volatile("st.shared.v2.u32 [%0], {%1,%2};" ::"r"(a), "r"(x), "r"(y) : "memory"); }
DEVI void sts32(uint32_t a, uint32_t x) { asm volatile("st.shared.u32 [%0], %1;" ::"r"(a), "r"(x) : "memory"); }
DEVI void stsf(uint32_t a, float x) { sts32(a, __float_as_uint(x)); }
DEVI uint32_t packbf(float lo, float hi) {
  uint32_t r;
  asm("cvt.rn.bf16x2.f32 %0, %1, %2;" : "=r"(r) : "f"(hi), "f"(lo));
  return r;
}
DEVI uint32_t nz(uint32_t w) { uint32_t y; asm("max.u32 %0, %1, 1;" : "=r"(y) : "r"(w)); return y; }
DEVI float blo(uint32_t w) { return __uint_as_float(w << 16); }
DEVI float bhi(uint32_t w) { return __uint_as_float(w & 0xffff0000u); }
DEVI float rbf(float x) { return __uint_as_float(packbf(0.f, x)); }
DEVI float shx(float v, int m) { return __shfl_xor_sync(0xffffffffu, v, m); }
DEVI float quad_sum(float v) { v += shx(v, 1); v += shx(v, 2); return v; }
DEVI uint32_t movm(uint32_t a) {
  uint32_t d;
  asm volatile("movmatrix.sync.aligned.m8n8.trans.b16 %0, %1;" : "=r"(d) : "r"(a));
  return d;
}
DEVI void mma16(float* d, uint32_t a0, uint32_t a1, uint32_t a2, uint32_t a3, uint32_t b0, uint32_t b1) {
  asm("mma.sync.aligned.m16n8k16.row.col.f32.bf16.bf16.f32 {%0,%1,%2,%3},{%4,%5,%6,%7},{%8,%9},{%0,%1,%2,%3};"
      : "+f"(d[0]), "+f"(d[1]), "+f"(d[2]), "+f"(d[3])
      : "r"(a0), "r"(a1), "r"(a2), "r"(a3), "r"(b0), "r"(b1));
}
DEVI void mma8z(float* d, uint32_t a0, uint32_t a1, uint32_t b0) {
  asm("mma.sync.aligned.m16n8k8.row.col.f32.bf16.bf16.f32 {%0,%1,%2,%3},{%4,%5},{%6},{%7,%7,%7,%7};"
      : "=f"(d[0]), "=f"(d[1]), "=f"(d[2]), "=f"(d[3])
      : "r"(a0), "r"(a1), "r"(b0), "f"(0.f));
}
DEVI void mma8(float* d, uint32_t a0, uint32_t a1, uint32_t b0) {
  asm("mma.sync.aligned.m16n8k8.row.col.f32.bf16.bf16.f32 {%0,%1,%2,%3},{%4,%5},{%6},{%0,%1,%2,%3};"
      : "+f"(d[0]), "+f"(d[1]), "+f"(d[2]), "+f"(d[3])
      : "r"(a0), "r"(a1), "r"(b0));
}
DEVI void mma16z(float* d, uint32_t a0, uint32_t a1, uint32_t a2, uint32_t a3, uint32_t b0, uint32_t b1) {
  asm("mma.sync.aligned.m16n8k16.row.col.f32.bf16.bf16.f32 {%0,%1,%2,%3},{%4,%5,%6,%7},{%8,%9},{%10,%10,%10,%10};"
      : "=f"(d[0]), "=f"(d[1]), "=f"(d[2]), "=f"(d[3])
      : "r"(a0), "r"(a1), "r"(a2), "r"(a3), "r"(b0), "r"(b1), "f"(0.f));
}
DEVI void mma16a(float* d, const uint32_t* a, uint32_t b0, uint32_t b1) { mma16(d, a[0], a[1], a[2], a[3], b0, b1); }
DEVI float ln_sd(float var) { return rbf(sqrt_a(rbf(rbf(var) + kEps))); }
DEVI int fkey(float f) { int i = __float_as_int(f); return i ^ ((i >> 31) & 0x7fffffff); }
DEVI float sigmoidf(float x) { return rcp(1.f + ex2(-1.4426950408889634f * x)); }

DEVI uint32_t probe_stage(uint32_t pa) { return lds32(pa); }
DEVI void check_stage(uint32_t pv, uint32_t fa, const uint8_t* src) {
  if (__any_sync(0xffffffffu, pv == 0)) {
    uint32_t n = 0, tid;
    asm volatile("mov.u32 %0, %%tid.x;" : "=r"(tid));
    const uint32_t fo = (tid & 96) * 8 + (tid & 16) * 64 + (tid & 15) * 16;
    fa += fo; src += fo;
#pragma unroll 1
    for (uint32_t o = 0; o < 8192;) {
      const uint4 v = ld_msg(src + o);
      sts128(fa + o, v.x, v.y, v.z, v.w);
      if (!__any_sync(0xffffffffu, min(min(v.x, v.y), min(v.z, v.w)) == 0) || ++n > (1u << 16)) o += 2048;
    }
    fence_async_smem();
    __syncwarp();
  }
}

struct Params {
  const uint8_t *x, *wqkv, *wo, *wr, *wg, *wu, *wd;
  uint8_t* out;
  Scratch* g;
};

struct Maps { CUtensorMap wq, x, wo, xr, wg, wu, out; };
#define QPRE 2
#define FDEPTH 2
#define PFSTART 700
#define PFPRE 0
#define PFPER 3
#define PFNS 200
#define XSTART 100
#define XSTEP 300
#define PKSTEP 350
#define WPOLL 300
#define CSROUND 0
#define XLROUND 0
#define CLNS 20
#define FSTART 4000
#define XLSTART 3000
#define WGAP0 0
#define XGAP 150
#define WEARLY 1

__global__ void __cluster_dims__(2, 1, 1) __launch_bounds__(512, 1) fused_kernel(const Params p, const __grid_constant__ Maps tm) {
  extern __shared__ __align__(1024) uint8_t smem_raw[];
  constexpr uint32_t sbd = 1024;
  int cta;
  uint32_t rank;
  {
    asm volatile("mov.u32 %0, %%cluster_ctarank;" : "=r"(rank));
    const int c = blockIdx.x >> 1, t = c - 4, u = c - 36, uq = (u * 37) >> 8;
    const int gpc = c < 4 ? 0 : c < 36 ? t & 7 : 1 + u - 7 * uq, idx = c < 4 ? 4 + c : c < 36 ? t >> 3 : 4 + uq;
    cta = __shfl_sync(0xffffffffu, (2 * gpc + (int)rank) * 8 + idx, 0);
  }
  const uint32_t sb = sbd | (rank << 24);
  if ((uint32_t)__cvta_generic_to_shared(smem_raw) != sb) return;
  if (threadIdx.x < 27) asm volatile("prefetch.global.L2 [%0];" ::"l"(p.wqkv + blockIdx.x * 3456 + threadIdx.x * 128));
  const int m = cta >> 3, r = cta & 7;
  const int warp = __shfl_sync(0xffffffffu, (int)(threadIdx.x >> 5), 0);
  const int lane = threadIdx.x & 31;
  uint8_t* const gb = reinterpret_cast<uint8_t*>(p.g);
  auto pack = [&]() -> uint32_t {
    const uint32_t t0 = clock();
    const uint32_t tp = sb + SM_W + 3 * WSTAGE + warp * 2304, bar = sb + SM_PART + 8 * warp;
    uint8_t* flag = GA(flagP, (12 * r + warp) * 128 + 4 * m);
    if (warp > 1) {
      asm volatile("bar.sync 4, 512;" ::: "memory");
      cluster_arrive();
      while ((uint32_t)clock() - t0 < (warp - 1) * PKSTEP) {}
    }
    if (elect()) {
      mbar_init(bar, 1);
      asm volatile("fence.mbarrier_init.release.cluster;" ::: "memory");
      mbar_expect(bar, 2304);
      if (warp < 9) tma3(tp, &tm.wq, 72 * r, 64 * warp + 8 * (m >> 1), m & 1, bar);
      else tma2(tp, &tm.wo, 72 * r, 192 * (warp - 9) + 24 * (m >> 1) + 8 * (m & 1), bar);
    }
    __syncwarp();
    if (lane == 0) st_rlx(flag, 0);
    if (warp <= 1) { asm volatile("bar.sync 4, 512;" ::: "memory"); cluster_arrive(); }
    mbar_wait(sb + B_EP, 0);
    const uint32_t epoch = lds32(sb + SM_EP);
    uint8_t* dst = GC(wpack, (r * 12 + warp) * WSTAGE + (27 * (m >> 1) + 14 * (m & 1)) * 128 + lane * 16);
    mbar_wait(bar, 0);
#pragma unroll
    for (int i = 0; i < 4; i++) {
      const int u = 4 * i + (lane >> 3) + 5 * (m & 1);
      const uint4 x = lds128(tp + (lane & 7) * 144 + u * 16 + (u >= 9 ? 1008 : 0));
      if (u < 14 + 4 * (m & 1)) stg128(dst + 512 * i, nz(x.x), nz(x.y), nz(x.z), nz(x.w));
    }
    if (lane == 0) st_rlx(flag, epoch);
    fence_async_smem();
    __syncwarp();
    if (elect()) asm volatile("mbarrier.inval.shared::cta.b64 [%0];" ::"r"(bar) : "memory");
    cluster_wait();
    return epoch;
  };

  if (warp >= 12) {
    asm volatile("setmaxnreg.dec.sync.aligned.u32 24;");
    uint32_t e0 = 0;
    if (warp == 15) e0 = ld_rlx(GA(epoch, 32 * cta));
    if (elect()) {
#pragma unroll
      for (int i = 0; i < NBAR; i++)
        if (warp - 12 == (i * 4) / NBAR)
          mbar_init(sb + SM_BAR + 8 * i, i < 4 ? 1 : i < 8 ? 16 : i < 16 ? 2 : i == (B_PKF - SM_BAR) / 8 ? 8 : i < NBAR4 ? 4 : 1);
      asm volatile("fence.mbarrier_init.release.cluster;" ::: "memory");
    }
    __syncwarp();
    asm volatile("bar.sync 4, 512;" ::: "memory");
    cluster_arrive();
    if (warp == 12) {
      mbar_wait(sb + B_EP, 0);
      cluster_wait();
      const uint32_t epoch = lds32(sb + SM_EP);
      const uint32_t half = (m & 1) * (WSTAGE / 2);
      const uint8_t* src = GC(wpack, r * 12 * WSTAGE + half);
      __nanosleep(WPOLL);
#pragma unroll 1
      for (int g = 0; g < 24; g++) {
        const uint32_t slot = g & 3;
        if (g < 12) wait_flags(GA(flagP, (12 * r + g) * 128), lane & 15, epoch);
        if (g == 0) TRL(3, 0);
        if (g == 3) mbar_wait(sb + B_PKF, 0);
        if (g >= 4) mbar_wait(sb + B_WEMPTY + 8 * slot, ((g >> 2) - 1) & 1);
        if (elect()) {
          const uint32_t bar = sb + (g < 12 ? B_WL : B_WFULL) + 8 * slot;
          mbar_expect(bar, WSTAGE);
          bulk_g2s_pair(sb + SM_W + slot * WSTAGE + half, src + (g >= 12 ? g - 12 : g) * WSTAGE, WSTAGE / 2, bar);
        }
      }
    } else if (warp <= 14) {
      const int w = warp - 13;
      const uint32_t full = sb + B_XFULL + 32 * w, empty = sb + B_XEMPTY + 32 * w, ring = sb + SM_X + w * 4 * XSTAGE;
      mbar_wait(sb + B_EP, 0);
      cluster_wait();
      const uint32_t epoch = lds32(sb + SM_EP);
      if (lane < 4) st_rlx(GA(flagX, 128 * (2 * m + w) + 16 * r + 4 * lane), epoch * 4);
#pragma unroll 1
      for (int gemm = 0; gemm < 4; gemm++) {
        const uint8_t* src = GC(act, (gemm - 1) * ACT + (2 * m + w) * 73728);
        if (gemm & 1) {
          mbar_wait(empty, 0);
          if (elect()) {
            mbar_expect(sb + B_RES + 8 * w, 9216);
            if (gemm == 1) tma3(ring, &tm.xr, 72 * r, w, m * 64, sb + B_RES + 8 * w);
            else bulk_g2s(ring, GC(act, ACT + (2 * m + w) * 73728 + r * 9216), 9216, sb + B_RES + 8 * w);
          }
        }
        if (gemm > 0) {
          mbar_wait(gemm & 1 ? sb + B_RC + 8 * w : empty, gemm & 1 ? gemm >> 1 : 1);
          TRL(3, 11 + w * 4 + gemm);
          wait_flags(GA(flagX, 128 * (2 * m + w)), lane, epoch * 4 + gemm);
          TRL(3, 1 + w * 4 + gemm);
        }
        if (gemm & 1) {
          if (elect()) {
#pragma unroll
            for (int s = 0; s < 9; s++) {
              if (s >= 4) mbar_wait(empty + 8 * (s & 3), s == 4);
              mbar_expect(full + 8 * (s & 3), XSTAGE);
              bulk_g2s(ring + (s & 3) * XSTAGE, src + s * XSTAGE, XSTAGE, full + 8 * (s & 3));
              mbar_arrive(full + 8 * (s & 3));
            }
          }
          __syncwarp();
          continue;
        }
        bool gate = gemm == 2;
#pragma unroll 1
        for (int s = 0; s < (gemm == 2 ? 11 : 9); s++) {
          const uint32_t slot = s & 3;
          if (gemm == 0 && s < 4) __nanosleep(s ? XSTEP : XSTART);
          if (gemm == 2 && s > 0 && s < 4) __nanosleep(XGAP);
          if (s >= 4) mbar_wait(empty + 8 * slot, s >> 3);
          const bool hold = gate && s >= 4 && mbar_test(sb + B_WANT, 0);
          if (lane == 0 && !hold && (gemm != 2 || (s & ~1) != 2)) mbar_arrive(full + 8 * (gemm == 2 && s >= 4 ? (s - 2) & 3 : slot));
          if (s < 9 && elect()) {
            mbar_expect(full + 8 * slot, XSTAGE);
            if (gemm == 0) tma3(ring + slot * XSTAGE, &tm.x, s * 64, w, m * 64, full + 8 * slot);
            else bulk_g2s(ring + slot * XSTAGE, src + s * XSTAGE, XSTAGE, full + 8 * slot);
          }
          if (hold) {
            mbar_wait(sb + B_DONE, 0);
            gate = false;
            if (lane == 0) mbar_arrive(full + 8 * ((s - 2) & 3));
          }
        }
      }
    } else {
      const uint32_t epoch = e0 + 1;
      if (lane == 0) {
        sts32(sb + SM_EP, epoch);
        mbar_arrive(sb + B_EP);
      }
      __syncwarp();
      cluster_wait();
      int pi = lane;
      auto prefetch = [&]() {
        const uint8_t* pp = pi < 648 ? ((cta & 1) ? p.wu : p.wg) + (uint32_t)(((pi / 72) * 63 + (cta >> 1)) * 9216 + pi * 128)
                                     : p.wd + (uint32_t)((cta * 324 + pi - 648) * 128);
        if (pi < 972 && !(ABL & 2)) asm volatile("prefetch.global.L2 [%0];" ::"l"(pp));
        pi += 32;
      };
      __nanosleep(PFSTART);
#pragma unroll 1
      for (int i = 0; i < PFPRE; i++) { prefetch(); __nanosleep(PFNS); }
      uint32_t ph = 0;
#pragma unroll 1
      for (int g = 0; g < 12; g++) {
        const uint32_t slot = g & 3;
#pragma unroll 1
        for (int n = 0; n < 4096; n++) {
          mbar_wait(sb + B_WL + 8 * slot, (ph >> slot) & 1);
          ph ^= 1 << slot;
          const uint32_t a = sb + SM_W + slot * WSTAGE + lane * 128 + (lane & 3) * 32 + (lane >> 2) * 4;
          uint32_t mn = lds32(a + (lane < 24 ? 6 * 4096 : 0));
#pragma unroll
          for (int u = 0; u < 6; u++) mn = min(mn, lds32(a + u * 4096));
          if (!__any_sync(0xffffffffu, mn == 0) || (ABL & 32)) break;
          fence_async_smem();
          __syncwarp();
          if (elect()) {
            mbar_expect(sb + B_WL + 8 * slot, WSTAGE);
            bulk_g2s(sb + SM_W + slot * WSTAGE, GC(wpack, (r * 12 + g) * WSTAGE), WSTAGE, sb + B_WL + 8 * slot);
          }
        }
        if (lane == 0) mbar_arrive(sb + B_WFULL + 8 * slot);
#pragma unroll 1
        for (int i = 0; i < PFPER; i++) prefetch();
      }
      TRL(3, 22);
      mbar_wait(sb + B_FD, 0);
      TRL(3, 20);
      if (elect()) {
        mbar_expect(sb + B_WD, (ABL & 64) ? 0 : 41472);
#pragma unroll 4
        for (int i = 0; i < 36; i++)
          if (!(ABL & 64)) bulk_g2s(sb + SM_WD + i * WDP, p.wd + (uint32_t)(cta * 36 + i) * 1152u, 1152, sb + B_WD);
      }
      __syncwarp();
      TRL(3, 21);
      {
        const uint32_t epoch = e0, h = (lane >> 1) * 128 + (lane & 1) * 16;
        mbar_wait(sb + B_OS, 0);
#pragma unroll 1
        for (int i = cta; i < 1296; i += 128) { stg128(GC(wpack, i * 2048 + (lane & 6) * 16 + h), 0, 0, 0, 0); __nanosleep(CLNS); }
#pragma unroll 1
        for (int i = 0; i < 5; i++) {
          stg128(GC(halo, (cta * 5 + i) * 2048 + h), 0, 0, 0, 0);
          if (i < 4 || lane < 16) stg128(GC(candrow, cta * 2304 + i * 512 + lane * 16), 0, 0, 0, 0);
          stg128(GC(act, (cta * 27 + i) * 2048 + 96 + h), 0, 0, 0, 0);
          __nanosleep(CLNS);
        }
        mbar_wait(sb + B_OS, 1);
#pragma unroll 1
        for (int i = 5; i < 27; i++) { stg128(GC(act, (cta * 27 + i) * 2048 + 96 + h), 0, 0, 0, 0); __nanosleep(CLNS); }
      }
      TRL(3, 23);
    }
  } else if (warp >= 8) {
    asm volatile("setmaxnreg.inc.sync.aligned.u32 200;");
    const int sw = warp - 8, s = threadIdx.x - 256;
    const uint32_t t0 = clock();
    const uint32_t epoch = pack();
    TR(2, 0);
    auto ffn_round = [&](int u) {
      const uint32_t bar = sb + B_FF + 8 * (u % FDEPTH), dst = sb + SM_WD + (u % FDEPTH) * FSLOT;
      if (ABL & 4) { mbar_arrive(bar); return; }
      mbar_expect(bar, 12288);
      tma2(dst, &tm.wg, ((cta * 72) >> 5) << 4, 64 * u, bar);
      tma2(dst + FSLOT / 2, &tm.wu, ((cta * 72) >> 5) << 4, 64 * u, bar);
    };
    const int xi = 8 * r + 4 * (sw >> 1) + (lane >> 3);
    uint4 xv[9];
    uint32_t wr[9];
        {
          const uint8_t* xsrc = p.x + (uint32_t)((128 * m + 2 * xi + (sw & 1)) * 1152 + (lane & 7) * 16);
#pragma unroll
          for (int u = 0; u < 9; u++) xv[u] = ldg128(xsrc + u * 128);
#pragma unroll
          for (int u = 0; u < 9; u++) wr[u] = sw == 0 ? ldg32(p.wr + 128 * u + 4 * lane) : 0u;
        }
    {
      asm volatile("bar.sync 15, 384;" ::: "memory");
      const int u = (s >> 3) + 5 * (m & 1);
      uint4 v[9];
#pragma unroll
      for (int g = 0; g < 9; g++) v[g] = lds128(sb + SM_W + 3 * WSTAGE + g * 2304 + u * 16 + (u >= 9 ? 1008 : 0) + (s & 7) * 144);
      fence_async_smem();
      __syncwarp();
      if (lane == 0) mbar_arrive_pair(sb + B_PKF);
      float a[8] = {};
#pragma unroll
      for (int g = 0; g < 9; g++) {
        a[0] += blo(v[g].x); a[1] += bhi(v[g].x); a[2] += blo(v[g].y); a[3] += bhi(v[g].y);
        a[4] += blo(v[g].z); a[5] += bhi(v[g].z); a[6] += blo(v[g].w); a[7] += bhi(v[g].w);
      }
      const bool b4 = s & 4, b2 = s & 2;
      float b[4];
#pragma unroll
      for (int e = 0; e < 4; e++) b[e] = (b4 ? a[4 + e] : a[e]) + shx(b4 ? a[e] : a[4 + e], 4);
      float c0 = (b2 ? b[2] : b[0]) + shx(b2 ? b[0] : b[2], 2), c1 = (b2 ? b[3] : b[1]) + shx(b2 ? b[1] : b[3], 2);
      c0 += shx(c0, 1); c1 += shx(c1, 1);
      if (!(s & 1) && (s >> 3) < 14 - (m & 1))
        st_rlx2(GA(colpart, (8 * r + (m >> 1)) * 864 + 14 * (m & 1) * 32 + 4 * s), __float_as_uint(c0), (__float_as_uint(c1) & ~15u) | (epoch & 15));
      TR(2, 1);
    }
    if (sw == 0) {
      while ((uint32_t)clock() - t0 < FSTART) {}
      if (elect()) {
#pragma unroll
        for (int u = 0; u < FDEPTH; u++) ffn_round(u);
      }
      __syncwarp();
    }
        {
          float sum = 0.f;
#pragma unroll
          for (int u = 0; u < 9; u++)
            sum += (blo(xv[u].x) + bhi(xv[u].x)) + (blo(xv[u].y) + bhi(xv[u].y)) + (blo(xv[u].z) + bhi(xv[u].z)) + (blo(xv[u].w) + bhi(xv[u].w));
          sum += shx(sum, 1); sum += shx(sum, 2); sum += shx(sum, 4);
          const float mu = sum * (1.f / kD);
          float q = 0.f;
#pragma unroll
          for (int u = 0; u < 9; u++) {
            const uint32_t ww[4] = {xv[u].x, xv[u].y, xv[u].z, xv[u].w};
#pragma unroll
            for (int e = 0; e < 4; e++) {
              const float d0 = blo(ww[e]) - mu, d1 = bhi(ww[e]) - mu;
              q = fmaf(d0, d0, q); q = fmaf(d1, d1, q);
            }
          }
          q += shx(q, 1); q += shx(q, 2); q += shx(q, 4);
          const float rho = rcp(ln_sd(q * (1.f / kD)));
          if ((lane & 7) == 0) st_msg(GA(stats0, 16 * (128 * m + 64 * (sw & 1) + xi)), __float_as_uint(rho), __float_as_uint(mu), 0, epoch);
          if (sw == 0) {
            float wsum = 0.f;
#pragma unroll
            for (int u = 0; u < 9; u++) wsum += blo(wr[u]) + bhi(wr[u]);
#pragma unroll
            for (int o = 1; o < 32; o <<= 1) wsum += shx(wsum, o);
            if (lane == 0) stsf(sb + SM_WSUM, wsum);
          }
          TR(2, 3);
        }
    uint32_t WF[9][4][4];
    {
      const int g = lane >> 2, t = lane & 3;
      const uint32_t c0 = (cta * 72) & 31, ra = 2 * (lane & 6) + (lane & 1) + 2 * ((lane >> 4) ^ ((lane >> 2) & 1));
      const uint32_t fa = sb + SM_WD + (16 * sw + ra) * 128 + ((((c0 + 8) >> 4) + ((lane >> 3) & 1)) << 4);
      const uint32_t fa0 = fa ^ ((ra & 7) << 4), fa1 = (fa + 32) ^ ((ra & 7) << 4);
      const uint32_t rl = 2 * (g & 6) + (g & 1) + 2 * (g >> 2);
      const uint32_t fl = sb + SM_WD + 16 * sw * 128 + (t >> 1) * (FSLOT / 2) + c0 + 64 * (~cta & 1) + 4 * (t & 1);
      const uint32_t fl0 = (fl + rl * 128) ^ ((rl & 7) << 4), fl1 = (fl + (rl ^ 2) * 128) ^ (((rl ^ 2) & 7) << 4);
#pragma unroll
      for (int i = 0; i < 9; i++) {
        mbar_wait(sb + B_FF + 8 * (i % FDEPTH), (i / FDEPTH) & 1);
#pragma unroll
        for (int e = 0; e < 4; e++) ldsm4t(WF[i][e], ((e & 1) ? fa1 : fa0) + (e >> 1) * (FSLOT / 2) + (i % FDEPTH) * FSLOT);
        const uint32_t v0 = lds32(fl0 + (i % FDEPTH) * FSLOT), v1 = lds32(fl1 + (i % FDEPTH) * FSLOT);
        if (i + FDEPTH < 9 || i == 8) {
          fence_async_smem();
          bar_sync(3);
          if (sw == 0 && elect()) {
            if (i < 8) ffn_round(i + FDEPTH);
            else mbar_arrive(sb + B_FD);
          }
        }
        sts64(sb + SM_LEFT + i * 1024 + s * 8, movm(v0), movm(v1));
        if (i == CSROUND) {
          TR(2, 21);
          float c0, c1;
          uint4 s0;
          uint32_t nc = 0;
          _Pragma("unroll 1") while (true) {
            s0 = ld_msg(GA(stats0, 16 * (128 * m + s)));
            uint32_t bad = s0.w != epoch;
            c0 = 0.f; c1 = 0.f;
#pragma unroll
            for (int mm = 0; mm < 8; mm++) {
              const uint2 v = ld_rlx2(GA(colpart, 8 * 864 * r + 8 * min(s, 107)) + mm * 864);
              c0 += __uint_as_float(v.x); c1 += __uint_as_float(v.y & ~15u);
              bad |= v.y ^ epoch;
            }
            if (!__any_sync(0xffffffffu, bad & 15)) break;
            spin_guard(nc);
          }
          if (s < 108) {
            const uint32_t hi = packbf(c0, c1);
            sts32(sb + SM_COLSUM + 32 * (s >> 2) + 4 * (s & 3), hi);
            sts32(sb + SM_COLSUM + 32 * (s >> 2) + 4 * (s & 3) + 16, packbf(c0 - blo(hi), c1 - bhi(hi)));
          }
          sts32(sb + SM_ROWC + 4 * s, s0.x);
          sts64(sb + SM_ROWM + 8 * s, s0.y, __float_as_uint(1.f));
          fence_async_smem();
          __syncwarp();
          if (lane == 0) mbar_arrive(sb + B_COLSUM);
          TR(2, 13);
        }
      }
      TR(2, 4);
    }
    {
      const uint32_t y = epoch * 2 - 1;
      st_msg(GA(ypart, (s >> 1) * 4096 + cta * 32 + (s & 1) * 16), y, y, y, y);
      if (s < 16) {
        st_msg(GA(ypart, (64 + (s >> 1)) * 4096 + cta * 32 + (s & 1) * 16), y, y, y, y);
        st_rlx(GA(fixmsg, 1024 * r + 64 * m + 4 * s), epoch - 1);
      }
      if (s < 64 && cta < 72) st_rlx(GA(x2msg, (s >> 3) * 2304 + 32 * cta + 4 * (s & 7)), epoch - 1);
    }
#pragma unroll 1
    for (int L = 0; L < 2; L++) {
      const uint32_t tag = epoch * 2 + L;
      int s0 = __shfl_sync(0xffffffffu, (int)threadIdx.x + L, threadIdx.x & 31) - L - 256;
#define RELANE asm volatile("" : "+r"(s0)); const int s = s0, lane = s & 31, g = lane >> 2, t = lane & 3; (void)g; (void)t
      RELANE;
      const uint8_t* crow = GC(candrow, L * 128 * 1152);
      const uint8_t* cptr = GA(cand, (8 * L + r) * 2048 + 16 * s);
      asm volatile("" : "+l"(crow), "+l"(cptr));
      mbar_wait2(sb + B_WD, 0, sb + B_EPI, L);
      uint32_t win;
      {
        uint32_t c, n = 0;
        _Pragma("unroll 1") while (true) {
          c = ld_rlx(cptr) ^ (epoch & 0x7f);
          if (!__any_sync(0xffffffffu, c & 0x7f)) break;
          spin_guard(n);
        }
        const int wm = __reduce_max_sync(0xffffffffu, (int)(c | s));
        if (lane == 0) sts32(sb + SM_RED + 4 * sw, wm);
        bar_sync(3);
        const uint4 v = lds128(sb + SM_RED);
        win = max(max((int)v.x, (int)v.y), max((int)v.z, (int)v.w));
      }
      crow += (win & 127) * 1152;
      if (s == 0) {
        if (L == 0 && WEARLY) mbar_arrive(sb + B_WANT);
        sts32(sb + SM_SEL + 4 * L, win & 0x7ff);
        mbar_arrive(sb + B_IDX + 8 * L);
      }
      TR(2, 5 + 10 * L);
      uint2 xw[9];
      {
        if (sw < 3) {
          uint4 v;
          uint32_t n = 0;
          _Pragma("unroll 1") while (true) {
            v = ld_msg(crow + 16 * min(s, 71));
            if (!__any_sync(0xffffffffu, min(min(v.x, v.y), min(v.z, v.w)) == 0)) break;
            spin_guard(n);
          }
          if (s < 72) sts128(sb + SM_PART + 16 * s, v.x, v.y, v.z, v.w);
        }
        bar_sync(3);
#pragma unroll
        for (int i = 0; i < 9; i++) xw[i] = lds64(sb + SM_PART + 128 * i + 32 * sw + 8 * t);
      }
      if (L == 0 && !WEARLY && s == 0) mbar_arrive(sb + B_WANT);
      TR(2, 6 + 10 * L);
      {
        float a[4][4] = {}, al[4] = {};
#pragma unroll
        for (int i = 0; i < 9; i++) {
          const uint2 wl = lds64(sb + SM_LEFT + s * 8 + i * 1024);
#pragma unroll
          for (int e = 0; e < 4; e++) mma16a(a[e], WF[i][e], xw[i].x, xw[i].y);
          mma8(al, wl.x, wl.y, (g & 1) ? xw[i].y : xw[i].x);
        }
        bar_sync(3);
        const uint32_t pp = sb + SM_PART + ((t >> 1) * 36 + 16 * (t & 1) + g + 4 * (cta & 1)) * 16 + 4 * sw;
        stsf(pp, selp(t & 2, selp(t & 1, a[3][0], a[2][0]), selp(t & 1, a[1][0], a[0][0])));
        stsf(pp + 128, selp(t & 2, selp(t & 1, a[3][2], a[2][2]), selp(t & 1, a[1][2], a[0][2])));
        stsf(sb + SM_PART + ((g >> 2) * 36 + 32 * (~cta & 1) + (g & 3)) * 16 + 4 * sw, al[0] + al[3]);
      }
      {
        RELANE;
        const uint32_t wa = sb + SM_WD + 288 * sw + ((lane >> 3) & 1) * 16 + ((lane & 7) + 8 * (lane >> 4)) * WDP;
        const uint32_t wb = sb + SM_WD + 288 * sw + ((lane >> 3) & 1) * 16 + (32 + (lane & 3)) * WDP;
        uint32_t f[4][4];
#pragma unroll
        for (int u = 0; u < 4; u++) ldsm4t(f[u], wa + 32 * (u & 1) + (u >> 1) * 16 * WDP);
        bar_sync(3);
        {
          float hv[2];
#pragma unroll
          for (int e = 0; e < 2; e++) {
            const uint32_t pp = sb + SM_PART + 16 * (e ? 32 + t : lane);
            const uint4 pg = lds128(pp), pu = lds128(pp + 576);
            const float gp = rbf((__uint_as_float(pg.x) + __uint_as_float(pg.y)) + (__uint_as_float(pg.z) + __uint_as_float(pg.w)));
            const float u = rbf((__uint_as_float(pu.x) + __uint_as_float(pu.y)) + (__uint_as_float(pu.z) + __uint_as_float(pu.w)));
            hv[e] = rbf(gp * sigmoidf(gp)) * u;
          }
          const uint32_t hh = packbf(hv[0], hv[1]);
          sts16(sb + SM_H + 80 * sw + 2 * lane, hh);
          sts16(sb + SM_H + 80 * sw + 64 + 2 * t, hh >> 16);
          __syncwarp();
        }
        TR(2, 7 + 10 * L);
        uint32_t hp[5];
#pragma unroll
        for (int i = 0; i < 4; i++) hp[i] = lds32(sb + SM_H + 80 * sw + 16 * i + 4 * t);
        hp[4] = lds32(sb + SM_H + 80 * sw + 64 + 4 * (t & 1));
        float Y[4] = {}, Z[4] = {}, C[4] = {};
        {
          uint32_t e0[4], e1[4], e2[4];
          const uint32_t wq = wb + 32 * (((lane >> 2) & 1) + 2 * (lane >> 4));
          ldsm4t(e0, wq); ldsm4t(e1, wq + 128); ldsm4t(e2, wb + 256);
          mma16a(Y, e0, g == (t >> 1) ? hp[4] : 0u, g == 2 + (t >> 1) ? hp[4] : 0u);
          mma16a(Z, e1, g == 4 + (t >> 1) ? hp[4] : 0u, g == 6 + (t >> 1) ? hp[4] : 0u);
          mma8(C, e2[0], e2[1], t < 2 ? hp[4] : 0u);
        }
#pragma unroll
        for (int u = 0; u < 4; u++) {
          const uint32_t wn = wa + 64 * (u + 1);
          const bool p0 = g == 2 * u, p1 = g == 2 * u + 1;
          mma16a(Y, f[0], p0 ? hp[0] : 0u, p0 ? hp[1] : 0u);
          mma16a(Z, f[1], p1 ? hp[0] : 0u, p1 ? hp[1] : 0u);
          ldsm4t(f[0], wn);
          if (u < 3) ldsm4t(f[1], wn + 32);
          mma16a(Y, f[2], p0 ? hp[2] : 0u, p0 ? hp[3] : 0u);
          mma16a(Z, f[3], p1 ? hp[2] : 0u, p1 ? hp[3] : 0u);
          ldsm4t(f[2], wn + 16 * WDP);
          if (u < 3) ldsm4t(f[3], wn + 32 + 16 * WDP);
        }
        mma16a(C, f[0], hp[0], hp[1]);
        mma16a(C, f[2], hp[2], hp[3]);
#pragma unroll
        for (int e = 0; e < 4; e++) Y[e] += Z[e];
        const uint32_t t4 = tag & 15;
        {
          uint8_t* yo = GA(ypart, (18 * sw + 4 * t) * 4096 + cta * 32 + 4 * g);
#pragma unroll
          for (int e = 0; e < 4; e++) st_rlx(yo + (2 * (e & 1) + (e >> 1)) * 4096, (__float_as_uint(Y[e]) & ~15u) | t4);
          if (t < 2) st_rlx(yo + (16 - 3 * t) * 4096, (__float_as_uint(t ? C[2] : C[0]) & ~15u) | t4);
          if (L == 0 && lane == 0) mbar_arrive(sb + B_DONE);
        }
      }
      TR(2, 8 + 10 * L);
      if (cta < 72) {
        RELANE;
        const uint32_t xn = ld_rlx(GC(candrow, (L * 128 + (win & 127)) * 1152 + 16 * cta + 2 * ((s & 6) ^ (2 * (cta & 1)))));
        const uint4 cm = ld_msg(GA(cand, (8 * L + r) * 2048 + 16 * (win & 127)));
        const uint8_t* yp = GA(ypart, cta * 4096 + s * 16);
        uint4 u0, u1;
        uint32_t n = 0;
        _Pragma("unroll 1") while (true) {
          u0 = ld_msg(yp);
          u1 = ld_msg(yp + 2048);
          const uint32_t t4 = tag & 15;
          u0.x ^= t4; u0.y ^= t4; u0.z ^= t4; u0.w ^= t4; u1.x ^= t4; u1.y ^= t4; u1.z ^= t4; u1.w ^= t4;
          if (!__any_sync(0xffffffffu, (u0.x | u0.y | u0.z | u0.w | u1.x | u1.y | u1.z | u1.w) & 15)) break;
          spin_guard(n);
        }
        const float a0 = __uint_as_float(u0.x) + __uint_as_float(u1.x), a1 = __uint_as_float(u0.y) + __uint_as_float(u1.y);
        const float a2 = __uint_as_float(u0.z) + __uint_as_float(u1.z), a3 = __uint_as_float(u0.w) + __uint_as_float(u1.w);
        const bool b4 = lane & 4, b2 = lane & 2;
        const float c0 = (b4 ? a2 : a0) + shx(b4 ? a0 : a2, 4), c1 = (b4 ? a3 : a1) + shx(b4 ? a1 : a3, 4);
        float d = (b2 ? c1 : c0) + shx(b2 ? c0 : c1, 2);
        d += shx(d, 8);
        if (!(lane & 8)) stsf(sb + SM_RED + 32 * (4 * (lane & 1) + ((lane >> 1) & 3)) + 8 * sw + 4 * (lane >> 4), d);
        bar_sync(3);
        if (s < 64) {
          const uint4 p0 = lds128(sb + SM_RED + 32 * (s & 7)), p1 = lds128(sb + SM_RED + 32 * (s & 7) + 16);
          const float y = rbf(((__uint_as_float(p0.x) + __uint_as_float(p0.y)) + (__uint_as_float(p0.z) + __uint_as_float(p0.w))) +
                              ((__uint_as_float(p1.x) + __uint_as_float(p1.y)) + (__uint_as_float(p1.z) + __uint_as_float(p1.w))));
          const uint32_t v = packbf(0.f, fmaf((s & 1) ? bhi(xn) : blo(xn), __uint_as_float(cm.z), __uint_as_float(cm.w)) + rbf(y * __uint_as_float(cm.y)));
          if (L == 0) st_rlx(GA(x2msg, (s >> 3) * 2304 + 32 * cta + 4 * (s & 7)), v | (epoch & 0xffff));
          const int tok = 128 * ((win >> 3) & 15) + 2 * (16 * (win & 3) + ((win >> 7) & 15)) + ((win >> 2) & 1);
          if (L == 1 && s < 8) *reinterpret_cast<uint16_t*>(p.out + (uint32_t)(tok * 1152 + 16 * cta + 2 * s)) = (uint16_t)(v >> 16);
        }
      }
      TR(2, 9 + 10 * L);
      if (L == 0 && m < 14) {
        RELANE;
        const int c = min(2 * m + ((s >> 3) & 1), 26);
        const uint8_t* wsrc = GC(wpack, r * 12 * WSTAGE + (s >> 4) * 3456 + c * 128 + (s & 7) * 16);
        const int k0 = 8 * (s >> 4) + (s & 7);
        uint4 wv[5];
#pragma unroll
        for (int i = 0; i < 5; i++) wv[i] = ldcg128(wsrc + i * WSTAGE);
        uint32_t xv[9];
        {
          uint32_t n = 0;
          _Pragma("unroll 1") while (true) {
            uint32_t bad = 0;
#pragma unroll
            for (int i = 0; i < 9; i++) { xv[i] = ld_rlx(GA(x2msg, r * 2304 + 4 * k0) + 256 * i); bad |= xv[i] ^ epoch; }
            if (!__any_sync(0xffffffffu, bad & 0xffff)) break;
            spin_guard(n);
          }
        }
        TR(2, 10);
        float a[8], z = 0.f;
#pragma unroll
        for (int e = 0; e < 8; e++) a[e] = 0.f;
#pragma unroll
        for (int i = 0; i < 9; i++) {
          const float xx = bhi(xv[i]);
          const uint4 w4 = wv[i % 5];
          if (i < 4) wv[i] = ldcg128(wsrc + (i + 5) * WSTAGE);
          z = fmaf(xx, (lane & 8) ? xx : 1.f, z);
          a[0] = fmaf(xx, blo(w4.x), a[0]); a[1] = fmaf(xx, bhi(w4.x), a[1]);
          a[2] = fmaf(xx, blo(w4.y), a[2]); a[3] = fmaf(xx, bhi(w4.y), a[3]);
          a[4] = fmaf(xx, blo(w4.z), a[4]); a[5] = fmaf(xx, bhi(w4.z), a[5]);
          a[6] = fmaf(xx, blo(w4.w), a[6]); a[7] = fmaf(xx, bhi(w4.w), a[7]);
        }
        const bool b4 = lane & 4, b2 = lane & 2, b1 = lane & 1;
        float b[4];
#pragma unroll
        for (int e = 0; e < 4; e++) b[e] = (b4 ? a[4 + e] : a[e]) + shx(b4 ? a[e] : a[4 + e], 4);
        z += shx(z, 4);
        const float c0 = (b2 ? b[2] : b[0]) + shx(b2 ? b[0] : b[2], 2);
        const float c1 = (b2 ? b[3] : b[1]) + shx(b2 ? b[1] : b[3], 2);
        z += shx(z, 2);
        float d = (b1 ? c1 : c0) + shx(b1 ? c0 : c1, 1);
        z += shx(z, 1);
        d += shx(d, 16);
        z += shx(z, 16);
        if (lane < 16) stsf(sb + SM_GEMV + 16 * lane + 4 * sw, d);
        if ((lane & 23) == 0) stsf(sb + SM_GEMV + 256 + 2 * lane + 4 * sw, z);
        bar_sync(3);
        if (s < 16) {
          const uint4 pd = lds128(sb + SM_GEMV + 16 * s), p1 = lds128(sb + SM_GEMV + 256), p2 = lds128(sb + SM_GEMV + 272);
          const float acc = (__uint_as_float(pd.x) + __uint_as_float(pd.y)) + (__uint_as_float(pd.z) + __uint_as_float(pd.w));
          const float m1 = ((__uint_as_float(p1.x) + __uint_as_float(p1.y)) + (__uint_as_float(p1.z) + __uint_as_float(p1.w))) * (1.f / kD);
          const float m2 = ((__uint_as_float(p2.x) + __uint_as_float(p2.y)) + (__uint_as_float(p2.z) + __uint_as_float(p2.w))) * (1.f / kD);
          const float cs = blo(lds16(sb + SM_COLSUM + 32 * c + 2 * (s & 7))) + blo(lds16(sb + SM_COLSUM + 32 * c + 2 * (s & 7) + 16));
          const float v = (acc - m1 * cs) * rcp(ln_sd(fmaxf(m2 - m1 * m1, 0.f)));
          st_rlx(GA(fixmsg, 1024 * r + 64 * m + 4 * s), __float_as_uint(rbf(v)) | (epoch & 0xffff));
        }
        TR(2, 11);
      }
      {
        if (L == 0 && (int)((win >> 3) & 15) == m) {
          RELANE;
          if (s < 72) {
            const uint8_t* fp = s < 54 ? GA(fixmsg, 1024 * r + 16 * s) : GA(x2msg, r * (2304 + 288) + 16 * (s - 54));
            uint4 v;
            uint32_t n = 0;
            _Pragma("unroll 1") while (true) {
              v = ld_msg(fp);
              if ((((v.x ^ epoch) | (v.y ^ epoch) | (v.z ^ epoch) | (v.w ^ epoch)) & 0xffff) == 0) break;
              spin_guard(n);
            }
            sts128(sb + SM_FIXQ + 16 * s, v.x & 0xffff0000u, v.y & 0xffff0000u, v.z & 0xffff0000u, v.w & 0xffff0000u);
          }
          __syncwarp();
          if (lane == 0) mbar_arrive(sb + B_FIX);
          TR(2, 12);
        }
      }
    }
    if (s == 0) st_rlx(GA(epoch, 32 * cta), epoch);
  } else {
    asm volatile("setmaxnreg.inc.sync.aligned.u32 144;");
    const int w = warp >> 2, j = warp & 3;
    const uint32_t xfull = sb + B_XFULL + 32 * w, xempty = sb + B_XEMPTY + 32 * w, xring = sb + SM_X + w * 4 * XSTAGE;
    if (threadIdx.x >= 128 && threadIdx.x < 188) { sts128(sb + SM_COLSUM + 16 * (threadIdx.x - 128), 0, 0, 0, 0); fence_async_smem(); }
    {
      const uint32_t epoch = pack();
      asm volatile("bar.arrive 15, 384;" ::: "memory");
      TRW(24);
      if (!(ABL & 8)) {
        if (lane < 16) st_msg(GA(statsP, (2 * m + w) * 8192 + r * 1024 + (16 * j + lane) * 16), 0, 0, 0, 0);
        if (lane < 2) st_msg(GA(cand, (8 * lane + r) * 2048 + 16 * (8 * m + warp)), ~epoch, 0, 0, 0);
        if (j == 3) {
#pragma unroll
          for (int u = 0; u < 10; u++) st_msg(GC(halo, (4 * cta + w) * 2560 + lane * 16) + (u / 5) * 5120 + (u % 5) * 512, 0, 0, 0, 0);
        }
        __syncwarp();
      }
      TRW(11);
    }
    const uint32_t mw = 2 * m + w, cid = 8 * m + warp;
    const uint32_t rowc = sb + SM_ROWC + 64 * warp, rowm = sb + SM_ROWM + 128 * warp;
#pragma unroll 1
    for (int L = 0; L < 2; L++) {
      int ln0 = __shfl_sync(0xffffffffu, lane + L, lane) - L;
#define RELANE2 asm volatile("" : "+r"(ln0)); const int ln = ln0, g = ln >> 2, t = ln & 3; \
      const uint32_t pa = xring + j * 256 + (ln & 7) * 1028 + ((ln >> 3) & 1) * 128 + 96; (void)pa
      uint32_t P[27][2], H[20];
      const uint8_t* hl;
      auto halo = [&]() {
#pragma unroll
        for (int u = 0; u < 5; u++) {
          const uint4 v = ld_gen(hl + u * 512);
          H[4 * u] = v.x; H[4 * u + 1] = v.y; H[4 * u + 2] = v.z; H[4 * u + 3] = v.w;
        }
      };
      {
        RELANE2;
        const uint32_t epoch = __shfl_sync(0xffffffffu, lds32(sb + SM_EP), 0);
        int selrow = -1;
        bool tgtwg = false;
        float d[108];
        uint32_t am[4];
        auto split_mean = [&](float m0, float m1) {
          const uint32_t h0 = packbf(m0, m0), h1 = packbf(m1, m1);
          const float l0 = m0 - bhi(h0), l1 = m1 - bhi(h1);
          am[0] = t ? 0u : h0; am[1] = t ? 0u : h1; am[2] = t ? 0u : packbf(l0, l0); am[3] = t ? 0u : packbf(l1, l1);
        };
        const uint32_t cdesc = mkdesc(sbd + SM_COLSUM, 0);
        am[0] = am[1] = am[2] = am[3] = 0;
        if (L == 1) split_mean(ldsf(rowm + 8 * g), ldsf(rowm + 8 * g + 64));
        asm volatile("wgmma.fence.sync.aligned;" ::: "memory");
        wgmma_n144_set(d + 36, am, cdesc + 18);
        wgmma_n72_set(d, am, cdesc);
        asm volatile("wgmma.commit_group.sync.aligned;" ::: "memory");
        const uint32_t adesc = mkdesc(sbd + SM_X + w * 4 * XSTAGE, 1024), ahi = L == 0 ? 0x40000040u : 8u, astep = L == 0 ? 2 : 128;
        const uint32_t bdesc = mkdesc(sbd + SM_W, 3456);
        const uint8_t* xsrc = GC(act, ACT + mw * 73728);
        mbar_wait2(sb + B_WFULL, L, xfull, 0);
        if (L == 1) check_stage(probe_stage(pa), xring, xsrc);
        TRW(0 + 12 * L);
#pragma unroll 1
        for (int s = 0; s < 7; s++) {
          TRQ(s + 9 * L);
          const uint32_t da = adesc + (s & 3) * (XSTAGE >> 4), db = bdesc + (s & 3) * (WSTAGE >> 4);
          const uint32_t nx = (s + 1) & 3, px = ((s + 1) >> 2) & 1;
          asm volatile("wgmma.fence.sync.aligned;" ::: "memory");
          wgmma_n72(d, da, ahi, db);
          wgmma_n144(d + 36, da, ahi, db + (1152 >> 4));
          wgmma_n72(d, da + astep, ahi, db + (6912 >> 4));
          asm volatile("wgmma.commit_group.sync.aligned;" ::: "memory");
          asm volatile("wgmma.wait_group.sync.aligned 1;" ::: "memory");
          if (s > 0 && ln == 0) {
            mbar_arrive_pair(sb + B_WEMPTY + 8 * ((s - 1) & 3));
            mbar_arrive(xempty + 8 * ((s - 1) & 3));
          }
          wgmma_n144(d + 36, da + astep, ahi, db + ((6912 + 1152) >> 4));
          wgmma_n72(d, da + 2 * astep, ahi, db + 2 * (6912 >> 4));
          uint32_t pv;
          const uint32_t dsc[6] = {da + 2 * astep, db + ((2 * 6912 + 1152) >> 4), da + 3 * astep, db + 3 * (6912 >> 4),
                                   da + 3 * astep, db + ((3 * 6912 + 1152) >> 4)};
          const uint32_t bar[4] = {sb + B_WFULL + 8 * nx, px ^ L, xfull + 8 * nx, px}, adr = pa + nx * XSTAGE;
          q_tail(d, &pv, ahi, dsc, bar, &adr);
          if (L == 1) check_stage(pv, xring + nx * XSTAGE, xsrc + (s + 1) * XSTAGE);
        }
        TRQ(7 + 9 * L);
        const uint32_t da7 = adesc + 3 * (XSTAGE >> 4), db7 = bdesc + 3 * (WSTAGE >> 4);
        asm volatile("wgmma.fence.sync.aligned;" ::: "memory");
        wgmma_n144(d + 36, da7, ahi, db7 + (1152 >> 4));
        wgmma_n144(d + 36, da7 + astep, ahi, db7 + ((6912 + 1152) >> 4));
        asm volatile("wgmma.commit_group.sync.aligned;" ::: "memory");
        asm volatile("wgmma.wait_group.sync.aligned 1;" ::: "memory");
        if (ln == 0) { mbar_arrive_pair(sb + B_WEMPTY + 16); mbar_arrive(xempty + 16); }
        {
          uint32_t v[2];
          const uint32_t dsc[4] = {da7 + 2 * astep, db7 + ((2 * 6912 + 1152) >> 4), da7 + 3 * astep, db7 + ((3 * 6912 + 1152) >> 4)};
          const uint32_t bar[6] = {sb + B_WFULL, (uint32_t)L, xfull, 0, sb + (L ? B_IDX : B_COLSUM), 0}, adr[2] = {pa, sb + SM_SEL + (ln >> 5)};
          kv_tail(d, v, ahi, dsc, bar, adr);
          if (L == 1) {
            if ((v[1] & 127) == cid) selrow = v[1] >> 7;
            tgtwg = ((v[1] & 127) >> 2) == (cid >> 2);
            check_stage(v[0], xring, xsrc + 8 * XSTAGE);
          }
        }
        TRQ(8 + 9 * L);
        const float m0 = ldsf(rowm + 8 * g), m1 = ldsf(rowm + 8 * g + 64);
        {
          uint32_t dsc[8];
#pragma unroll
          for (int kk = 0; kk < 4; kk++) { dsc[2 * kk] = adesc + kk * astep; dsc[2 * kk + 1] = bdesc + ((kk * 6912 + 1152) >> 4); }
          const uint32_t bar[2] = {xempty + 16, 1};
          asm volatile("wgmma.fence.sync.aligned;" ::: "memory");
          kv_last(d, nullptr, ahi, dsc, bar, nullptr);
        }
        if (L == 0) {
          split_mean(m0, m1);
          asm volatile("wgmma.fence.sync.aligned;" ::: "memory");
          wgmma_n144_add(d + 36, am, cdesc + 18);
          wgmma_n72_add(d, am, cdesc);
          asm volatile("wgmma.commit_group.sync.aligned;" ::: "memory");
        }
        auto qstep = [&](int k) {
          wgmma_n72(d, (k < 4 ? da7 : adesc) + (k & 3) * astep, ahi, (k < 4 ? db7 : bdesc) + (k & 3) * (6912 >> 4));
        };
#pragma unroll
        for (int k = 0; k < QPRE; k++) qstep(k);
        asm volatile("wgmma.commit_group.sync.aligned;" ::: "memory");
        if (tgtwg) {
          asm volatile("wgmma.fence.sync.aligned;" ::: "memory");
#pragma unroll
          for (int k = QPRE; k < 8; k++) qstep(k);
          asm volatile("wgmma.commit_group.sync.aligned;" ::: "memory");
        }
        asm volatile("wgmma.wait_group.sync.aligned 1;" ::: "memory");
#pragma unroll
        for (int i = 36; i < 108; i++) asm volatile("" : "+f"(d[i])::"memory");
        if (selrow >= 0) {
          mbar_wait(sb + B_FIX, 0);
          stsf(rowc + 4 * selrow, 1.f);
#pragma unroll
          for (int q = 18; q < 54; q++) lds64f_if(selrow == g + 8 * (q & 1), d[2 * q], d[2 * q + 1], sb + SM_FIXQ + 32 * (q >> 1) + 8 * t);
          __syncwarp();
        }
#pragma unroll
        for (int q = 26; q >= 9; q--) { P[q][1] = packbf(d[4 * q + 2], d[4 * q + 3]); P[q][0] = packbf(d[4 * q], d[4 * q + 1]); }
#pragma unroll
        for (int q = 26; q >= 18; q--) P[q][1] = movm(P[q][1]);
        const uint2 ck1 = lds64(rowc + 32 + 8 * t);
        uint8_t* ha = (j < 3 ? smem_raw + (SM_X + (4 * w + 2) * XSTAGE + j * 2560) : GC(halo, (4 * cta + 2 * L + w) * 2560)) + ln * 16;
        P[9][1] = nz(P[9][1]); P[13][1] = nz(P[13][1]); P[17][1] = nz(P[17][1]);
        st_gen(ha, P[9][1], P[10][1], P[11][1], P[12][1]);
        st_gen(ha + 512, P[13][1], P[14][1], P[15][1], P[16][1]);
        st_gen(ha + 2048, nz(ck1.y), P[24][1], P[25][1], P[26][1]);
        st_gen(ha + 1536, nz(ck1.x), P[21][1], P[22][1], P[23][1]);
        st_gen(ha + 1024, P[17][1], P[18][1], P[19][1], P[20][1]);
#pragma unroll
        for (int q = 9; q < 27; q++) asm volatile("" : "+r"(P[q][0]));
        if (j < 3) asm volatile("bar.arrive %0, 64;" ::"r"(5 + warp) : "memory");
        mbar_wait(sb + B_EP, 0);
#pragma unroll
        for (int q = 26; q >= 18; q--) P[q][0] = movm(P[q][0]);
        if (!tgtwg)
        {
          asm volatile("wgmma.fence.sync.aligned;" ::: "memory");
#pragma unroll
          for (int k = QPRE; k < 8; k++) qstep(k);
          asm volatile("wgmma.commit_group.sync.aligned;" ::: "memory");
        }
        hl = (j > 0 || m == 0 ? smem_raw + (SM_X + (4 * w + 2) * XSTAGE + max(j - 1, 0) * 2560)
                              : GC(halo, (4 * (cta - 8) + 2 * L + w) * 2560)) + ln * 16;
        if (j > 0) asm volatile("bar.sync %0, 64;" ::"r"(4 + warp) : "memory");
        asm volatile("wgmma.wait_group.sync.aligned 0;" ::: "memory");
#pragma unroll
        for (int i = 0; i < 36; i++) asm volatile("" : "+f"(d[i])::"memory");
        TRW(1 + 12 * L);
        if (selrow >= 0) {
#pragma unroll
          for (int q = 0; q < 18; q++) lds64f_if(selrow == g + 8 * (q & 1), d[2 * q], d[2 * q + 1], sb + SM_FIXQ + 32 * (q >> 1) + 8 * t);
        }
#pragma unroll
        for (int q = 0; q < 9; q++) { P[q][0] = packbf(d[4 * q], d[4 * q + 1]); P[q][1] = packbf(d[4 * q + 2], d[4 * q + 3]); }
      }
      TRW(2 + 12 * L);
      const uint32_t epoch = lds32(sb + SM_EP);
      uint8_t* fptr = GA(flagX, 128 * mw + 16 * r + 4 * j + ln0);
      {
        RELANE2;
        halo();
        if (ln == 0) { mbar_arrive(xempty + 24); mbar_arrive(xempty); }
        const bool le0 = 2 * t <= g, le1 = 2 * t + 1 <= g;
        uint32_t A0[4][2], A2[4][2];
        float s0[4][4], s1[4][4];
#pragma unroll
        for (int h = 0; h < 4; h++) {
          const int T = 2 * h;
          A0[h][0] = t >= h ? P[T][0] : 0u; A0[h][1] = t >= h ? P[T][1] : 0u;
          A2[h][0] = t <= h ? P[T + 2][0] : 0u; A2[h][1] = t <= h ? P[T + 2][1] : 0u;
          mma8z(s0[h], A2[h][0], A2[h][1], P[9 + T + 2][0]);
          mma8z(s1[h], A2[h][0], A2[h][1], P[9 + T + 2][1]);
        }
#pragma unroll
        for (int h = 0; h < 4; h++) {
          const int T = 2 * h;
          mma16(s0[h], A0[h][0], A0[h][1], P[T + 1][0], P[T + 1][1], P[9 + T][0], P[9 + T + 1][0]);
          mma16(s1[h], A0[h][0], A0[h][1], P[T + 1][0], P[T + 1][1], P[9 + T][1], P[9 + T + 1][1]);
        }
        const uint2 ck0 = lds64(rowc + 8 * t), ck1 = lds64(rowc + 32 + 8 * t);
        const float sc = 0.23570226039551584f * 1.4426950408889634f;
        const float cq0 = ldsf(rowc + 4 * g) * sc, cq1 = ldsf(rowc + 32 + 4 * g) * sc;
        uint8_t* ob = GC(act, 2 * L * ACT + mw * 73728 + r * 9216 + j * 256 + ln * 4);
        float l[2][4][2], ks[2][2], mx[2][4];
        ks[1][0] = __uint_as_float(le0 ? ck1.x : ck0.x); ks[1][1] = __uint_as_float(le1 ? ck1.y : ck0.y);
#pragma unroll
        for (int h = 0; h < 4; h++) {
          l[1][h][0] = (le0 ? s1[h][2] : s0[h][2]) * (cq1 * ks[1][0]); l[1][h][1] = (le1 ? s1[h][3] : s0[h][3]) * (cq1 * ks[1][1]);
          asm volatile("" : "+f"(l[1][h][0]), "+f"(l[1][h][1]));
        }
        asm volatile("" : "+l"(fptr), "+l"(ob));
        {
          uint32_t n = 0;
          _Pragma("unroll 1") while (__any_sync(0xffffffffu, min(min(min(H[0], H[4]), min(H[8], H[12])), H[16]) == 0)) {
            halo();
            spin_guard(n);
          }
        }
        if (ln == 0) mbar_arrive_pair(sb + B_WEMPTY + 24);
        TRW(3 + 12 * L);
        {
          float sm[4][4];
#pragma unroll
          for (int h = 0; h < 4; h++) mma8z(sm[h], A2[h][0], A2[h][1], H[2 * h + 2]);
#pragma unroll
          for (int h = 0; h < 4; h++) mma16(sm[h], A0[h][0], A0[h][1], P[2 * h + 1][0], P[2 * h + 1][1], H[2 * h], H[2 * h + 1]);
          ks[0][0] = __uint_as_float(le0 ? ck0.x : H[12]); ks[0][1] = __uint_as_float(le1 ? ck0.y : H[16]);
          const bool nohalo = (m == 0 && j == 0);
          const float b0 = (nohalo && !le0) ? -INFINITY : 0.f, b1 = (nohalo && !le1) ? -INFINITY : 0.f;
#pragma unroll
          for (int h = 0; h < 4; h++) {
            l[0][h][0] = fmaf(le0 ? s0[h][0] : sm[h][0], cq0 * ks[0][0], b0);
            l[0][h][1] = fmaf(le1 ? s0[h][1] : sm[h][1], cq0 * ks[0][1], b1);
          }
        }
#pragma unroll
        for (int i = 7; i >= 0; i--) mx[i >> 2][i & 3] = fmaxf(l[i >> 2][i & 3][0], l[i >> 2][i & 3][1]);
#pragma unroll
        for (int x = 1; x <= 2; x <<= 1) {
#pragma unroll
          for (int i = 7; i >= 0; i--) mx[i >> 2][i & 3] = fmaxf(mx[i >> 2][i & 3], shx(mx[i >> 2][i & 3], x));
        }
        const uint32_t mle = (le0 ? 0xffffu : 0u) | (le1 ? 0xffff0000u : 0u);
        uint32_t pp[2][4], pc[2][4];
#pragma unroll
        for (int i = 3; i >= 0; i--) {
          const int e = i >> 1, h = 2 * (i & 1);
          const float p0 = ex2(l[e][h][0] - mx[e][h]), p1 = ex2(l[e][h][1] - mx[e][h]);
          const float p2 = ex2(l[e][h + 1][0] - mx[e][h + 1]), p3 = ex2(l[e][h + 1][1] - mx[e][h + 1]);
          float sum[4];
          mma8z(sum, packbf(p0, p1), packbf(p2, p3), 0x3f803f80u);
          const float inv = rcp(sum[0] * sum[2]);
          const float ia = inv * sum[2], ib = inv * sum[0];
          const uint32_t u0 = packbf(p0 * ks[e][0] * ia, p1 * ks[e][1] * ia), u1 = packbf(p2 * ks[e][0] * ib, p3 * ks[e][1] * ib);
          pp[e][h] = u0 & ~mle; pc[e][h] = u0 & mle; pp[e][h + 1] = u1 & ~mle; pc[e][h + 1] = u1 & mle;
        }
#pragma unroll
        for (int e = 1; e >= 0; e--) {
#pragma unroll
          for (int q = 8; q >= 0; q--) {
            const int h = q < 4 ? 0 : q == 4 ? 1 : 2;
            float a[4];
            mma16z(a, pp[e][h], pp[e][h + 1], pc[e][h], pc[e][h + 1], e ? P[18 + q][0] : H[9 + q + q / 3], P[18 + q][e]);
            const bool second = q == 2 * h + 2 ? t > h : q > 2 * h + 2;
            st_rlx(ob + q * 1024 + e * 128, nz(packbf(second ? a[2] : a[0], second ? a[3] : a[1])));
          }
        }
        if (ln == 0) st_rlx(fptr, epoch * 4 + 1 + 2 * L);
        TRW(4 + 12 * L);
      }
      RELANE2;
      float d[36];
      uint32_t WB[9];
      {
        uint32_t R[10][2];
        const uint32_t qs = L == 0 ? 16 : 1024, ra = xring + (16 * j + (ln & 15)) * (L == 0 ? 144 : 16) + (ln >> 4) * qs;
        mbar_wait(sb + B_RES + 8 * w, L);
#pragma unroll
        for (int q = 0; q < 10; q += 2) ldsm4(&R[q][0], ra + q * qs);
        fence_async_smem();
        __syncwarp();
        if (ln == 0) mbar_arrive(sb + B_RC + 8 * w);
#pragma unroll
        for (int q = 0; q < 9; q++) WB[q] = ldg32(p.wr + (uint32_t)(r * 144 + 4 * t) + 16 * q);
#pragma unroll
        for (int h = 0; h < 2; h++) {
          const uint2 mf = lds64(rowm + 8 * g + 64 * h);
          const float f = __uint_as_float(mf.y), k = -__uint_as_float(mf.x) * f;
#pragma unroll
          for (int q = 0; q < 9; q++) { d[4 * q + 2 * h] = fmaf(blo(R[q][h]), f, k); d[4 * q + 2 * h + 1] = fmaf(bhi(R[q][h]), f, k); }
        }
        const uint32_t sel = lds32(sb + SM_SEL);
        if (L == 1 && (sel & 127) == cid) {
          const int selrow = sel >> 7;
#pragma unroll
          for (int q = 0; q < 18; q++) lds64f_if(selrow == g + 8 * (q & 1), d[2 * q], d[2 * q + 1], sb + SM_X2R + 32 * (q >> 1) + 8 * t);
        }
#pragma unroll
        for (int q = 0; q < 9; q++) WB[q] = (g & 1) ? WB[q] : 0x3f803f80u;
        __syncwarp();
      }
      uint8_t* xb = GC(act, ACT + mw * 73728 + r * 9216 + j * 256 + ln * 4);
      uint8_t* sst = GA(statsP, mw * 8192 + r * 1024 + (16 * j + g + 8 * t) * 16);
      const uint8_t* sld = GA(statsP, mw * 8192 + (ln >> 4) * 4096 + (16 * j + (ln & 15)) * 16);
      uint8_t* cptr = GA(cand, (8 * L + r) * 2048 + 16 * cid);
      uint8_t* crow = GC(candrow, (128 * L + cid) * 1152 + 144 * r + 4 * t);
      uint32_t tag = epoch * 2 + L, ktag = ((ln & 15) << 7) | (epoch & 0x7f);
      float wsum = ldsf(sb + SM_WSUM);
      float pivot = __uint_as_float(ld_rlx(GA(stats0, 16 * (16 * cid + (ln & 15)) + 4))) + (L ? ldsf(rowm + 8 * (ln & 15)) : 0.f);
      asm volatile("" : "+l"(xb), "+l"(sst), "+l"(sld), "+l"(cptr), "+l"(crow), "+r"(tag), "+r"(ktag), "+f"(wsum), "+f"(pivot));
      TRW(5 + 12 * L);
      {
        constexpr uint32_t bdesc = mkdesc(sbd + SM_W + WSTAGE, 1152);
        uint32_t adesc[3];
#pragma unroll
        for (int i = 0; i < 3; i++) adesc[i] = __shfl_sync(0xffffffffu, mkdesc(sbd + SM_X + w * 4 * XSTAGE, 1024) + (ln >> 2), i);
#pragma unroll
        for (int i = 0; i < 36; i++) asm volatile("" : "+f"(d[i])::"memory");
        const bool lead = warp == 0 && ln == 0;
        const uint8_t* osrc = GC(act, 2 * L * ACT + mw * 73728);
        mbar_wait2(sb + B_WFULL + 8, L, xfull, 1);
        check_stage(probe_stage(pa), xring, osrc);
        TRW(6 + 12 * L);
#pragma unroll
        for (int s = 0; s < 9; s++) {
          TRQ(18 + s);
          const uint32_t da = adesc[s >> 2] + (s & 3) * (XSTAGE >> 4), db = bdesc + s * (9216 >> 4);
          const uint32_t nx = (s + 1) & 3;
          asm volatile("wgmma.fence.sync.aligned;" ::: "memory");
          wgmma_n72(d, da, 8u, db);
          wgmma_n72(d, da + 128, 8u, db + (2304 >> 4));
          asm volatile("wgmma.commit_group.sync.aligned;" ::: "memory");
          if (s > 0) {
            asm volatile("wgmma.wait_group.sync.aligned 1;" ::: "memory");
            if (ln == 0) {
              mbar_arrive(xempty + 8 * ((s - 1) & 3));
              if ((s == 1 || s == 3 || s == 6) && L == 0) mbar_arrive_pair(sb + B_WEMPTY + (s / 3) * 8);
            }
          }
          const uint32_t px = (((s + 1) >> 2) + (nx == 0)) & 1;
          if ((s == 0 || s == 5) && lead) mbar_arrive(sb + (s ? B_EPI : B_OS));
          if (s < 8) {
            uint32_t pv;
            const uint32_t dsc[4] = {da + 256, db + (4608 >> 4), da + 384, db + (6912 >> 4)};
            const uint32_t bar[4] = {sb + B_WFULL + 8 + 8 * ((s + 1) / 3), (uint32_t)L, xfull + 8 * nx, px}, adr = pa + nx * XSTAGE;
            o_tail2(d, &pv, 8u, dsc, bar, &adr);
            check_stage(pv, xring + nx * XSTAGE, osrc + (s + 1) * XSTAGE);
          } else {
            wgmma_n72(d, da + 256, 8u, db + (4608 >> 4));
            wgmma_n72(d, da + 384, 8u, db + (6912 >> 4));
            asm volatile("wgmma.commit_group.sync.aligned;" ::: "memory");
          }
        }
        asm volatile("wgmma.wait_group.sync.aligned 0;" ::: "memory");
#pragma unroll
        for (int i = 0; i < 36; i++) asm volatile("" : "+f"(d[i])::"memory");
        if (ln == 0) { if (L == 0) mbar_arrive_pair(sb + B_WEMPTY + 24); mbar_arrive(xempty); }
      }
      TRW(7 + 12 * L);
      uint32_t R[9][2];
#pragma unroll
      for (int q = 0; q < 9; q++) { R[q][0] = packbf(d[4 * q], d[4 * q + 1]); R[q][1] = packbf(d[4 * q + 2], d[4 * q + 3]); }
      {
        float sa[4], sc[4];
        mma16z(sa, R[0][0], R[0][1], R[1][0], R[1][1], WB[0], WB[1]);
        mma16z(sc, R[2][0], R[2][1], R[3][0], R[3][1], WB[2], WB[3]);
        mma16(sa, R[4][0], R[4][1], R[5][0], R[5][1], WB[4], WB[5]);
        mma16(sc, R[6][0], R[6][1], R[7][0], R[7][1], WB[6], WB[7]);
        mma8(sa, R[8][0], R[8][1], WB[8]);
        float qq[4] = {0.f, 0.f, 0.f, 0.f};
#pragma unroll
        for (int q = 0; q < 36; q++) qq[q & 3] = fmaf(d[q], d[q], qq[q & 3]);
        const float qa = qq[0] + qq[1], qc = qq[2] + qq[3];
        const bool odd = t & 1;
        float q2 = (odd ? qc : qa) + shx(odd ? qa : qc, 1);
        q2 += shx(q2, 2);
        if (t < 2)
          st_msg(sst, __float_as_uint(odd ? sa[2] + sc[2] : sa[0] + sc[0]), __float_as_uint(q2),
                 __float_as_uint(odd ? sa[3] + sc[3] : sa[1] + sc[1]), tag);
      }
      if (L == 0) {
#pragma unroll
        for (int q = 0; q < 9; q++) { st_rlx(xb + q * 1024, nz(R[q][0])); st_rlx(xb + q * 1024 + 128, nz(R[q][1])); }
        if (ln == 0) st_rlx(fptr, epoch * 4 + 2);
      }
      TRW(8 + 12 * L);
      {
        uint4 u[4];
        uint32_t n = 0;
        _Pragma("unroll 1") while (true) {
#pragma unroll
          for (int i = 0; i < 4; i++) u[i] = ld_msg(sld + 1024 * i);
          if (!__any_sync(0xffffffffu, (u[0].w ^ tag) | (u[1].w ^ tag) | (u[2].w ^ tag) | (u[3].w ^ tag))) break;
          spin_guard(n);
        }
        TRW(9 + 12 * L);
        float s1 = (__uint_as_float(u[0].x) + __uint_as_float(u[1].x)) + (__uint_as_float(u[2].x) + __uint_as_float(u[3].x));
        float s2 = (__uint_as_float(u[0].y) + __uint_as_float(u[1].y)) + (__uint_as_float(u[2].y) + __uint_as_float(u[3].y));
        float s3 = (__uint_as_float(u[0].z) + __uint_as_float(u[1].z)) + (__uint_as_float(u[2].z) + __uint_as_float(u[3].z));
        s1 += shx(s1, 16); s2 += shx(s2, 16); s3 += shx(s3, 16);
        const float mu = s1 * (1.f / kD);
        const float var = fmaxf(fmaf(s2, 1.f / kD, -mu * mu), 0.f);
        const float sd = ln_sd(var), rho = rcp(sd);
        const float rr = (s3 - mu * wsum) * rho;
        const int key = __reduce_max_sync(0xffffffffu, (int)((fkey(rr) & ~0x7ff) | ktag));
        const int best = (key >> 7) & 15;
        if (ln == best) st_msg(cptr, key, __float_as_uint(rbf(sigmoidf(rbf(rr)))), __float_as_uint(1.f + sd), __float_as_uint(L ? pivot + mu : 0.f));
        const float rb = __shfl_sync(0xffffffffu, rho, best), nb = __shfl_sync(0xffffffffu, -mu * rho, best);
        if ((best & 7) == g) {
          const bool hi = best >= 8;
#pragma unroll
          for (int q = 0; q < 9; q++)
            st_rlx(crow + (((q ^ r) & 1) * (4 - 8 * (t & 1))) + 16 * q, nz(packbf(fmaf(hi ? d[4 * q + 2] : d[4 * q], rb, nb), fmaf(hi ? d[4 * q + 3] : d[4 * q + 1], rb, nb))));
        }
        const float f = 1.f + rho, k = pivot - mu * rho;
        sts32(rowc + 4 * (ln & 15), __float_as_uint(f * rcp(ln_sd(var * f * f))));
        sts64(rowm + 8 * (ln & 15), __float_as_uint(L == 0 ? mu : k), __float_as_uint(f));
        __syncwarp();
      }
      TRW(10 + 12 * L);
      if (L == 1) {
#pragma unroll
        for (int h = 0; h < 2; h++) {
          const uint2 kf = lds64(rowm + 8 * g + 64 * h);
          const float k = __uint_as_float(kf.x), f = __uint_as_float(kf.y);
#pragma unroll
          for (int q = 0; q < 9; q++) R[q][h] = packbf(fmaf(d[4 * q + 2 * h], f, k), fmaf(d[4 * q + 2 * h + 1], f, k));
        }
        mbar_wait(xempty + 16, 1);
        const uint32_t st = xring + XSTAGE + (16 * j + (ln & 15)) * 144;
#pragma unroll
        for (int q = 0; q < 8; q += 2) stsm4(st + (ln >> 4) * 16 + q * 16, R[q][0], R[q][1], R[q + 1][0], R[q + 1][1]);
        stsm2(st + 128, R[8][0], R[8][1]);
        fence_async_smem();
        __syncwarp();
        mbar_wait(sb + B_IDX + 8, 0);
        const uint32_t sel = lds32(sb + SM_SEL + 4);
        if ((sel & 127) != cid) {
          if (elect())
            asm volatile("cp.async.bulk.tensor.3d.global.shared::cta.bulk_group [%0, {%2,%3,%4}], [%1];" ::"l"(&tm.out),
                         "r"(xring + XSTAGE + 16 * j * 144), "r"(72 * r), "r"(w), "r"(64 * m + 16 * j) : "memory");
        } else if (ln < 16 && ln != (sel >> 7)) {
          bulk_s2g(p.out + (uint32_t)((128 * m + 2 * (16 * j + ln) + w) * 1152 + r * 144), st, 144);
        }
        asm volatile("cp.async.bulk.commit_group;" ::: "memory");
        asm volatile("cp.async.bulk.wait_group.read 0;" ::: "memory");
        TRW(11 + 12 * L);
        TRDUMP(w);
      }
    }
  }
}

typedef CUresult (*EncodeFn)(CUtensorMap*, CUtensorMapDataType, cuuint32_t, void*, const cuuint64_t*, const cuuint64_t*,
                             const cuuint32_t*, const cuuint32_t*, CUtensorMapInterleave, CUtensorMapSwizzle,
                             CUtensorMapL2promotion, CUtensorMapFloatOOBfill);

}

extern "C" void kernel_launch(void* const* d_in, const int* in_sizes, int n_in, void* d_out, int out_size) {
  static EncodeFn enc = nullptr;
  static Scratch* scratch = nullptr;
  if (!enc) {
    cudaDriverEntryPointQueryResult q;
    cudaGetDriverEntryPoint("cuTensorMapEncodeTiled", (void**)&enc, cudaEnableDefault, &q);
    cudaGetSymbolAddress((void**)&scratch, g_s);
    cudaFuncSetAttribute(fused_kernel, cudaFuncAttributeMaxDynamicSharedMemorySize, 232448);
  }
  Maps tm;
  auto mk = [&](CUtensorMap* t, void* ptr, int rank, const cuuint64_t* dims, const cuuint64_t* strides, const cuuint32_t* box,
                CUtensorMapSwizzle sw, CUtensorMapL2promotion pr) {
    const cuuint32_t es[4] = {1, 1, 1, 1};
    enc(t, CU_TENSOR_MAP_DATA_TYPE_BFLOAT16, rank, ptr, dims, strides, box, es, CU_TENSOR_MAP_INTERLEAVE_NONE, sw, pr,
        CU_TENSOR_MAP_FLOAT_OOB_FILL_NONE);
  };
  { const cuuint64_t d[3] = {576, 2, 1024}, st[2] = {1152, 2304}; const cuuint32_t bx[3] = {64, 1, 64};
    mk(&tm.x, d_in[0], 3, d, st, bx, CU_TENSOR_MAP_SWIZZLE_128B, CU_TENSOR_MAP_L2_PROMOTION_NONE);
    const cuuint32_t br[3] = {72, 1, 64};
    mk(&tm.xr, d_in[0], 3, d, st, br, CU_TENSOR_MAP_SWIZZLE_NONE, CU_TENSOR_MAP_L2_PROMOTION_NONE);
    const cuuint32_t bo[3] = {72, 1, 16};
    mk(&tm.out, d_out, 3, d, st, bo, CU_TENSOR_MAP_SWIZZLE_NONE, CU_TENSOR_MAP_L2_PROMOTION_NONE); }
  { const cuuint64_t d[3] = {576, 576, 3}, st[2] = {3456, 1152}; const cuuint32_t bx[3] = {72, 8, 2};
    mk(&tm.wq, d_in[1], 3, d, st, bx, CU_TENSOR_MAP_SWIZZLE_NONE, CU_TENSOR_MAP_L2_PROMOTION_NONE); }
  { const cuuint64_t d[2] = {576, 576}, st[1] = {1152}; const cuuint32_t bx[2] = {72, 16};
    mk(&tm.wo, d_in[2], 2, d, st, bx, CU_TENSOR_MAP_SWIZZLE_NONE, CU_TENSOR_MAP_L2_PROMOTION_NONE); }
  { const cuuint64_t d[2] = {4608, 576}, st[1] = {9216}; const cuuint32_t bx[2] = {48, 64};
    mk(&tm.wg, d_in[5], 2, d, st, bx, CU_TENSOR_MAP_SWIZZLE_128B, CU_TENSOR_MAP_L2_PROMOTION_L2_128B);
    mk(&tm.wu, d_in[6], 2, d, st, bx, CU_TENSOR_MAP_SWIZZLE_128B, CU_TENSOR_MAP_L2_PROMOTION_L2_128B); }
  Params p;
  p.x = (const uint8_t*)d_in[0]; p.wqkv = (const uint8_t*)d_in[1]; p.wo = (const uint8_t*)d_in[2];
  p.wr = (const uint8_t*)d_in[4]; p.wg = (const uint8_t*)d_in[5]; p.wu = (const uint8_t*)d_in[6]; p.wd = (const uint8_t*)d_in[7];
  p.out = (uint8_t*)d_out;
  p.g = scratch;
  fused_kernel<<<128, 512, 232448>>>(p, tm);
}
```

```cpp
#include <cuda_runtime.h>
#include <cuda_bf16.h>
#include <cuda.h>
#include <stdint.h>
#include <stddef.h>

#define DEVI __device__ __forceinline__

namespace {

constexpr int kD = 576, kF = 4608;
constexpr uint32_t WSTAGE = 27648, XSTAGE = 8192;
constexpr float kEps = 1e-5f;

constexpr uint32_t WDP = 1168;
constexpr uint32_t SM_W = 0;
constexpr uint32_t SM_X = 110592;
constexpr uint32_t SM_WD = 176128;
constexpr uint32_t SM_LEFT = SM_WD + 36 * WDP;
constexpr uint32_t SM_COLSUM = SM_LEFT + 9216;
constexpr uint32_t SM_ROWC = SM_COLSUM + 960;
constexpr uint32_t SM_ROWM = SM_ROWC + 512;
constexpr uint32_t SM_PART = SM_ROWM + 1024;
constexpr uint32_t SM_FIXQ = SM_PART;
constexpr uint32_t SM_X2R = SM_PART + 864;
constexpr uint32_t SM_H = SM_PART + 1152;
constexpr uint32_t SM_GEMV = SM_H;
constexpr uint32_t SM_RED = SM_H + 320;
constexpr uint32_t SM_SEL = SM_RED + 256;
constexpr uint32_t SM_EP = SM_SEL + 8, SM_WSUM = SM_SEL + 12;
constexpr uint32_t SM_BAR = SM_SEL + 16;
constexpr uint32_t B_WFULL = SM_BAR, B_WEMPTY = B_WFULL + 32, B_XFULL = B_WEMPTY + 32, B_XEMPTY = B_XFULL + 64;
constexpr uint32_t B_RC = B_XEMPTY + 64;
constexpr uint32_t B_COLSUM = B_RC + 16, B_PKF = B_COLSUM + 8, B_FIX = B_PKF + 8, B_DONE = B_FIX + 8;
constexpr uint32_t B_FF = B_DONE + 8;
constexpr uint32_t B_IDX = B_FF + 24;
constexpr uint32_t B_WD = B_IDX + 16, B_WANT = B_WD + 8, B_EPI = B_WANT + 8, B_EP = B_EPI + 8, B_OS = B_EP + 8, B_FD = B_OS + 8;
constexpr uint32_t B_WL = B_FD + 8;
constexpr uint32_t B_RES = B_WL + 32;
constexpr uint32_t SM_TOTAL = B_RES + 16;
constexpr int NBAR = (SM_TOTAL - SM_BAR) / 8, NBAR4 = (B_FF - SM_BAR) / 8;
static_assert(((B_EP - SM_BAR) / 8 * 4) / NBAR == 3, "warp 15 initialises B_EP");
constexpr uint32_t FSLOT = 16384;
static_assert(SM_TOTAL + 256 <= 232448, "smem");

struct __align__(1024) Checked {
  uint32_t candrow[2][128][288];
  uint4 halo[128][2][2][5][32];
  uint8_t wpack[8][12 * WSTAGE];
  uint8_t act[3][16][2][73728];
};
struct __align__(1024) Scratch {
  uint4 cand[2][8][128];
  uint4 ypart[72][128][2];
  uint32_t x2msg[8][576];
  uint32_t fixmsg[8][256];
  uint32_t flagP[8][12][32];
  uint32_t flagX[16][2][32];
  uint32_t epoch[128][8];
  uint4 stats0[16][2][64];
  uint4 statsP[16][2][8][64];
  float colpart[8][8][216];
  Checked chk[2];
};
__device__ Scratch g_s;
#define GA(member, off) (gb + offsetof(Scratch, member) + (uint32_t)(off))
#define GC(member, off) (gb + offsetof(Scratch, chk) + offsetof(Checked, member) + (uint32_t)((off) + (epoch & 1) * (uint32_t)sizeof(Checked)))
constexpr uint32_t ACT = 16 * 2 * 73728;

#define TR(role, i)
#define TRL(role, i)
#define TRDUMP(role)
#define TRW(i)
#define TRZ(i)
#define TRQ(i)

__device__ __forceinline__ void wgmma_n144(float* d, uint32_t alo, uint32_t ahi, uint32_t blo) {
  asm volatile("{\n.reg .b64 da, db;\nmov.b64 da, {%72, %73};\nmov.b64 db, {%74, 8};\n"
    "wgmma.mma_async.sync.aligned.m64n144k16.f32.bf16.bf16 "
    "{%0, %1, %2, %3, %4, %5, %6, %7, %8, %9, %10, %11, %12, %13, %14, %15, %16, %17, %18, %19, %20, %21, %22, %23, %24, %25, %26, %27, %28, %29, %30, %31, %32, %33, %34, %35, %36, %37, %38, %39, %40, %41, %42, %43, %44, %45, %46, %47, %48, %49, %50, %51, %52, %53, %54, %55, %56, %57, %58, %59, %60, %61, %62, %63, %64, %65, %66, %67, %68, %69, %70, %71}, da, db, 1, 1, 1, 0, 1;\n}\n"
    : "+f"(d[0]), "+f"(d[1]), "+f"(d[2]), "+f"(d[3]), "+f"(d[4]), "+f"(d[5]), "+f"(d[6]), "+f"(d[7]), "+f"(d[8]),
      "+f"(d[9]), "+f"(d[10]), "+f"(d[11]), "+f"(d[12]), "+f"(d[13]), "+f"(d[14]), "+f"(d[15]), "+f"(d[16]), "+f"(d[17]),
      "+f"(d[18]), "+f"(d[19]), "+f"(d[20]), "+f"(d[21]), "+f"(d[22]), "+f"(d[23]), "+f"(d[24]), "+f"(d[25]), "+f"(d[26]),
      "+f"(d[27]), "+f"(d[28]), "+f"(d[29]), "+f"(d[30]), "+f"(d[31]), "+f"(d[32]), "+f"(d[33]), "+f"(d[34]), "+f"(d[35]),
      "+f"(d[36]), "+f"(d[37]), "+f"(d[38]), "+f"(d[39]), "+f"(d[40]), "+f"(d[41]), "+f"(d[42]), "+f"(d[43]), "+f"(d[44]),
      "+f"(d[45]), "+f"(d[46]), "+f"(d[47]), "+f"(d[48]), "+f"(d[49]), "+f"(d[50]), "+f"(d[51]), "+f"(d[52]), "+f"(d[53]),
      "+f"(d[54]), "+f"(d[55]), "+f"(d[56]), "+f"(d[57]), "+f"(d[58]), "+f"(d[59]), "+f"(d[60]), "+f"(d[61]), "+f"(d[62]),
      "+f"(d[63]), "+f"(d[64]), "+f"(d[65]), "+f"(d[66]), "+f"(d[67]), "+f"(d[68]), "+f"(d[69]), "+f"(d[70]), "+f"(d[71])
    : "r"(alo), "r"(ahi), "r"(blo));
}
__device__ __forceinline__ void wgmma_n144_set(float* d, const uint32_t* a, uint32_t blo) {
  asm volatile("{\n.reg .b64 db;\nmov.b64 db, {%76, 2};\n"
    "wgmma.mma_async.sync.aligned.m64n144k16.f32.bf16.bf16 "
    "{%0, %1, %2, %3, %4, %5, %6, %7, %8, %9, %10, %11, %12, %13, %14, %15, %16, %17, %18, %19, %20, %21, %22, %23, %24, %25, %26, %27, %28, %29, %30, %31, %32, %33, %34, %35, %36, %37, %38, %39, %40, %41, %42, %43, %44, %45, %46, %47, %48, %49, %50, %51, %52, %53, %54, %55, %56, %57, %58, %59, %60, %61, %62, %63, %64, %65, %66, %67, %68, %69, %70, %71}, {%72, %73, %74, %75}, db, 0, -1, 1, 1;\n}\n"
    : "=f"(d[0]), "=f"(d[1]), "=f"(d[2]), "=f"(d[3]), "=f"(d[4]), "=f"(d[5]), "=f"(d[6]), "=f"(d[7]), "=f"(d[8]),
      "=f"(d[9]), "=f"(d[10]), "=f"(d[11]), "=f"(d[12]), "=f"(d[13]), "=f"(d[14]), "=f"(d[15]), "=f"(d[16]), "=f"(d[17]),
      "=f"(d[18]), "=f"(d[19]), "=f"(d[20]), "=f"(d[21]), "=f"(d[22]), "=f"(d[23]), "=f"(d[24]), "=f"(d[25]), "=f"(d[26]),
      "=f"(d[27]), "=f"(d[28]), "=f"(d[29]), "=f"(d[30]), "=f"(d[31]), "=f"(d[32]), "=f"(d[33]), "=f"(d[34]), "=f"(d[35]),
      "=f"(d[36]), "=f"(d[37]), "=f"(d[38]), "=f"(d[39]), "=f"(d[40]), "=f"(d[41]), "=f"(d[42]), "=f"(d[43]), "=f"(d[44]),
      "=f"(d[45]), "=f"(d[46]), "=f"(d[47]), "=f"(d[48]), "=f"(d[49]), "=f"(d[50]), "=f"(d[51]), "=f"(d[52]), "=f"(d[53]),
      "=f"(d[54]), "=f"(d[55]), "=f"(d[56]), "=f"(d[57]), "=f"(d[58]), "=f"(d[59]), "=f"(d[60]), "=f"(d[61]), "=f"(d[62]),
      "=f"(d[63]), "=f"(d[64]), "=f"(d[65]), "=f"(d[66]), "=f"(d[67]), "=f"(d[68]), "=f"(d[69]), "=f"(d[70]), "=f"(d[71])
    : "r"(a[0]), "r"(a[1]), "r"(a[2]), "r"(a[3]), "r"(blo));
}
__device__ __forceinline__ void wgmma_n144_add(float* d, const uint32_t* a, uint32_t blo) {
  asm volatile("{\n.reg .b64 db;\nmov.b64 db, {%76, 2};\n"
    "wgmma.mma_async.sync.aligned.m64n144k16.f32.bf16.bf16 "
    "{%0, %1, %2, %3, %4, %5, %6, %7, %8, %9, %10, %11, %12, %13, %14, %15, %16, %17, %18, %19, %20, %21, %22, %23, %24, %25, %26, %27, %28, %29, %30, %31, %32, %33, %34, %35, %36, %37, %38, %39, %40, %41, %42, %43, %44, %45, %46, %47, %48, %49, %50, %51, %52, %53, %54, %55, %56, %57, %58, %59, %60, %61, %62, %63, %64, %65, %66, %67, %68, %69, %70, %71}, {%72, %73, %74, %75}, db, 1, -1, 1, 1;\n}\n"
    : "+f"(d[0]), "+f"(d[1]), "+f"(d[2]), "+f"(d[3]), "+f"(d[4]), "+f"(d[5]), "+f"(d[6]), "+f"(d[7]), "+f"(d[8]),
      "+f"(d[9]), "+f"(d[10]), "+f"(d[11]), "+f"(d[12]), "+f"(d[13]), "+f"(d[14]), "+f"(d[15]), "+f"(d[16]), "+f"(d[17]),
      "+f"(d[18]), "+f"(d[19]), "+f"(d[20]), "+f"(d[21]), "+f"(d[22]), "+f"(d[23]), "+f"(d[24]), "+f"(d[25]), "+f"(d[26]),
      "+f"(d[27]), "+f"(d[28]), "+f"(d[29]), "+f"(d[30]), "+f"(d[31]), "+f"(d[32]), "+f"(d[33]), "+f"(d[34]), "+f"(d[35]),
      "+f"(d[36]), "+f"(d[37]), "+f"(d[38]), "+f"(d[39]), "+f"(d[40]), "+f"(d[41]), "+f"(d[42]), "+f"(d[43]), "+f"(d[44]),
      "+f"(d[45]), "+f"(d[46]), "+f"(d[47]), "+f"(d[48]), "+f"(d[49]), "+f"(d[50]), "+f"(d[51]), "+f"(d[52]), "+f"(d[53]),
      "+f"(d[54]), "+f"(d[55]), "+f"(d[56]), "+f"(d[57]), "+f"(d[58]), "+f"(d[59]), "+f"(d[60]), "+f"(d[61]), "+f"(d[62]),
      "+f"(d[63]), "+f"(d[64]), "+f"(d[65]), "+f"(d[66]), "+f"(d[67]), "+f"(d[68]), "+f"(d[69]), "+f"(d[70]), "+f"(d[71])
    : "r"(a[0]), "r"(a[1]), "r"(a[2]), "r"(a[3]), "r"(blo));
}
__device__ __forceinline__ void wgmma_n72(float* d, uint32_t alo, uint32_t ahi, uint32_t blo) {
  asm volatile("{\n.reg .b64 da, db;\nmov.b64 da, {%36, %37};\nmov.b64 db, {%38, 8};\n"
    "wgmma.mma_async.sync.aligned.m64n72k16.f32.bf16.bf16 "
    "{%0, %1, %2, %3, %4, %5, %6, %7, %8, %9, %10, %11, %12, %13, %14, %15, %16, %17, %18, %19, %20, %21, %22, %23, %24, %25, %26, %27, %28, %29, %30, %31, %32, %33, %34, %35}, da, db, 1, 1, 1, 0, 1;\n}\n"
    : "+f"(d[0]), "+f"(d[1]), "+f"(d[2]), "+f"(d[3]), "+f"(d[4]), "+f"(d[5]), "+f"(d[6]), "+f"(d[7]), "+f"(d[8]),
      "+f"(d[9]), "+f"(d[10]), "+f"(d[11]), "+f"(d[12]), "+f"(d[13]), "+f"(d[14]), "+f"(d[15]), "+f"(d[16]), "+f"(d[17]),
      "+f"(d[18]), "+f"(d[19]), "+f"(d[20]), "+f"(d[21]), "+f"(d[22]), "+f"(d[23]), "+f"(d[24]), "+f"(d[25]), "+f"(d[26]),
      "+f"(d[27]), "+f"(d[28]), "+f"(d[29]), "+f"(d[30]), "+f"(d[31]), "+f"(d[32]), "+f"(d[33]), "+f"(d[34]), "+f"(d[35])
    : "r"(alo), "r"(ahi), "r"(blo));
}
__device__ __forceinline__ void wgmma_n72_set(float* d, const uint32_t* a, uint32_t blo) {
  asm volatile("{\n.reg .b64 db;\nmov.b64 db, {%40, 2};\n"
    "wgmma.mma_async.sync.aligned.m64n72k16.f32.bf16.bf16 "
    "{%0, %1, %2, %3, %4, %5, %6, %7, %8, %9, %10, %11, %12, %13, %14, %15, %16, %17, %18, %19, %20, %21, %22, %23, %24, %25, %26, %27, %28, %29, %30, %31, %32, %33, %34, %35}, {%36, %37, %38, %39}, db, 0, -1, 1, 1;\n}\n"
    : "=f"(d[0]), "=f"(d[1]), "=f"(d[2]), "=f"(d[3]), "=f"(d[4]), "=f"(d[5]), "=f"(d[6]), "=f"(d[7]), "=f"(d[8]),
      "=f"(d[9]), "=f"(d[10]), "=f"(d[11]), "=f"(d[12]), "=f"(d[13]), "=f"(d[14]), "=f"(d[15]), "=f"(d[16]), "=f"(d[17]),
      "=f"(d[18]), "=f"(d[19]), "=f"(d[20]), "=f"(d[21]), "=f"(d[22]), "=f"(d[23]), "=f"(d[24]), "=f"(d[25]), "=f"(d[26]),
      "=f"(d[27]), "=f"(d[28]), "=f"(d[29]), "=f"(d[30]), "=f"(d[31]), "=f"(d[32]), "=f"(d[33]), "=f"(d[34]), "=f"(d[35])
    : "r"(a[0]), "r"(a[1]), "r"(a[2]), "r"(a[3]), "r"(blo));
}
__device__ __forceinline__ void wgmma_n72_add(float* d, const uint32_t* a, uint32_t blo) {
  asm volatile("{\n.reg .b64 db;\nmov.b64 db, {%40, 2};\n"
    "wgmma.mma_async.sync.aligned.m64n72k16.f32.bf16.bf16 "
    "{%0, %1, %2, %3, %4, %5, %6, %7, %8, %9, %10, %11, %12, %13, %14, %15, %16, %17, %18, %19, %20, %21, %22, %23, %24, %25, %26, %27, %28, %29, %30, %31, %32, %33, %34, %35}, {%36, %37, %38, %39}, db, 1, -1, 1, 1;\n}\n"
    : "+f"(d[0]), "+f"(d[1]), "+f"(d[2]), "+f"(d[3]), "+f"(d[4]), "+f"(d[5]), "+f"(d[6]), "+f"(d[7]), "+f"(d[8]),
      "+f"(d[9]), "+f"(d[10]), "+f"(d[11]), "+f"(d[12]), "+f"(d[13]), "+f"(d[14]), "+f"(d[15]), "+f"(d[16]), "+f"(d[17]),
      "+f"(d[18]), "+f"(d[19]), "+f"(d[20]), "+f"(d[21]), "+f"(d[22]), "+f"(d[23]), "+f"(d[24]), "+f"(d[25]), "+f"(d[26]),
      "+f"(d[27]), "+f"(d[28]), "+f"(d[29]), "+f"(d[30]), "+f"(d[31]), "+f"(d[32]), "+f"(d[33]), "+f"(d[34]), "+f"(d[35])
    : "r"(a[0]), "r"(a[1]), "r"(a[2]), "r"(a[3]), "r"(blo));
}
__device__ __forceinline__ void q_tail(float* d, uint32_t* v, uint32_t ahi, const uint32_t* dsc, const uint32_t* bar, const uint32_t* adr) {
  asm volatile(
    "{\n.reg .pred p<2>, q;\n.reg .b64 da, db;\n.reg .u32 n;\n"
    "mbarrier.test_wait.parity.shared::cta.b64 p0, [%116], %117;\n"
    "mbarrier.test_wait.parity.shared::cta.b64 p1, [%118], %119;\n"
    "ld.volatile.shared.u32 %108, [%120];\n"
    "mov.b64 da, {%110, %109};\nmov.b64 db, {%111, 8};\n"
    "wgmma.mma_async.sync.aligned.m64n144k16.f32.bf16.bf16 {%36, %37, %38, %39, %40, %41, %42, %43, %44, %45, %46, %47, %48, %49, %50, %51, %52, %53, %54, %55, %56, %57, %58, %59, %60, %61, %62, %63, %64, %65, %66, %67, %68, %69, %70, %71, %72, %73, %74, %75, %76, %77, %78, %79, %80, %81, %82, %83, %84, %85, %86, %87, %88, %89, %90, %91, %92, %93, %94, %95, %96, %97, %98, %99, %100, %101, %102, %103, %104, %105, %106, %107}, da, db, 1, 1, 1, 0, 1;\n"
    "mov.b64 da, {%112, %109};\nmov.b64 db, {%113, 8};\n"
    "wgmma.mma_async.sync.aligned.m64n72k16.f32.bf16.bf16 {%0, %1, %2, %3, %4, %5, %6, %7, %8, %9, %10, %11, %12, %13, %14, %15, %16, %17, %18, %19, %20, %21, %22, %23, %24, %25, %26, %27, %28, %29, %30, %31, %32, %33, %34, %35}, da, db, 1, 1, 1, 0, 1;\n"
    "mov.b64 da, {%114, %109};\nmov.b64 db, {%115, 8};\n"
    "wgmma.mma_async.sync.aligned.m64n144k16.f32.bf16.bf16 {%36, %37, %38, %39, %40, %41, %42, %43, %44, %45, %46, %47, %48, %49, %50, %51, %52, %53, %54, %55, %56, %57, %58, %59, %60, %61, %62, %63, %64, %65, %66, %67, %68, %69, %70, %71, %72, %73, %74, %75, %76, %77, %78, %79, %80, %81, %82, %83, %84, %85, %86, %87, %88, %89, %90, %91, %92, %93, %94, %95, %96, %97, %98, %99, %100, %101, %102, %103, %104, %105, %106, %107}, da, db, 1, 1, 1, 0, 1;\n"
    "wgmma.commit_group.sync.aligned;\n"
    "@p0 bra.uni D0;\nmov.u32 n, 0;\nW0:\nmbarrier.try_wait.parity.shared::cta.b64 q, [%116], %117;\n@q bra.uni R0;\nadd.u32 n, n, 1;\nsetp.lt.u32 q, n, 8192;\n@q bra.uni W0;\nR0:\n"
    "D0:\n"
    "@p1 bra.uni D1;\nmov.u32 n, 0;\nW1:\nmbarrier.try_wait.parity.shared::cta.b64 q, [%118], %119;\n@q bra.uni R1;\nadd.u32 n, n, 1;\nsetp.lt.u32 q, n, 8192;\n@q bra.uni W1;\nR1:\n"
    "ld.volatile.shared.u32 %108, [%120];\n"
    "D1:\n"
    "}\n"
    : "+f"(d[0]), "+f"(d[1]), "+f"(d[2]), "+f"(d[3]), "+f"(d[4]), "+f"(d[5]), "+f"(d[6]), "+f"(d[7]), "+f"(d[8]),
      "+f"(d[9]), "+f"(d[10]), "+f"(d[11]), "+f"(d[12]), "+f"(d[13]), "+f"(d[14]), "+f"(d[15]), "+f"(d[16]), "+f"(d[17]),
      "+f"(d[18]), "+f"(d[19]), "+f"(d[20]), "+f"(d[21]), "+f"(d[22]), "+f"(d[23]), "+f"(d[24]), "+f"(d[25]), "+f"(d[26]),
      "+f"(d[27]), "+f"(d[28]), "+f"(d[29]), "+f"(d[30]), "+f"(d[31]), "+f"(d[32]), "+f"(d[33]), "+f"(d[34]), "+f"(d[35]),
      "+f"(d[36]), "+f"(d[37]), "+f"(d[38]), "+f"(d[39]), "+f"(d[40]), "+f"(d[41]), "+f"(d[42]), "+f"(d[43]), "+f"(d[44]),
      "+f"(d[45]), "+f"(d[46]), "+f"(d[47]), "+f"(d[48]), "+f"(d[49]), "+f"(d[50]), "+f"(d[51]), "+f"(d[52]), "+f"(d[53]),
      "+f"(d[54]), "+f"(d[55]), "+f"(d[56]), "+f"(d[57]), "+f"(d[58]), "+f"(d[59]), "+f"(d[60]), "+f"(d[61]), "+f"(d[62]),
      "+f"(d[63]), "+f"(d[64]), "+f"(d[65]), "+f"(d[66]), "+f"(d[67]), "+f"(d[68]), "+f"(d[69]), "+f"(d[70]), "+f"(d[71]),
      "+f"(d[72]), "+f"(d[73]), "+f"(d[74]), "+f"(d[75]), "+f"(d[76]), "+f"(d[77]), "+f"(d[78]), "+f"(d[79]), "+f"(d[80]),
      "+f"(d[81]), "+f"(d[82]), "+f"(d[83]), "+f"(d[84]), "+f"(d[85]), "+f"(d[86]), "+f"(d[87]), "+f"(d[88]), "+f"(d[89]),
      "+f"(d[90]), "+f"(d[91]), "+f"(d[92]), "+f"(d[93]), "+f"(d[94]), "+f"(d[95]), "+f"(d[96]), "+f"(d[97]), "+f"(d[98]),
      "+f"(d[99]), "+f"(d[100]), "+f"(d[101]), "+f"(d[102]), "+f"(d[103]), "+f"(d[104]), "+f"(d[105]), "+f"(d[106]), "+f"(d[107]),
      "=&r"(v[0])
    : "r"(ahi), "r"(dsc[0]), "r"(dsc[1]), "r"(dsc[2]), "r"(dsc[3]), "r"(dsc[4]), "r"(dsc[5]), "r"(bar[0]), "r"(bar[1]), "r"(bar[2]), "r"(bar[3]), "r"(adr[0]) : "memory");
}
__device__ __forceinline__ void kv_tail(float* d, uint32_t* v, uint32_t ahi, const uint32_t* dsc, const uint32_t* bar, const uint32_t* adr) {
  asm volatile(
    "{\n.reg .pred p<3>, q;\n.reg .b64 da, db;\n.reg .u32 n;\n"
    "mbarrier.test_wait.parity.shared::cta.b64 p0, [%79], %80;\n"
    "mbarrier.test_wait.parity.shared::cta.b64 p1, [%81], %82;\n"
    "mbarrier.test_wait.parity.shared::cta.b64 p2, [%83], %84;\n"
    "ld.volatile.shared.u32 %72, [%85];\n"
    "ld.volatile.shared.u32 %73, [%86];\n"
    "mov.b64 da, {%75, %74};\nmov.b64 db, {%76, 8};\n"
    "wgmma.mma_async.sync.aligned.m64n144k16.f32.bf16.bf16 {%0, %1, %2, %3, %4, %5, %6, %7, %8, %9, %10, %11, %12, %13, %14, %15, %16, %17, %18, %19, %20, %21, %22, %23, %24, %25, %26, %27, %28, %29, %30, %31, %32, %33, %34, %35, %36, %37, %38, %39, %40, %41, %42, %43, %44, %45, %46, %47, %48, %49, %50, %51, %52, %53, %54, %55, %56, %57, %58, %59, %60, %61, %62, %63, %64, %65, %66, %67, %68, %69, %70, %71}, da, db, 1, 1, 1, 0, 1;\n"
    "mov.b64 da, {%77, %74};\nmov.b64 db, {%78, 8};\n"
    "wgmma.mma_async.sync.aligned.m64n144k16.f32.bf16.bf16 {%0, %1, %2, %3, %4, %5, %6, %7, %8, %9, %10, %11, %12, %13, %14, %15, %16, %17, %18, %19, %20, %21, %22, %23, %24, %25, %26, %27, %28, %29, %30, %31, %32, %33, %34, %35, %36, %37, %38, %39, %40, %41, %42, %43, %44, %45, %46, %47, %48, %49, %50, %51, %52, %53, %54, %55, %56, %57, %58, %59, %60, %61, %62, %63, %64, %65, %66, %67, %68, %69, %70, %71}, da, db, 1, 1, 1, 0, 1;\n"
    "wgmma.commit_group.sync.aligned;\n"
    "@p0 bra.uni D0;\nmov.u32 n, 0;\nW0:\nmbarrier.try_wait.parity.shared::cta.b64 q, [%79], %80;\n@q bra.uni R0;\nadd.u32 n, n, 1;\nsetp.lt.u32 q, n, 8192;\n@q bra.uni W0;\nR0:\n"
    "D0:\n"
    "@p1 bra.uni D1;\nmov.u32 n, 0;\nW1:\nmbarrier.try_wait.parity.shared::cta.b64 q, [%81], %82;\n@q bra.uni R1;\nadd.u32 n, n, 1;\nsetp.lt.u32 q, n, 8192;\n@q bra.uni W1;\nR1:\n"
    "ld.volatile.shared.u32 %72, [%85];\n"
    "D1:\n"
    "@p2 bra.uni D2;\nmov.u32 n, 0;\nW2:\nmbarrier.try_wait.parity.shared::cta.b64 q, [%83], %84;\n@q bra.uni R2;\nadd.u32 n, n, 1;\nsetp.lt.u32 q, n, 8192;\n@q bra.uni W2;\nR2:\n"
    "ld.volatile.shared.u32 %73, [%86];\n"
    "D2:\n"
    "}\n"
    : "+f"(d[36]), "+f"(d[37]), "+f"(d[38]), "+f"(d[39]), "+f"(d[40]), "+f"(d[41]), "+f"(d[42]), "+f"(d[43]), "+f"(d[44]),
      "+f"(d[45]), "+f"(d[46]), "+f"(d[47]), "+f"(d[48]), "+f"(d[49]), "+f"(d[50]), "+f"(d[51]), "+f"(d[52]), "+f"(d[53]),
      "+f"(d[54]), "+f"(d[55]), "+f"(d[56]), "+f"(d[57]), "+f"(d[58]), "+f"(d[59]), "+f"(d[60]), "+f"(d[61]), "+f"(d[62]),
      "+f"(d[63]), "+f"(d[64]), "+f"(d[65]), "+f"(d[66]), "+f"(d[67]), "+f"(d[68]), "+f"(d[69]), "+f"(d[70]), "+f"(d[71]),
      "+f"(d[72]), "+f"(d[73]), "+f"(d[74]), "+f"(d[75]), "+f"(d[76]), "+f"(d[77]), "+f"(d[78]), "+f"(d[79]), "+f"(d[80]),
      "+f"(d[81]), "+f"(d[82]), "+f"(d[83]), "+f"(d[84]), "+f"(d[85]), "+f"(d[86]), "+f"(d[87]), "+f"(d[88]), "+f"(d[89]),
      "+f"(d[90]), "+f"(d[91]), "+f"(d[92]), "+f"(d[93]), "+f"(d[94]), "+f"(d[95]), "+f"(d[96]), "+f"(d[97]), "+f"(d[98]),
      "+f"(d[99]), "+f"(d[100]), "+f"(d[101]), "+f"(d[102]), "+f"(d[103]), "+f"(d[104]), "+f"(d[105]), "+f"(d[106]), "+f"(d[107]),
      "=&r"(v[0]), "=&r"(v[1])
    : "r"(ahi), "r"(dsc[0]), "r"(dsc[1]), "r"(dsc[2]), "r"(dsc[3]), "r"(bar[0]), "r"(bar[1]), "r"(bar[2]), "r"(bar[3]), "r"(bar[4]), "r"(bar[5]), "r"(adr[0]), "r"(adr[1]) : "memory");
}
__device__ __forceinline__ void kv_last(float* d, uint32_t* v, uint32_t ahi, const uint32_t* dsc, const uint32_t* bar, const uint32_t* adr) {
  asm volatile(
    "{\n.reg .pred p<1>, q;\n.reg .b64 da, db;\n.reg .u32 n;\n"
    "mbarrier.test_wait.parity.shared::cta.b64 p0, [%81], %82;\n"
    "mov.b64 da, {%73, %72};\nmov.b64 db, {%74, 8};\n"
    "wgmma.mma_async.sync.aligned.m64n144k16.f32.bf16.bf16 {%0, %1, %2, %3, %4, %5, %6, %7, %8, %9, %10, %11, %12, %13, %14, %15, %16, %17, %18, %19, %20, %21, %22, %23, %24, %25, %26, %27, %28, %29, %30, %31, %32, %33, %34, %35, %36, %37, %38, %39, %40, %41, %42, %43, %44, %45, %46, %47, %48, %49, %50, %51, %52, %53, %54, %55, %56, %57, %58, %59, %60, %61, %62, %63, %64, %65, %66, %67, %68, %69, %70, %71}, da, db, 1, 1, 1, 0, 1;\n"
    "mov.b64 da, {%75, %72};\nmov.b64 db, {%76, 8};\n"
    "wgmma.mma_async.sync.aligned.m64n144k16.f32.bf16.bf16 {%0, %1, %2, %3, %4, %5, %6, %7, %8, %9, %10, %11, %12, %13, %14, %15, %16, %17, %18, %19, %20, %21, %22, %23, %24, %25, %26, %27, %28, %29, %30, %31, %32, %33, %34, %35, %36, %37, %38, %39, %40, %41, %42, %43, %44, %45, %46, %47, %48, %49, %50, %51, %52, %53, %54, %55, %56, %57, %58, %59, %60, %61, %62, %63, %64, %65, %66, %67, %68, %69, %70, %71}, da, db, 1, 1, 1, 0, 1;\n"
    "mov.b64 da, {%77, %72};\nmov.b64 db, {%78, 8};\n"
    "wgmma.mma_async.sync.aligned.m64n144k16.f32.bf16.bf16 {%0, %1, %2, %3, %4, %5, %6, %7, %8, %9, %10, %11, %12, %13, %14, %15, %16, %17, %18, %19, %20, %21, %22, %23, %24, %25, %26, %27, %28, %29, %30, %31, %32, %33, %34, %35, %36, %37, %38, %39, %40, %41, %42, %43, %44, %45, %46, %47, %48, %49, %50, %51, %52, %53, %54, %55, %56, %57, %58, %59, %60, %61, %62, %63, %64, %65, %66, %67, %68, %69, %70, %71}, da, db, 1, 1, 1, 0, 1;\n"
    "mov.b64 da, {%79, %72};\nmov.b64 db, {%80, 8};\n"
    "wgmma.mma_async.sync.aligned.m64n144k16.f32.bf16.bf16 {%0, %1, %2, %3, %4, %5, %6, %7, %8, %9, %10, %11, %12, %13, %14, %15, %16, %17, %18, %19, %20, %21, %22, %23, %24, %25, %26, %27, %28, %29, %30, %31, %32, %33, %34, %35, %36, %37, %38, %39, %40, %41, %42, %43, %44, %45, %46, %47, %48, %49, %50, %51, %52, %53, %54, %55, %56, %57, %58, %59, %60, %61, %62, %63, %64, %65, %66, %67, %68, %69, %70, %71}, da, db, 1, 1, 1, 0, 1;\n"
    "wgmma.commit_group.sync.aligned;\n"
    "@p0 bra.uni D0;\nmov.u32 n, 0;\nW0:\nmbarrier.try_wait.parity.shared::cta.b64 q, [%81], %82;\n@q bra.uni R0;\nadd.u32 n, n, 1;\nsetp.lt.u32 q, n, 8192;\n@q bra.uni W0;\nR0:\n"
    "D0:\n"
    "}\n"
    : "+f"(d[36]), "+f"(d[37]), "+f"(d[38]), "+f"(d[39]), "+f"(d[40]), "+f"(d[41]), "+f"(d[42]), "+f"(d[43]), "+f"(d[44]),
      "+f"(d[45]), "+f"(d[46]), "+f"(d[47]), "+f"(d[48]), "+f"(d[49]), "+f"(d[50]), "+f"(d[51]), "+f"(d[52]), "+f"(d[53]),
      "+f"(d[54]), "+f"(d[55]), "+f"(d[56]), "+f"(d[57]), "+f"(d[58]), "+f"(d[59]), "+f"(d[60]), "+f"(d[61]), "+f"(d[62]),
      "+f"(d[63]), "+f"(d[64]), "+f"(d[65]), "+f"(d[66]), "+f"(d[67]), "+f"(d[68]), "+f"(d[69]), "+f"(d[70]), "+f"(d[71]),
      "+f"(d[72]), "+f"(d[73]), "+f"(d[74]), "+f"(d[75]), "+f"(d[76]), "+f"(d[77]), "+f"(d[78]), "+f"(d[79]), "+f"(d[80]),
      "+f"(d[81]), "+f"(d[82]), "+f"(d[83]), "+f"(d[84]), "+f"(d[85]), "+f"(d[86]), "+f"(d[87]), "+f"(d[88]), "+f"(d[89]),
      "+f"(d[90]), "+f"(d[91]), "+f"(d[92]), "+f"(d[93]), "+f"(d[94]), "+f"(d[95]), "+f"(d[96]), "+f"(d[97]), "+f"(d[98]),
      "+f"(d[99]), "+f"(d[100]), "+f"(d[101]), "+f"(d[102]), "+f"(d[103]), "+f"(d[104]), "+f"(d[105]), "+f"(d[106]), "+f"(d[107])
    : "r"(ahi), "r"(dsc[0]), "r"(dsc[1]), "r"(dsc[2]), "r"(dsc[3]), "r"(dsc[4]), "r"(dsc[5]), "r"(dsc[6]), "r"(dsc[7]), "r"(bar[0]), "r"(bar[1]) : "memory");
}
__device__ __forceinline__ void o_tail(float* d, uint32_t* v, uint32_t ahi, const uint32_t* dsc, const uint32_t* bar, const uint32_t* adr) {
  asm volatile(
    "{\n.reg .pred p<1>, q;\n.reg .b64 da, db;\n.reg .u32 n;\n"
    "mbarrier.test_wait.parity.shared::cta.b64 p0, [%42], %43;\n"
    "ld.volatile.shared.u32 %36, [%44];\n"
    "mov.b64 da, {%38, %37};\nmov.b64 db, {%39, 8};\n"
    "wgmma.mma_async.sync.aligned.m64n72k16.f32.bf16.bf16 {%0, %1, %2, %3, %4, %5, %6, %7, %8, %9, %10, %11, %12, %13, %14, %15, %16, %17, %18, %19, %20, %21, %22, %23, %24, %25, %26, %27, %28, %29, %30, %31, %32, %33, %34, %35}, da, db, 1, 1, 1, 0, 1;\n"
    "mov.b64 da, {%40, %37};\nmov.b64 db, {%41, 8};\n"
    "wgmma.mma_async.sync.aligned.m64n72k16.f32.bf16.bf16 {%0, %1, %2, %3, %4, %5, %6, %7, %8, %9, %10, %11, %12, %13, %14, %15, %16, %17, %18, %19, %20, %21, %22, %23, %24, %25, %26, %27, %28, %29, %30, %31, %32, %33, %34, %35}, da, db, 1, 1, 1, 0, 1;\n"
    "wgmma.commit_group.sync.aligned;\n"
    "@p0 bra.uni D0;\nmov.u32 n, 0;\nW0:\nmbarrier.try_wait.parity.shared::cta.b64 q, [%42], %43;\n@q bra.uni R0;\nadd.u32 n, n, 1;\nsetp.lt.u32 q, n, 8192;\n@q bra.uni W0;\nR0:\n"
    "ld.volatile.shared.u32 %36, [%44];\n"
    "D0:\n"
    "}\n"
    : "+f"(d[0]), "+f"(d[1]), "+f"(d[2]), "+f"(d[3]), "+f"(d[4]), "+f"(d[5]), "+f"(d[6]), "+f"(d[7]), "+f"(d[8]),
      "+f"(d[9]), "+f"(d[10]), "+f"(d[11]), "+f"(d[12]), "+f"(d[13]), "+f"(d[14]), "+f"(d[15]), "+f"(d[16]), "+f"(d[17]),
      "+f"(d[18]), "+f"(d[19]), "+f"(d[20]), "+f"(d[21]), "+f"(d[22]), "+f"(d[23]), "+f"(d[24]), "+f"(d[25]), "+f"(d[26]),
      "+f"(d[27]), "+f"(d[28]), "+f"(d[29]), "+f"(d[30]), "+f"(d[31]), "+f"(d[32]), "+f"(d[33]), "+f"(d[34]), "+f"(d[35]),
      "=&r"(v[0])
    : "r"(ahi), "r"(dsc[0]), "r"(dsc[1]), "r"(dsc[2]), "r"(dsc[3]), "r"(bar[0]), "r"(bar[1]), "r"(adr[0]) : "memory");
}
__device__ __forceinline__ void o_tail2(float* d, uint32_t* v, uint32_t ahi, const uint32_t* dsc, const uint32_t* bar, const uint32_t* adr) {
  asm volatile(
    "{\n.reg .pred p<2>, q;\n.reg .b64 da, db;\n.reg .u32 n;\n"
    "mbarrier.test_wait.parity.shared::cta.b64 p0, [%42], %43;\n"
    "mbarrier.test_wait.parity.shared::cta.b64 p1, [%44], %45;\n"
    "ld.volatile.shared.u32 %36, [%46];\n"
    "mov.b64 da, {%38, %37};\nmov.b64 db, {%39, 8};\n"
    "wgmma.mma_async.sync.aligned.m64n72k16.f32.bf16.bf16 {%0, %1, %2, %3, %4, %5, %6, %7, %8, %9, %10, %11, %12, %13, %14, %15, %16, %17, %18, %19, %20, %21, %22, %23, %24, %25, %26, %27, %28, %29, %30, %31, %32, %33, %34, %35}, da, db, 1, 1, 1, 0, 1;\n"
    "mov.b64 da, {%40, %37};\nmov.b64 db, {%41, 8};\n"
    "wgmma.mma_async.sync.aligned.m64n72k16.f32.bf16.bf16 {%0, %1, %2, %3, %4, %5, %6, %7, %8, %9, %10, %11, %12, %13, %14, %15, %16, %17, %18, %19, %20, %21, %22, %23, %24, %25, %26, %27, %28, %29, %30, %31, %32, %33, %34, %35}, da, db, 1, 1, 1, 0, 1;\n"
    "wgmma.commit_group.sync.aligned;\n"
    "@p0 bra.uni D0;\nmov.u32 n, 0;\nW0:\nmbarrier.try_wait.parity.shared::cta.b64 q, [%42], %43;\n@q bra.uni R0;\nadd.u32 n, n, 1;\nsetp.lt.u32 q, n, 8192;\n@q bra.uni W0;\nR0:\n"
    "D0:\n"
    "@p1 bra.uni D1;\nmov.u32 n, 0;\nW1:\nmbarrier.try_wait.parity.shared::cta.b64 q, [%44], %45;\n@q bra.uni R1;\nadd.u32 n, n, 1;\nsetp.lt.u32 q, n, 8192;\n@q bra.uni W1;\nR1:\n"
    "ld.volatile.shared.u32 %36, [%46];\n"
    "D1:\n"
    "}\n"
    : "+f"(d[0]), "+f"(d[1]), "+f"(d[2]), "+f"(d[3]), "+f"(d[4]), "+f"(d[5]), "+f"(d[6]), "+f"(d[7]), "+f"(d[8]),
      "+f"(d[9]), "+f"(d[10]), "+f"(d[11]), "+f"(d[12]), "+f"(d[13]), "+f"(d[14]), "+f"(d[15]), "+f"(d[16]), "+f"(d[17]),
      "+f"(d[18]), "+f"(d[19]), "+f"(d[20]), "+f"(d[21]), "+f"(d[22]), "+f"(d[23]), "+f"(d[24]), "+f"(d[25]), "+f"(d[26]),
      "+f"(d[27]), "+f"(d[28]), "+f"(d[29]), "+f"(d[30]), "+f"(d[31]), "+f"(d[32]), "+f"(d[33]), "+f"(d[34]), "+f"(d[35]),
      "=&r"(v[0])
    : "r"(ahi), "r"(dsc[0]), "r"(dsc[1]), "r"(dsc[2]), "r"(dsc[3]), "r"(bar[0]), "r"(bar[1]), "r"(bar[2]), "r"(bar[3]), "r"(adr[0]) : "memory");
}

DEVI void mbar_init(uint32_t b, int c) { asm volatile("mbarrier.init.shared::cta.b64 [%0], %1;" ::"r"(b), "r"(c)); }
DEVI void mbar_arrive(uint32_t b) { asm volatile("mbarrier.arrive.shared::cta.b64 _, [%0];" ::"r"(b) : "memory"); }
DEVI void mbar_expect(uint32_t b, uint32_t tx) {
  asm volatile("mbarrier.arrive.expect_tx.shared::cta.b64 _, [%0], %1;" ::"r"(b), "r"(tx) : "memory");
}
DEVI void mbar_wait(uint32_t b, uint32_t ph) {
  asm volatile(
      "{\n.reg .pred p;\n.reg .u32 n;\nmov.u32 n, 0;\n"
      "LW:\nmbarrier.try_wait.parity.shared::cta.b64 p, [%0], %1;\n"
      "@p bra LD;\nadd.u32 n, n, 1;\nsetp.lt.u32 p, n, 8192;\n@p bra LW;\nLD:\n}\n" ::"r"(b), "r"(ph)
      : "memory");
}
DEVI void mbar_wait2(uint32_t a, uint32_t pa, uint32_t b, uint32_t pb) {
  asm volatile(
      "{\n.reg .pred p, q;\n.reg .u32 n;\nmov.u32 n, 0;\n"
      "LW:\nmbarrier.try_wait.parity.shared::cta.b64 p, [%0], %1;\nmbarrier.try_wait.parity.shared::cta.b64 q, [%2], %3;\n"
      "and.pred p, p, q;\n@p bra LD;\nadd.u32 n, n, 1;\nsetp.lt.u32 p, n, 8192;\n@p bra LW;\nLD:\n}\n" ::"r"(a), "r"(pa), "r"(b), "r"(pb)
      : "memory");
}
DEVI bool elect() {
  uint32_t el;
  asm volatile("{\n.reg .pred p;\nelect.sync _|p, 0xffffffff;\nselp.u32 %0,1,0,p;\n}\n" : "=r"(el));
  return el;
}
DEVI void bulk_g2s(uint32_t dst, const void* src, uint32_t bytes, uint32_t bar) {
  asm volatile("cp.async.bulk.shared::cluster.global.mbarrier::complete_tx::bytes [%0], [%1], %2, [%3];" ::"r"(dst),
               "l"(src), "r"(bytes), "r"(bar)
               : "memory");
}
DEVI void bulk_g2s_pair(uint32_t dst, const void* src, uint32_t bytes, uint32_t bar) {
  asm volatile("cp.async.bulk.shared::cluster.global.mbarrier::complete_tx::bytes.multicast::cluster [%0], [%1], %2, [%3], %4;" ::"r"(dst),
               "l"(src), "r"(bytes), "r"(bar), "h"((uint16_t)3)
               : "memory");
}
DEVI void mbar_arrive_pair(uint32_t b) {
  asm volatile("mbarrier.arrive.shared::cta.b64 _, [%0];\nmbarrier.arrive.shared::cluster.b64 _, [%1];\n" ::"r"(b), "r"(b ^ 0x1000000u) : "memory");
}
DEVI void cluster_arrive() { asm volatile("barrier.cluster.arrive.relaxed.aligned;" ::: "memory"); }
DEVI void cluster_wait() { asm volatile("barrier.cluster.wait.aligned;" ::: "memory"); }
DEVI void tma3(uint32_t dst, const CUtensorMap* m, int c0, int c1, int c2, uint32_t bar) {
  asm volatile(
      "cp.async.bulk.tensor.3d.shared::cluster.global.mbarrier::complete_tx::bytes [%0], [%1, {%3,%4,%5}], [%2];" ::"r"(dst),
      "l"(m), "r"(bar), "r"(c0), "r"(c1), "r"(c2)
      : "memory");
}
DEVI constexpr uint32_t mkdesc(uint32_t addr, uint32_t lbo) { return ((addr & 0x3FFFF) >> 4) | ((lbo >> 4) << 16); }
DEVI void bar_sync(int id) { asm volatile("bar.sync %0, 128;" ::"r"(id) : "memory"); }
DEVI uint4 ld_msg(const void* p) {
  uint4 v;
  asm volatile("ld.relaxed.gpu.global.v4.u32 {%0,%1,%2,%3}, [%4];" : "=r"(v.x), "=r"(v.y), "=r"(v.z), "=r"(v.w) : "l"(p) : "memory");
  return v;
}
DEVI void st_msg(void* p, uint32_t a, uint32_t b, uint32_t c, uint32_t d) {
  asm volatile("st.relaxed.gpu.global.v4.u32 [%0], {%1,%2,%3,%4};" ::"l"(p), "r"(a), "r"(b), "r"(c), "r"(d) : "memory");
}
DEVI uint4 ld_gen(const void* p) {
  uint4 v;
  asm volatile("ld.relaxed.gpu.v4.u32 {%0,%1,%2,%3}, [%4];" : "=r"(v.x), "=r"(v.y), "=r"(v.z), "=r"(v.w) : "l"(p) : "memory");
  return v;
}
DEVI void st_gen(void* p, uint32_t a, uint32_t b, uint32_t c, uint32_t d) {
  asm volatile("st.relaxed.gpu.v4.u32 [%0], {%1,%2,%3,%4};" ::"l"(p), "r"(a), "r"(b), "r"(c), "r"(d) : "memory");
}
DEVI uint32_t ld_rlx(const void* p) {
  uint32_t v;
  asm volatile("ld.relaxed.gpu.global.u32 %0, [%1];" : "=r"(v) : "l"(p) : "memory");
  return v;
}
DEVI uint2 ld_rlx2(const void* p) {
  uint2 v;
  asm volatile("ld.relaxed.gpu.global.v2.u32 {%0,%1}, [%2];" : "=r"(v.x), "=r"(v.y) : "l"(p) : "memory");
  return v;
}
DEVI void st_rlx(void* p, uint32_t v) { asm volatile("st.relaxed.gpu.global.u32 [%0], %1;" ::"l"(p), "r"(v) : "memory"); }
#define spin_guard(n) if (++n > (1u << 16)) break
DEVI void wait_flags(const uint8_t* p, int word, uint32_t target) {
  uint32_t n = 0;
  p += 4 * word;
  _Pragma("unroll 1") while (__any_sync(0xffffffffu, (int)(ld_rlx(p) - target) < 0)) spin_guard(n);
  asm volatile("fence.acquire.gpu;" ::: "memory");
  asm volatile("fence.proxy.async.global;" ::: "memory");
}
DEVI void bulk_s2g(void* dst, uint32_t src, uint32_t bytes) {
  asm volatile("cp.async.bulk.global.shared::cta.bulk_group [%0], [%1], %2;" ::"l"(dst), "r"(src), "r"(bytes) : "memory");
}
#define ABL 0
DEVI void l2_prefetch(const void* p, uint32_t bytes) { if (!(ABL & 2)) asm volatile("cp.async.bulk.prefetch.L2.global [%0], %1;" ::"l"(p), "r"(bytes) : "memory"); }
DEVI void fence_async_smem() { asm volatile("fence.proxy.async.shared::cta;" ::: "memory"); }
DEVI void tma2(uint32_t dst, const CUtensorMap* m, int c0, int c1, uint32_t bar) {
  asm volatile("cp.async.bulk.tensor.2d.shared::cluster.global.mbarrier::complete_tx::bytes [%0], [%1, {%3,%4}], [%2];" ::"r"(dst),
               "l"(m), "r"(bar), "r"(c0), "r"(c1) : "memory");
}
DEVI void stsm4(uint32_t a, uint32_t r0, uint32_t r1, uint32_t r2, uint32_t r3) {
  asm volatile("stmatrix.sync.aligned.m8n8.x4.shared.b16 [%0], {%1,%2,%3,%4};" ::"r"(a), "r"(r0), "r"(r1), "r"(r2), "r"(r3) : "memory");
}
DEVI void stsm2(uint32_t a, uint32_t r0, uint32_t r1) {
  asm volatile("stmatrix.sync.aligned.m8n8.x2.shared.b16 [%0], {%1,%2};" ::"r"(a), "r"(r0), "r"(r1) : "memory");
}
DEVI uint32_t mbar_test(uint32_t b, uint32_t ph) {
  uint32_t ok;
  asm volatile("{\n.reg .pred p;\nmbarrier.test_wait.parity.shared::cta.b64 p, [%1], %2;\nselp.u32 %0,1,0,p;\n}\n"
               : "=r"(ok) : "r"(b), "r"(ph) : "memory");
  return ok;
}
DEVI void st_rlx2(void* p, uint32_t a, uint32_t b) {
  asm volatile("{\n.reg .b64 v;\nmov.b64 v, {%1,%2};\nst.relaxed.gpu.global.b64 [%0], v;\n}\n" ::"l"(p), "r"(a), "r"(b) : "memory");
}
DEVI float selp(int c, float a, float b) {
  float y;
  asm("{\n.reg .pred p;\nsetp.ne.s32 p, %3, 0;\nselp.f32 %0, %1, %2, p;\n}\n" : "=f"(y) : "f"(a), "f"(b), "r"(c));
  return y;
}
DEVI float ex2(float x) { float y; asm("ex2.approx.ftz.f32 %0, %1;" : "=f"(y) : "f"(x)); return y; }
DEVI float rcp(float x) { float y; asm("rcp.approx.ftz.f32 %0, %1;" : "=f"(y) : "f"(x)); return y; }
DEVI float sqrt_a(float x) { float y; asm("sqrt.approx.ftz.f32 %0, %1;" : "=f"(y) : "f"(x)); return y; }
DEVI void ldsm4t(uint32_t* r, uint32_t a) {
  asm volatile("ldmatrix.sync.aligned.m8n8.x4.trans.shared.b16 {%0,%1,%2,%3}, [%4];"
               : "=r"(r[0]), "=r"(r[1]), "=r"(r[2]), "=r"(r[3]) : "r"(a) : "memory");
}
DEVI void ldsm4(uint32_t* r, uint32_t a) {
  asm volatile("ldmatrix.sync.aligned.m8n8.x4.shared.b16 {%0,%1,%2,%3}, [%4];"
               : "=r"(r[0]), "=r"(r[1]), "=r"(r[2]), "=r"(r[3]) : "r"(a) : "memory");
}
DEVI uint32_t lds16(uint32_t a) {
  uint32_t v;
  asm volatile("ld.shared.u16 %0, [%1];" : "=r"(v) : "r"(a) : "memory");
  return v;
}
DEVI void sts16(uint32_t a, uint32_t x) { asm volatile("st.shared.u16 [%0], %1;" ::"r"(a), "r"(x) : "memory"); }
DEVI uint4 ldg128(const void* p) {
  uint4 v;
  asm volatile("ld.global.nc.v4.u32 {%0,%1,%2,%3}, [%4];" : "=r"(v.x), "=r"(v.y), "=r"(v.z), "=r"(v.w) : "l"(p));
  return v;
}
DEVI uint2 ldg64(const void* p) {
  uint2 v;
  asm volatile("ld.global.nc.v2.u32 {%0,%1}, [%2];" : "=r"(v.x), "=r"(v.y) : "l"(p));
  return v;
}
DEVI uint32_t ldg32(const void* p) {
  uint32_t v;
  asm volatile("ld.global.nc.u32 %0, [%1];" : "=r"(v) : "l"(p));
  return v;
}
DEVI uint4 ldcg128(const void* p) {
  uint4 v;
  asm volatile("ld.global.cg.v4.u32 {%0,%1,%2,%3}, [%4];" : "=r"(v.x), "=r"(v.y), "=r"(v.z), "=r"(v.w) : "l"(p) : "memory");
  return v;
}
DEVI uint2 ldcg64(const void* p) {
  uint2 v;
  asm volatile("ld.global.cg.v2.u32 {%0,%1}, [%2];" : "=r"(v.x), "=r"(v.y) : "l"(p) : "memory");
  return v;
}
DEVI uint32_t ldcg32(const void* p) {
  uint32_t v;
  asm volatile("ld.global.cg.u32 %0, [%1];" : "=r"(v) : "l"(p) : "memory");
  return v;
}
DEVI void stg128(void* p, uint32_t a, uint32_t b, uint32_t c, uint32_t d) {
  asm volatile("st.global.v4.u32 [%0], {%1,%2,%3,%4};" ::"l"(p), "r"(a), "r"(b), "r"(c), "r"(d) : "memory");
}
DEVI void stg32(void* p, uint32_t a) { asm volatile("st.global.u32 [%0], %1;" ::"l"(p), "r"(a) : "memory"); }
DEVI uint4 lds128(uint32_t a) {
  uint4 v;
  asm volatile("ld.shared.v4.u32 {%0,%1,%2,%3}, [%4];" : "=r"(v.x), "=r"(v.y), "=r"(v.z), "=r"(v.w) : "r"(a) : "memory");
  return v;
}
DEVI uint2 lds64(uint32_t a) {
  uint2 v;
  asm volatile("ld.shared.v2.u32 {%0,%1}, [%2];" : "=r"(v.x), "=r"(v.y) : "r"(a) : "memory");
  return v;
}
DEVI uint32_t lds32(uint32_t a) {
  uint32_t v;
  asm volatile("ld.shared.u32 %0, [%1];" : "=r"(v) : "r"(a) : "memory");
  return v;
}
DEVI void lds64f_if(bool p, float& a, float& b, uint32_t addr) {
  asm volatile("{\n.reg .pred p;\nsetp.ne.u32 p, %3, 0;\n@p ld.shared.v2.f32 {%0,%1}, [%2];\n}\n"
               : "+f"(a), "+f"(b) : "r"(addr), "r"((uint32_t)p) : "memory");
}
DEVI float ldsf(uint32_t a) { return __uint_as_float(lds32(a)); }
DEVI void sts128(uint32_t a, uint32_t x, uint32_t y, uint32_t z, uint32_t w) {
  asm volatile("st.shared.v4.u32 [%0], {%1,%2,%3,%4};" ::"r"(a), "r"(x), "r"(y), "r"(z), "r"(w) : "memory");
}
DEVI void sts64(uint32_t a, uint32_t x, uint32_t y) { asm volatile("st.shared.v2.u32 [%0], {%1,%2};" ::"r"(a), "r"(x), "r"(y) : "memory"); }
DEVI void sts32(uint32_t a, uint32_t x) { asm volatile("st.shared.u32 [%0], %1;" ::"r"(a), "r"(x) : "memory"); }
DEVI void stsf(uint32_t a, float x) { sts32(a, __float_as_uint(x)); }
DEVI uint32_t packbf(float lo, float hi) {
  uint32_t r;
  asm("cvt.rn.bf16x2.f32 %0, %1, %2;" : "=r"(r) : "f"(hi), "f"(lo));
  return r;
}
DEVI uint32_t nz(uint32_t w) { uint32_t y; asm("max.u32 %0, %1, 1;" : "=r"(y) : "r"(w)); return y; }
DEVI float blo(uint32_t w) { return __uint_as_float(w << 16); }
DEVI float bhi(uint32_t w) { return __uint_as_float(w & 0xffff0000u); }
DEVI float rbf(float x) { return __uint_as_float(packbf(0.f, x)); }
DEVI float shx(float v, int m) { return __shfl_xor_sync(0xffffffffu, v, m); }
DEVI float quad_sum(float v) { v += shx(v, 1); v += shx(v, 2); return v; }
DEVI uint32_t movm(uint32_t a) {
  uint32_t d;
  asm volatile("movmatrix.sync.aligned.m8n8.trans.b16 %0, %1;" : "=r"(d) : "r"(a));
  return d;
}
DEVI void mma16(float* d, uint32_t a0, uint32_t a1, uint32_t a2, uint32_t a3, uint32_t b0, uint32_t b1) {
  asm("mma.sync.aligned.m16n8k16.row.col.f32.bf16.bf16.f32 {%0,%1,%2,%3},{%4,%5,%6,%7},{%8,%9},{%0,%1,%2,%3};"
      : "+f"(d[0]), "+f"(d[1]), "+f"(d[2]), "+f"(d[3])
      : "r"(a0), "r"(a1), "r"(a2), "r"(a3), "r"(b0), "r"(b1));
}
DEVI void mma8z(float* d, uint32_t a0, uint32_t a1, uint32_t b0) {
  asm("mma.sync.aligned.m16n8k8.row.col.f32.bf16.bf16.f32 {%0,%1,%2,%3},{%4,%5},{%6},{%7,%7,%7,%7};"
      : "=f"(d[0]), "=f"(d[1]), "=f"(d[2]), "=f"(d[3])
      : "r"(a0), "r"(a1), "r"(b0), "f"(0.f));
}
DEVI void mma8(float* d, uint32_t a0, uint32_t a1, uint32_t b0) {
  asm("mma.sync.aligned.m16n8k8.row.col.f32.bf16.bf16.f32 {%0,%1,%2,%3},{%4,%5},{%6},{%0,%1,%2,%3};"
      : "+f"(d[0]), "+f"(d[1]), "+f"(d[2]), "+f"(d[3])
      : "r"(a0), "r"(a1), "r"(b0));
}
DEVI void mma16z(float* d, uint32_t a0, uint32_t a1, uint32_t a2, uint32_t a3, uint32_t b0, uint32_t b1) {
  asm("mma.sync.aligned.m16n8k16.row.col.f32.bf16.bf16.f32 {%0,%1,%2,%3},{%4,%5,%6,%7},{%8,%9},{%10,%10,%10,%10};"
      : "=f"(d[0]), "=f"(d[1]), "=f"(d[2]), "=f"(d[3])
      : "r"(a0), "r"(a1), "r"(a2), "r"(a3), "r"(b0), "r"(b1), "f"(0.f));
}
DEVI void mma16a(float* d, const uint32_t* a, uint32_t b0, uint32_t b1) { mma16(d, a[0], a[1], a[2], a[3], b0, b1); }
DEVI float ln_sd(float var) { return rbf(sqrt_a(rbf(rbf(var) + kEps))); }
DEVI int fkey(float f) { int i = __float_as_int(f); return i ^ ((i >> 31) & 0x7fffffff); }
DEVI float sigmoidf(float x) { return rcp(1.f + ex2(-1.4426950408889634f * x)); }

DEVI uint32_t probe_stage(uint32_t pa) { return lds32(pa); }
DEVI void check_stage(uint32_t pv, uint32_t fa, const uint8_t* src) {
  if (__any_sync(0xffffffffu, pv == 0)) {
    uint32_t n = 0, tid;
    asm volatile("mov.u32 %0, %%tid.x;" : "=r"(tid));
    const uint32_t fo = (tid & 96) * 8 + (tid & 16) * 64 + (tid & 15) * 16;
    fa += fo; src += fo;
#pragma unroll 1
    for (uint32_t o = 0; o < 8192;) {
      const uint4 v = ld_msg(src + o);
      sts128(fa + o, v.x, v.y, v.z, v.w);
      if (!__any_sync(0xffffffffu, min(min(v.x, v.y), min(v.z, v.w)) == 0) || ++n > (1u << 16)) o += 2048;
    }
    fence_async_smem();
    __syncwarp();
  }
}

struct Params {
  const uint8_t *x, *wqkv, *wo, *wr, *wg, *wu, *wd;
  uint8_t* out;
  Scratch* g;
};

struct Maps { CUtensorMap wq, x, wo, xr, wg, wu, out; };
#define QPRE 2
#define FDEPTH 2
#define PFSTART 700
#define PFPRE 0
#define PFPER 3
#define PFNS 200
#define XSTART 100
#define XSTEP 300
#define PKSTEP 350
#define WPOLL 300
#define CSROUND 0
#define XLROUND 0
#define CLNS 20
#define FSTART 4000
#define XLSTART 3000
#define WGAP0 0
#define XGAP 150
#define WEARLY 1

__global__ void __cluster_dims__(2, 1, 1) __launch_bounds__(512, 1) fused_kernel(const Params p, const __grid_constant__ Maps tm) {
  extern __shared__ __align__(1024) uint8_t smem_raw[];
  constexpr uint32_t sbd = 1024;
  int cta;
  uint32_t rank;
  {
    asm volatile("mov.u32 %0, %%cluster_ctarank;" : "=r"(rank));
    const int c = blockIdx.x >> 1, t = c - 4, u = c - 36, uq = (u * 37) >> 8;
    const int gpc = c < 4 ? 0 : c < 36 ? t & 7 : 1 + u - 7 * uq, idx = c < 4 ? 4 + c : c < 36 ? t >> 3 : 4 + uq;
    cta = __shfl_sync(0xffffffffu, (2 * gpc + (int)rank) * 8 + idx, 0);
  }
  const uint32_t sb = sbd | (rank << 24);
  if ((uint32_t)__cvta_generic_to_shared(smem_raw) != sb) return;
  if (threadIdx.x < 27) asm volatile("prefetch.global.L2 [%0];" ::"l"(p.wqkv + blockIdx.x * 3456 + threadIdx.x * 128));
  const int m = cta >> 3, r = cta & 7;
  const int warp = __shfl_sync(0xffffffffu, (int)(threadIdx.x >> 5), 0);
  const int lane = threadIdx.x & 31;
  uint8_t* const gb = reinterpret_cast<uint8_t*>(p.g);
  auto pack = [&]() -> uint32_t {
    const uint32_t t0 = clock();
    const uint32_t tp = sb + SM_WD + warp * 2304, bar = sb + SM_PART + 8 * warp;
    uint8_t* flag = GA(flagP, (12 * r + warp) * 128 + 4 * m);
    if (warp > 1) {
      asm volatile("bar.sync 4, 512;" ::: "memory");
      cluster_arrive();
      while ((uint32_t)clock() - t0 < (warp - 1) * PKSTEP) {}
    }
    if (elect()) {
      mbar_init(bar, 1);
      asm volatile("fence.mbarrier_init.release.cluster;" ::: "memory");
      mbar_expect(bar, 2304);
      if (warp < 9) tma3(tp, &tm.wq, 72 * r, 64 * warp + 8 * (m >> 1), m & 1, bar);
      else tma2(tp, &tm.wo, 72 * r, 192 * (warp - 9) + 24 * (m >> 1) + 8 * (m & 1), bar);
    }
    __syncwarp();
    if (lane == 0) st_rlx(flag, 0);
    if (warp <= 1) { asm volatile("bar.sync 4, 512;" ::: "memory"); cluster_arrive(); }
    mbar_wait(sb + B_EP, 0);
    const uint32_t epoch = lds32(sb + SM_EP);
    uint8_t* dst = GC(wpack, (r * 12 + warp) * WSTAGE + (27 * (m >> 1) + 14 * (m & 1)) * 128 + lane * 16);
    mbar_wait(bar, 0);
#pragma unroll
    for (int i = 0; i < 4; i++) {
      const int u = 4 * i + (lane >> 3) + 5 * (m & 1);
      const uint4 x = lds128(tp + (lane & 7) * 144 + u * 16 + (u >= 9 ? 1008 : 0));
      if (u < 14 + 4 * (m & 1)) stg128(dst + 512 * i, nz(x.x), nz(x.y), nz(x.z), nz(x.w));
    }
    if (lane == 0) st_rlx(flag, epoch);
    fence_async_smem();
    __syncwarp();
    if (elect()) asm volatile("mbarrier.inval.shared::cta.b64 [%0];" ::"r"(bar) : "memory");
    cluster_wait();
    return epoch;
  };

  if (warp >= 12) {
    asm volatile("setmaxnreg.dec.sync.aligned.u32 24;");
    uint32_t e0 = 0;
    if (elect()) {
#pragma unroll
      for (int i = 0; i < NBAR; i++)
        if (warp - 12 == (i * 4) / NBAR)
          mbar_init(sb + SM_BAR + 8 * i, i < 4 ? 1 : i < 8 ? 16 : i < 16 ? 2 : i < NBAR4 ? 4 : 1);
      asm volatile("fence.mbarrier_init.release.cluster;" ::: "memory");
    }
    __syncwarp();
    if (warp == 15) asm volatile("bar.arrive 4, 512;" ::: "memory");
    else asm volatile("bar.sync 4, 512;" ::: "memory");
    cluster_arrive();
    if (warp == 15) e0 = ld_rlx(GA(epoch, 32 * cta));
    if (warp == 12) {
      mbar_wait(sb + B_EP, 0);
      cluster_wait();
      const uint32_t epoch = lds32(sb + SM_EP);
      const uint32_t half = (m & 1) * (WSTAGE / 2);
      const uint8_t* src = GC(wpack, r * 12 * WSTAGE + half);
      __nanosleep(WPOLL);
#pragma unroll 1
      for (int g = 0; g < 24; g++) {
        const uint32_t slot = g & 3;
        if (g < 12) wait_flags(GA(flagP, (12 * r + g) * 128), lane & 15, epoch);
        if (g == 0) TRL(3, 0);
        if (g >= 4) mbar_wait(sb + B_WEMPTY + 8 * slot, ((g >> 2) - 1) & 1);
        if (elect()) {
          const uint32_t bar = sb + (g < 12 ? B_WL : B_WFULL) + 8 * slot;
          mbar_expect(bar, WSTAGE);
          bulk_g2s_pair(sb + SM_W + slot * WSTAGE + half, src + (g >= 12 ? g - 12 : g) * WSTAGE, WSTAGE / 2, bar);
        }
      }
    } else if (warp <= 14) {
      const int w = warp - 13;
      const uint32_t full = sb + B_XFULL + 32 * w, empty = sb + B_XEMPTY + 32 * w, ring = sb + SM_X + w * 4 * XSTAGE;
      mbar_wait(sb + B_EP, 0);
      cluster_wait();
      const uint32_t epoch = lds32(sb + SM_EP);
      if (lane < 4) st_rlx(GA(flagX, 128 * (2 * m + w) + 16 * r + 4 * lane), epoch * 4);
#pragma unroll 1
      for (int gemm = 0; gemm < 4; gemm++) {
        const uint8_t* src = GC(act, (gemm - 1) * ACT + (2 * m + w) * 73728);
        if (gemm & 1) {
          mbar_wait(empty, 0);
          if (elect()) {
            mbar_expect(sb + B_RES + 8 * w, 9216);
            if (gemm == 1) tma3(ring, &tm.xr, 72 * r, w, m * 64, sb + B_RES + 8 * w);
            else bulk_g2s(ring, GC(act, ACT + (2 * m + w) * 73728 + r * 9216), 9216, sb + B_RES + 8 * w);
          }
        }
        if (gemm > 0) {
          mbar_wait(gemm & 1 ? sb + B_RC + 8 * w : empty, gemm & 1 ? gemm >> 1 : 1);
          TRL(3, 11 + w * 4 + gemm);
          wait_flags(GA(flagX, 128 * (2 * m + w)), lane, epoch * 4 + gemm);
          TRL(3, 1 + w * 4 + gemm);
        }
        if (gemm & 1) {
          if (elect()) {
#pragma unroll
            for (int s = 0; s < 9; s++) {
              if (s >= 4) mbar_wait(empty + 8 * (s & 3), s == 4);
              mbar_expect(full + 8 * (s & 3), XSTAGE);
              bulk_g2s(ring + (s & 3) * XSTAGE, src + s * XSTAGE, XSTAGE, full + 8 * (s & 3));
              mbar_arrive(full + 8 * (s & 3));
            }
          }
          __syncwarp();
          continue;
        }
        bool gate = gemm == 2;
#pragma unroll 1
        for (int s = 0; s < (gemm == 2 ? 11 : 9); s++) {
          const uint32_t slot = s & 3;
          if (gemm == 0 && s < 4) __nanosleep(s ? XSTEP : XSTART);
          if (gemm == 2 && s > 0 && s < 4) __nanosleep(XGAP);
          if (s >= 4) mbar_wait(empty + 8 * slot, s >> 3);
          const bool hold = gate && s >= 4 && mbar_test(sb + B_WANT, 0);
          if (lane == 0 && !hold && (gemm != 2 || (s & ~1) != 2)) mbar_arrive(full + 8 * (gemm == 2 && s >= 4 ? (s - 2) & 3 : slot));
          if (s < 9 && elect()) {
            mbar_expect(full + 8 * slot, XSTAGE);
            if (gemm == 0) tma3(ring + slot * XSTAGE, &tm.x, s * 64, w, m * 64, full + 8 * slot);
            else bulk_g2s(ring + slot * XSTAGE, src + s * XSTAGE, XSTAGE, full + 8 * slot);
          }
          if (hold) {
            mbar_wait(sb + B_DONE, 0);
            gate = false;
            if (lane == 0) mbar_arrive(full + 8 * ((s - 2) & 3));
          }
        }
      }
    } else {
      const uint32_t epoch = e0 + 1;
      if (lane == 0) {
        sts32(sb + SM_EP, epoch);
        mbar_arrive(sb + B_EP);
      }
      __syncwarp();
      cluster_wait();
      int pi = lane;
      auto prefetch = [&]() {
        const uint8_t* pp = pi < 648 ? ((cta & 1) ? p.wu : p.wg) + (uint32_t)(((pi / 72) * 63 + (cta >> 1)) * 9216 + pi * 128)
                                     : p.wd + (uint32_t)((cta * 324 + pi - 648) * 128);
        if (pi < 972 && !(ABL & 2)) asm volatile("prefetch.global.L2 [%0];" ::"l"(pp));
        pi += 32;
      };
      __nanosleep(PFSTART);
#pragma unroll 1
      for (int i = 0; i < PFPRE; i++) { prefetch(); __nanosleep(PFNS); }
      uint32_t ph = 0;
#pragma unroll 1
      for (int g = 0; g < 12; g++) {
        const uint32_t slot = g & 3;
#pragma unroll 1
        for (int n = 0; n < 4096; n++) {
          mbar_wait(sb + B_WL + 8 * slot, (ph >> slot) & 1);
          ph ^= 1 << slot;
          const uint32_t a = sb + SM_W + slot * WSTAGE + lane * 128 + (lane & 3) * 32 + (lane >> 2) * 4;
          uint32_t mn = lds32(a + (lane < 24 ? 6 * 4096 : 0));
#pragma unroll
          for (int u = 0; u < 6; u++) mn = min(mn, lds32(a + u * 4096));
          if (!__any_sync(0xffffffffu, mn == 0) || (ABL & 32)) break;
          fence_async_smem();
          __syncwarp();
          if (elect()) {
            mbar_expect(sb + B_WL + 8 * slot, WSTAGE);
            bulk_g2s(sb + SM_W + slot * WSTAGE, GC(wpack, (r * 12 + g) * WSTAGE), WSTAGE, sb + B_WL + 8 * slot);
          }
        }
        if (lane == 0) mbar_arrive(sb + B_WFULL + 8 * slot);
#pragma unroll 1
        for (int i = 0; i < PFPER; i++) prefetch();
      }
      TRL(3, 22);
      mbar_wait(sb + B_FD, 0);
      TRL(3, 20);
      if (elect()) {
        mbar_expect(sb + B_WD, (ABL & 64) ? 0 : 41472);
#pragma unroll 4
        for (int i = 0; i < 36; i++)
          if (!(ABL & 64)) bulk_g2s(sb + SM_WD + i * WDP, p.wd + (uint32_t)(cta * 36 + i) * 1152u, 1152, sb + B_WD);
      }
      __syncwarp();
      TRL(3, 21);
      {
        const uint32_t epoch = e0, h = (lane >> 1) * 128 + (lane & 1) * 16;
        mbar_wait(sb + B_OS, 0);
#pragma unroll 1
        for (int i = cta; i < 1296; i += 128) { stg128(GC(wpack, i * 2048 + (lane & 6) * 16 + h), 0, 0, 0, 0); __nanosleep(CLNS); }
#pragma unroll 1
        for (int i = 0; i < 5; i++) {
          stg128(GC(halo, (cta * 5 + i) * 2048 + h), 0, 0, 0, 0);
          if (i < 4 || lane < 16) stg128(GC(candrow, cta * 2304 + i * 512 + lane * 16), 0, 0, 0, 0);
          stg128(GC(act, (cta * 27 + i) * 2048 + 96 + h), 0, 0, 0, 0);
          __nanosleep(CLNS);
        }
        mbar_wait(sb + B_OS, 1);
#pragma unroll 1
        for (int i = 5; i < 27; i++) { stg128(GC(act, (cta * 27 + i) * 2048 + 96 + h), 0, 0, 0, 0); __nanosleep(CLNS); }
      }
      TRL(3, 23);
    }
  } else if (warp >= 8) {
    asm volatile("setmaxnreg.inc.sync.aligned.u32 200;");
    const int sw = warp - 8, s = threadIdx.x - 256;
    const uint32_t t0 = clock();
    const uint32_t epoch = pack();
    TR(2, 0);
    auto ffn_round = [&](int u) {
      const uint32_t bar = sb + B_FF + 8 * (u % FDEPTH), dst = sb + SM_WD + (u % FDEPTH) * FSLOT;
      if (ABL & 4) { mbar_arrive(bar); return; }
      mbar_expect(bar, 12288);
      tma2(dst, &tm.wg, ((cta * 72) >> 5) << 4, 64 * u, bar);
      tma2(dst + FSLOT / 2, &tm.wu, ((cta * 72) >> 5) << 4, 64 * u, bar);
    };
    const int xi = 8 * r + 4 * (sw >> 1) + (lane >> 3);
    uint4 xv[9];
    uint32_t wr[9];
        {
          const uint8_t* xsrc = p.x + (uint32_t)((128 * m + 2 * xi + (sw & 1)) * 1152 + (lane & 7) * 16);
#pragma unroll
          for (int u = 0; u < 9; u++) xv[u] = ldg128(xsrc + u * 128);
#pragma unroll
          for (int u = 0; u < 9; u++) wr[u] = sw == 0 ? ldg32(p.wr + 128 * u + 4 * lane) : 0u;
        }
    {
      asm volatile("bar.sync 15, 384;" ::: "memory");
      const int u = (s >> 3) + 5 * (m & 1);
      uint4 v[9];
#pragma unroll
      for (int g = 0; g < 9; g++) v[g] = lds128(sb + SM_WD + g * 2304 + u * 16 + (u >= 9 ? 1008 : 0) + (s & 7) * 144);
      fence_async_smem();
      bar_sync(3);
      float a[8] = {};
#pragma unroll
      for (int g = 0; g < 9; g++) {
        a[0] += blo(v[g].x); a[1] += bhi(v[g].x); a[2] += blo(v[g].y); a[3] += bhi(v[g].y);
        a[4] += blo(v[g].z); a[5] += bhi(v[g].z); a[6] += blo(v[g].w); a[7] += bhi(v[g].w);
      }
      const bool b4 = s & 4, b2 = s & 2;
      float b[4];
#pragma unroll
      for (int e = 0; e < 4; e++) b[e] = (b4 ? a[4 + e] : a[e]) + shx(b4 ? a[e] : a[4 + e], 4);
      float c0 = (b2 ? b[2] : b[0]) + shx(b2 ? b[0] : b[2], 2), c1 = (b2 ? b[3] : b[1]) + shx(b2 ? b[1] : b[3], 2);
      c0 += shx(c0, 1); c1 += shx(c1, 1);
      if (!(s & 1) && (s >> 3) < 14 - (m & 1))
        st_rlx2(GA(colpart, (8 * r + (m >> 1)) * 864 + 14 * (m & 1) * 32 + 4 * s), __float_as_uint(c0), (__float_as_uint(c1) & ~15u) | (epoch & 15));
      TR(2, 1);
    }
    if (sw == 0) {
      while ((uint32_t)clock() - t0 < FSTART) {}
      if (elect()) {
#pragma unroll
        for (int u = 0; u < FDEPTH; u++) ffn_round(u);
      }
      __syncwarp();
    }
        {
          float sum = 0.f;
#pragma unroll
          for (int u = 0; u < 9; u++)
            sum += (blo(xv[u].x) + bhi(xv[u].x)) + (blo(xv[u].y) + bhi(xv[u].y)) + (blo(xv[u].z) + bhi(xv[u].z)) + (blo(xv[u].w) + bhi(xv[u].w));
          sum += shx(sum, 1); sum += shx(sum, 2); sum += shx(sum, 4);
          const float mu = sum * (1.f / kD);
          float q = 0.f;
#pragma unroll
          for (int u = 0; u < 9; u++) {
            const uint32_t ww[4] = {xv[u].x, xv[u].y, xv[u].z, xv[u].w};
#pragma unroll
            for (int e = 0; e < 4; e++) {
              const float d0 = blo(ww[e]) - mu, d1 = bhi(ww[e]) - mu;
              q = fmaf(d0, d0, q); q = fmaf(d1, d1, q);
            }
          }
          q += shx(q, 1); q += shx(q, 2); q += shx(q, 4);
          const float rho = rcp(ln_sd(q * (1.f / kD)));
          if ((lane & 7) == 0) st_msg(GA(stats0, 16 * (128 * m + 64 * (sw & 1) + xi)), __float_as_uint(rho), __float_as_uint(mu), 0, epoch);
          if (sw == 0) {
            float wsum = 0.f;
#pragma unroll
            for (int u = 0; u < 9; u++) wsum += blo(wr[u]) + bhi(wr[u]);
#pragma unroll
            for (int o = 1; o < 32; o <<= 1) wsum += shx(wsum, o);
            if (lane == 0) stsf(sb + SM_WSUM, wsum);
          }
          TR(2, 3);
        }
    uint32_t WF[9][4][4];
    {
      const int g = lane >> 2, t = lane & 3;
      const uint32_t c0 = (cta * 72) & 31, ra = 2 * (lane & 6) + (lane & 1) + 2 * ((lane >> 4) ^ ((lane >> 2) & 1));
      const uint32_t fa = sb + SM_WD + (16 * sw + ra) * 128 + ((((c0 + 8) >> 4) + ((lane >> 3) & 1)) << 4);
      const uint32_t fa0 = fa ^ ((ra & 7) << 4), fa1 = (fa + 32) ^ ((ra & 7) << 4);
      const uint32_t rl = 2 * (g & 6) + (g & 1) + 2 * (g >> 2);
      const uint32_t fl = sb + SM_WD + 16 * sw * 128 + (t >> 1) * (FSLOT / 2) + c0 + 64 * (~cta & 1) + 4 * (t & 1);
      const uint32_t fl0 = (fl + rl * 128) ^ ((rl & 7) << 4), fl1 = (fl + (rl ^ 2) * 128) ^ (((rl ^ 2) & 7) << 4);
#pragma unroll
      for (int i = 0; i < 9; i++) {
        mbar_wait(sb + B_FF + 8 * (i % FDEPTH), (i / FDEPTH) & 1);
#pragma unroll
        for (int e = 0; e < 4; e++) ldsm4t(WF[i][e], ((e & 1) ? fa1 : fa0) + (e >> 1) * (FSLOT / 2) + (i % FDEPTH) * FSLOT);
        const uint32_t v0 = lds32(fl0 + (i % FDEPTH) * FSLOT), v1 = lds32(fl1 + (i % FDEPTH) * FSLOT);
        if (i + FDEPTH < 9 || i == 8) {
          fence_async_smem();
          bar_sync(3);
          if (sw == 0 && elect()) {
            if (i < 8) ffn_round(i + FDEPTH);
            else mbar_arrive(sb + B_FD);
          }
        }
        sts64(sb + SM_LEFT + i * 1024 + s * 8, movm(v0), movm(v1));
        if (i == CSROUND) {
          TR(2, 21);
          float c0, c1;
          uint4 s0;
          uint32_t nc = 0;
          _Pragma("unroll 1") while (true) {
            s0 = ld_msg(GA(stats0, 16 * (128 * m + s)));
            uint32_t bad = s0.w != epoch;
            c0 = 0.f; c1 = 0.f;
#pragma unroll
            for (int mm = 0; mm < 8; mm++) {
              const uint2 v = ld_rlx2(GA(colpart, 8 * 864 * r + 8 * min(s, 107)) + mm * 864);
              c0 += __uint_as_float(v.x); c1 += __uint_as_float(v.y & ~15u);
              bad |= v.y ^ epoch;
            }
            if (!__any_sync(0xffffffffu, bad & 15)) break;
            spin_guard(nc);
          }
          if (s < 108) {
            const uint32_t hi = packbf(c0, c1);
            sts32(sb + SM_COLSUM + 32 * (s >> 2) + 4 * (s & 3), hi);
            sts32(sb + SM_COLSUM + 32 * (s >> 2) + 4 * (s & 3) + 16, packbf(c0 - blo(hi), c1 - bhi(hi)));
          }
          sts32(sb + SM_ROWC + 4 * s, s0.x);
          sts64(sb + SM_ROWM + 8 * s, s0.y, __float_as_uint(1.f));
          fence_async_smem();
          __syncwarp();
          if (lane == 0) mbar_arrive(sb + B_COLSUM);
          TR(2, 13);
        }
      }
      TR(2, 4);
    }
    {
      const uint32_t y = epoch * 2 - 1;
      st_msg(GA(ypart, (s >> 1) * 4096 + cta * 32 + (s & 1) * 16), y, y, y, y);
      if (s < 16) {
        st_msg(GA(ypart, (64 + (s >> 1)) * 4096 + cta * 32 + (s & 1) * 16), y, y, y, y);
        st_rlx(GA(fixmsg, 1024 * r + 64 * m + 4 * s), epoch - 1);
      }
      if (s < 64 && cta < 72) st_rlx(GA(x2msg, (s >> 3) * 2304 + 32 * cta + 4 * (s & 7)), epoch - 1);
    }
#pragma unroll 1
    for (int L = 0; L < 2; L++) {
      const uint32_t tag = epoch * 2 + L;
      int s0 = __shfl_sync(0xffffffffu, (int)threadIdx.x + L, threadIdx.x & 31) - L - 256;
#define RELANE asm volatile("" : "+r"(s0)); const int s = s0, lane = s & 31, g = lane >> 2, t = lane & 3; (void)g; (void)t
      RELANE;
      const uint8_t* crow = GC(candrow, L * 128 * 1152);
      const uint8_t* cptr = GA(cand, (8 * L + r) * 2048 + 16 * s);
      asm volatile("" : "+l"(crow), "+l"(cptr));
      mbar_wait2(sb + B_WD, 0, sb + B_EPI, L);
      uint32_t win;
      {
        uint32_t c, n = 0;
        _Pragma("unroll 1") while (true) {
          c = ld_rlx(cptr) ^ (epoch & 0x7f);
          if (!__any_sync(0xffffffffu, c & 0x7f)) break;
          spin_guard(n);
        }
        const int wm = __reduce_max_sync(0xffffffffu, (int)(c | s));
        if (lane == 0) sts32(sb + SM_RED + 4 * sw, wm);
        bar_sync(3);
        const uint4 v = lds128(sb + SM_RED);
        win = max(max((int)v.x, (int)v.y), max((int)v.z, (int)v.w));
      }
      crow += (win & 127) * 1152;
      if (s == 0) {
        if (L == 0 && WEARLY) mbar_arrive(sb + B_WANT);
        sts32(sb + SM_SEL + 4 * L, win & 0x7ff);
        mbar_arrive(sb + B_IDX + 8 * L);
      }
      TR(2, 5 + 10 * L);
      uint2 xw[9];
      {
        if (sw < 3) {
          uint4 v;
          uint32_t n = 0;
          _Pragma("unroll 1") while (true) {
            v = ld_msg(crow + 16 * min(s, 71));
            if (!__any_sync(0xffffffffu, min(min(v.x, v.y), min(v.z, v.w)) == 0)) break;
            spin_guard(n);
          }
          if (s < 72) sts128(sb + SM_PART + 16 * s, v.x, v.y, v.z, v.w);
        }
        bar_sync(3);
#pragma unroll
        for (int i = 0; i < 9; i++) xw[i] = lds64(sb + SM_PART + 128 * i + 32 * sw + 8 * t);
      }
      if (L == 0 && !WEARLY && s == 0) mbar_arrive(sb + B_WANT);
      TR(2, 6 + 10 * L);
      {
        float a[4][4] = {}, al[4] = {};
#pragma unroll
        for (int i = 0; i < 9; i++) {
          const uint2 wl = lds64(sb + SM_LEFT + s * 8 + i * 1024);
#pragma unroll
          for (int e = 0; e < 4; e++) mma16a(a[e], WF[i][e], xw[i].x, xw[i].y);
          mma8(al, wl.x, wl.y, (g & 1) ? xw[i].y : xw[i].x);
        }
        bar_sync(3);
        const uint32_t pp = sb + SM_PART + ((t >> 1) * 36 + 16 * (t & 1) + g + 4 * (cta & 1)) * 16 + 4 * sw;
        stsf(pp, selp(t & 2, selp(t & 1, a[3][0], a[2][0]), selp(t & 1, a[1][0], a[0][0])));
        stsf(pp + 128, selp(t & 2, selp(t & 1, a[3][2], a[2][2]), selp(t & 1, a[1][2], a[0][2])));
        stsf(sb + SM_PART + ((g >> 2) * 36 + 32 * (~cta & 1) + (g & 3)) * 16 + 4 * sw, al[0] + al[3]);
      }
      {
        RELANE;
        const uint32_t wa = sb + SM_WD + 288 * sw + ((lane >> 3) & 1) * 16 + ((lane & 7) + 8 * (lane >> 4)) * WDP;
        const uint32_t wb = sb + SM_WD + 288 * sw + ((lane >> 3) & 1) * 16 + (32 + (lane & 3)) * WDP;
        uint32_t f[4][4];
#pragma unroll
        for (int u = 0; u < 4; u++) ldsm4t(f[u], wa + 32 * (u & 1) + (u >> 1) * 16 * WDP);
        bar_sync(3);
        {
          float hv[2];
#pragma unroll
          for (int e = 0; e < 2; e++) {
            const uint32_t pp = sb + SM_PART + 16 * (e ? 32 + t : lane);
            const uint4 pg = lds128(pp), pu = lds128(pp + 576);
            const float gp = rbf((__uint_as_float(pg.x) + __uint_as_float(pg.y)) + (__uint_as_float(pg.z) + __uint_as_float(pg.w)));
            const float u = rbf((__uint_as_float(pu.x) + __uint_as_float(pu.y)) + (__uint_as_float(pu.z) + __uint_as_float(pu.w)));
            hv[e] = rbf(gp * sigmoidf(gp)) * u;
          }
          const uint32_t hh = packbf(hv[0], hv[1]);
          sts16(sb + SM_H + 80 * sw + 2 * lane, hh);
          sts16(sb + SM_H + 80 * sw + 64 + 2 * t, hh >> 16);
          __syncwarp();
        }
        TR(2, 7 + 10 * L);
        uint32_t hp[5];
#pragma unroll
        for (int i = 0; i < 4; i++) hp[i] = lds32(sb + SM_H + 80 * sw + 16 * i + 4 * t);
        hp[4] = lds32(sb + SM_H + 80 * sw + 64 + 4 * (t & 1));
        float Y[4] = {}, Z[4] = {}, C[4] = {};
        {
          uint32_t e0[4], e1[4], e2[4];
          const uint32_t wq = wb + 32 * (((lane >> 2) & 1) + 2 * (lane >> 4));
          ldsm4t(e0, wq); ldsm4t(e1, wq + 128); ldsm4t(e2, wb + 256);
          mma16a(Y, e0, g == (t >> 1) ? hp[4] : 0u, g == 2 + (t >> 1) ? hp[4] : 0u);
          mma16a(Z, e1, g == 4 + (t >> 1) ? hp[4] : 0u, g == 6 + (t >> 1) ? hp[4] : 0u);
          mma8(C, e2[0], e2[1], t < 2 ? hp[4] : 0u);
        }
#pragma unroll
        for (int u = 0; u < 4; u++) {
          const uint32_t wn = wa + 64 * (u + 1);
          const bool p0 = g == 2 * u, p1 = g == 2 * u + 1;
          mma16a(Y, f[0], p0 ? hp[0] : 0u, p0 ? hp[1] : 0u);
          mma16a(Z, f[1], p1 ? hp[0] : 0u, p1 ? hp[1] : 0u);
          ldsm4t(f[0], wn);
          if (u < 3) ldsm4t(f[1], wn + 32);
          mma16a(Y, f[2], p0 ? hp[2] : 0u, p0 ? hp[3] : 0u);
          mma16a(Z, f[3], p1 ? hp[2] : 0u, p1 ? hp[3] : 0u);
          ldsm4t(f[2], wn + 16 * WDP);
          if (u < 3) ldsm4t(f[3], wn + 32 + 16 * WDP);
        }
        mma16a(C, f[0], hp[0], hp[1]);
        mma16a(C, f[2], hp[2], hp[3]);
#pragma unroll
        for (int e = 0; e < 4; e++) Y[e] += Z[e];
        const uint32_t t4 = tag & 15;
        {
          uint8_t* yo = GA(ypart, (18 * sw + 4 * t) * 4096 + cta * 32 + 4 * g);
#pragma unroll
          for (int e = 0; e < 4; e++) st_rlx(yo + (2 * (e & 1) + (e >> 1)) * 4096, (__float_as_uint(Y[e]) & ~15u) | t4);
          if (t < 2) st_rlx(yo + (16 - 3 * t) * 4096, (__float_as_uint(t ? C[2] : C[0]) & ~15u) | t4);
          if (L == 0 && lane == 0) mbar_arrive(sb + B_DONE);
        }
      }
      TR(2, 8 + 10 * L);
      if (cta < 72) {
        RELANE;
        const uint32_t xn = ld_rlx(GC(candrow, (L * 128 + (win & 127)) * 1152 + 16 * cta + 2 * ((s & 6) ^ (2 * (cta & 1)))));
        const uint4 cm = ld_msg(GA(cand, (8 * L + r) * 2048 + 16 * (win & 127)));
        const uint8_t* yp = GA(ypart, cta * 4096 + s * 16);
        uint4 u0, u1;
        uint32_t n = 0;
        _Pragma("unroll 1") while (true) {
          u0 = ld_msg(yp);
          u1 = ld_msg(yp + 2048);
          const uint32_t t4 = tag & 15;
          u0.x ^= t4; u0.y ^= t4; u0.z ^= t4; u0.w ^= t4; u1.x ^= t4; u1.y ^= t4; u1.z ^= t4; u1.w ^= t4;
          if (!__any_sync(0xffffffffu, (u0.x | u0.y | u0.z | u0.w | u1.x | u1.y | u1.z | u1.w) & 15)) break;
          spin_guard(n);
        }
        const float a0 = __uint_as_float(u0.x) + __uint_as_float(u1.x), a1 = __uint_as_float(u0.y) + __uint_as_float(u1.y);
        const float a2 = __uint_as_float(u0.z) + __uint_as_float(u1.z), a3 = __uint_as_float(u0.w) + __uint_as_float(u1.w);
        const bool b4 = lane & 4, b2 = lane & 2;
        const float c0 = (b4 ? a2 : a0) + shx(b4 ? a0 : a2, 4), c1 = (b4 ? a3 : a1) + shx(b4 ? a1 : a3, 4);
        float d = (b2 ? c1 : c0) + shx(b2 ? c0 : c1, 2);
        d += shx(d, 8);
        if (!(lane & 8)) stsf(sb + SM_RED + 32 * (4 * (lane & 1) + ((lane >> 1) & 3)) + 8 * sw + 4 * (lane >> 4), d);
        bar_sync(3);
        if (s < 64) {
          const uint4 p0 = lds128(sb + SM_RED + 32 * (s & 7)), p1 = lds128(sb + SM_RED + 32 * (s & 7) + 16);
          const float y = rbf(((__uint_as_float(p0.x) + __uint_as_float(p0.y)) + (__uint_as_float(p0.z) + __uint_as_float(p0.w))) +
                              ((__uint_as_float(p1.x) + __uint_as_float(p1.y)) + (__uint_as_float(p1.z) + __uint_as_float(p1.w))));
          const uint32_t v = packbf(0.f, fmaf((s & 1) ? bhi(xn) : blo(xn), __uint_as_float(cm.z), __uint_as_float(cm.w)) + rbf(y * __uint_as_float(cm.y)));
          if (L == 0) st_rlx(GA(x2msg, (s >> 3) * 2304 + 32 * cta + 4 * (s & 7)), v | (epoch & 0xffff));
          const int tok = 128 * ((win >> 3) & 15) + 2 * (16 * (win & 3) + ((win >> 7) & 15)) + ((win >> 2) & 1);
          if (L == 1 && s < 8) *reinterpret_cast<uint16_t*>(p.out + (uint32_t)(tok * 1152 + 16 * cta + 2 * s)) = (uint16_t)(v >> 16);
        }
      }
      TR(2, 9 + 10 * L);
      if (L == 0 && m < 14) {
        RELANE;
        const int c = min(2 * m + ((s >> 3) & 1), 26);
        const uint8_t* wsrc = GC(wpack, r * 12 * WSTAGE + (s >> 4) * 3456 + c * 128 + (s & 7) * 16);
        const int k0 = 8 * (s >> 4) + (s & 7);
        uint4 wv[5];
#pragma unroll
        for (int i = 0; i < 5; i++) wv[i] = ldcg128(wsrc + i * WSTAGE);
        uint32_t xv[9];
        {
          uint32_t n = 0;
          _Pragma("unroll 1") while (true) {
            uint32_t bad = 0;
#pragma unroll
            for (int i = 0; i < 9; i++) { xv[i] = ld_rlx(GA(x2msg, r * 2304 + 4 * k0) + 256 * i); bad |= xv[i] ^ epoch; }
            if (!__any_sync(0xffffffffu, bad & 0xffff)) break;
            spin_guard(n);
          }
        }
        TR(2, 10);
        float a[8], z = 0.f;
#pragma unroll
        for (int e = 0; e < 8; e++) a[e] = 0.f;
#pragma unroll
        for (int i = 0; i < 9; i++) {
          const float xx = bhi(xv[i]);
          const uint4 w4 = wv[i % 5];
          if (i < 4) wv[i] = ldcg128(wsrc + (i + 5) * WSTAGE);
          z = fmaf(xx, (lane & 8) ? xx : 1.f, z);
          a[0] = fmaf(xx, blo(w4.x), a[0]); a[1] = fmaf(xx, bhi(w4.x), a[1]);
          a[2] = fmaf(xx, blo(w4.y), a[2]); a[3] = fmaf(xx, bhi(w4.y), a[3]);
          a[4] = fmaf(xx, blo(w4.z), a[4]); a[5] = fmaf(xx, bhi(w4.z), a[5]);
          a[6] = fmaf(xx, blo(w4.w), a[6]); a[7] = fmaf(xx, bhi(w4.w), a[7]);
        }
        const bool b4 = lane & 4, b2 = lane & 2, b1 = lane & 1;
        float b[4];
#pragma unroll
        for (int e = 0; e < 4; e++) b[e] = (b4 ? a[4 + e] : a[e]) + shx(b4 ? a[e] : a[4 + e], 4);
        z += shx(z, 4);
        const float c0 = (b2 ? b[2] : b[0]) + shx(b2 ? b[0] : b[2], 2);
        const float c1 = (b2 ? b[3] : b[1]) + shx(b2 ? b[1] : b[3], 2);
        z += shx(z, 2);
        float d = (b1 ? c1 : c0) + shx(b1 ? c0 : c1, 1);
        z += shx(z, 1);
        d += shx(d, 16);
        z += shx(z, 16);
        if (lane < 16) stsf(sb + SM_GEMV + 16 * lane + 4 * sw, d);
        if ((lane & 23) == 0) stsf(sb + SM_GEMV + 256 + 2 * lane + 4 * sw, z);
        bar_sync(3);
        if (s < 16) {
          const uint4 pd = lds128(sb + SM_GEMV + 16 * s), p1 = lds128(sb + SM_GEMV + 256), p2 = lds128(sb + SM_GEMV + 272);
          const float acc = (__uint_as_float(pd.x) + __uint_as_float(pd.y)) + (__uint_as_float(pd.z) + __uint_as_float(pd.w));
          const float m1 = ((__uint_as_float(p1.x) + __uint_as_float(p1.y)) + (__uint_as_float(p1.z) + __uint_as_float(p1.w))) * (1.f / kD);
          const float m2 = ((__uint_as_float(p2.x) + __uint_as_float(p2.y)) + (__uint_as_float(p2.z) + __uint_as_float(p2.w))) * (1.f / kD);
          const float cs = blo(lds16(sb + SM_COLSUM + 32 * c + 2 * (s & 7))) + blo(lds16(sb + SM_COLSUM + 32 * c + 2 * (s & 7) + 16));
          const float v = (acc - m1 * cs) * rcp(ln_sd(fmaxf(m2 - m1 * m1, 0.f)));
          st_rlx(GA(fixmsg, 1024 * r + 64 * m + 4 * s), __float_as_uint(rbf(v)) | (epoch & 0xffff));
        }
        TR(2, 11);
      }
      {
        if (L == 0 && (int)((win >> 3) & 15) == m) {
          RELANE;
          if (s < 72) {
            const uint8_t* fp = s < 54 ? GA(fixmsg, 1024 * r + 16 * s) : GA(x2msg, r * (2304 + 288) + 16 * (s - 54));
            uint4 v;
            uint32_t n = 0;
            _Pragma("unroll 1") while (true) {
              v = ld_msg(fp);
              if ((((v.x ^ epoch) | (v.y ^ epoch) | (v.z ^ epoch) | (v.w ^ epoch)) & 0xffff) == 0) break;
              spin_guard(n);
            }
            sts128(sb + SM_FIXQ + 16 * s, v.x & 0xffff0000u, v.y & 0xffff0000u, v.z & 0xffff0000u, v.w & 0xffff0000u);
          }
          __syncwarp();
          if (lane == 0) mbar_arrive(sb + B_FIX);
          TR(2, 12);
        }
      }
    }
    if (s == 0) st_rlx(GA(epoch, 32 * cta), epoch);
  } else {
    asm volatile("setmaxnreg.inc.sync.aligned.u32 144;");
    const int w = warp >> 2, j = warp & 3;
    const uint32_t xfull = sb + B_XFULL + 32 * w, xempty = sb + B_XEMPTY + 32 * w, xring = sb + SM_X + w * 4 * XSTAGE;
    if (threadIdx.x >= 128 && threadIdx.x < 188) { sts128(sb + SM_COLSUM + 16 * (threadIdx.x - 128), 0, 0, 0, 0); fence_async_smem(); }
    {
      const uint32_t epoch = pack();
      asm volatile("bar.arrive 15, 384;" ::: "memory");
      TRW(24);
      if (!(ABL & 8)) {
        if (lane < 16) st_msg(GA(statsP, (2 * m + w) * 8192 + r * 1024 + (16 * j + lane) * 16), 0, 0, 0, 0);
        if (lane < 2) st_msg(GA(cand, (8 * lane + r) * 2048 + 16 * (8 * m + warp)), ~epoch, 0, 0, 0);
        if (j == 3) {
#pragma unroll
          for (int u = 0; u < 10; u++) st_msg(GC(halo, (4 * cta + w) * 2560 + lane * 16) + (u / 5) * 5120 + (u % 5) * 512, 0, 0, 0, 0);
        }
        __syncwarp();
      }
      TRW(11);
    }
    const uint32_t mw = 2 * m + w, cid = 8 * m + warp;
    const uint32_t rowc = sb + SM_ROWC + 64 * warp, rowm = sb + SM_ROWM + 128 * warp;
#pragma unroll 1
    for (int L = 0; L < 2; L++) {
      int ln0 = __shfl_sync(0xffffffffu, lane + L, lane) - L;
#define RELANE2 asm volatile("" : "+r"(ln0)); const int ln = ln0, g = ln >> 2, t = ln & 3; \
      const uint32_t pa = xring + j * 256 + (ln & 7) * 1028 + ((ln >> 3) & 1) * 128 + 96; (void)pa
      uint32_t P[27][2], H[20];
      const uint8_t* hl;
      auto halo = [&]() {
#pragma unroll
        for (int u = 0; u < 5; u++) {
          const uint4 v = ld_gen(hl + u * 512);
          H[4 * u] = v.x; H[4 * u + 1] = v.y; H[4 * u + 2] = v.z; H[4 * u + 3] = v.w;
        }
      };
      {
        RELANE2;
        const uint32_t epoch = __shfl_sync(0xffffffffu, lds32(sb + SM_EP), 0);
        int selrow = -1;
        bool tgtwg = false;
        float d[108];
        uint32_t am[4];
        auto split_mean = [&](float m0, float m1) {
          const uint32_t h0 = packbf(m0, m0), h1 = packbf(m1, m1);
          const float l0 = m0 - bhi(h0), l1 = m1 - bhi(h1);
          am[0] = t ? 0u : h0; am[1] = t ? 0u : h1; am[2] = t ? 0u : packbf(l0, l0); am[3] = t ? 0u : packbf(l1, l1);
        };
        const uint32_t cdesc = mkdesc(sbd + SM_COLSUM, 0);
        am[0] = am[1] = am[2] = am[3] = 0;
        if (L == 1) split_mean(ldsf(rowm + 8 * g), ldsf(rowm + 8 * g + 64));
        asm volatile("wgmma.fence.sync.aligned;" ::: "memory");
        wgmma_n144_set(d + 36, am, cdesc + 18);
        wgmma_n72_set(d, am, cdesc);
        asm volatile("wgmma.commit_group.sync.aligned;" ::: "memory");
        const uint32_t adesc = mkdesc(sbd + SM_X + w * 4 * XSTAGE, 1024), ahi = L == 0 ? 0x40000040u : 8u, astep = L == 0 ? 2 : 128;
        const uint32_t bdesc = mkdesc(sbd + SM_W, 3456);
        const uint8_t* xsrc = GC(act, ACT + mw * 73728);
        mbar_wait2(sb + B_WFULL, L, xfull, 0);
        if (L == 1) check_stage(probe_stage(pa), xring, xsrc);
        TRW(0 + 12 * L);
#pragma unroll 1
        for (int s = 0; s < 7; s++) {
          TRQ(s + 9 * L);
          const uint32_t da = adesc + (s & 3) * (XSTAGE >> 4), db = bdesc + (s & 3) * (WSTAGE >> 4);
          const uint32_t nx = (s + 1) & 3, px = ((s + 1) >> 2) & 1;
          asm volatile("wgmma.fence.sync.aligned;" ::: "memory");
          wgmma_n72(d, da, ahi, db);
          wgmma_n144(d + 36, da, ahi, db + (1152 >> 4));
          wgmma_n72(d, da + astep, ahi, db + (6912 >> 4));
          asm volatile("wgmma.commit_group.sync.aligned;" ::: "memory");
          asm volatile("wgmma.wait_group.sync.aligned 1;" ::: "memory");
          if (s > 0 && ln == 0) {
            mbar_arrive_pair(sb + B_WEMPTY + 8 * ((s - 1) & 3));
            mbar_arrive(xempty + 8 * ((s - 1) & 3));
          }
          wgmma_n144(d + 36, da + astep, ahi, db + ((6912 + 1152) >> 4));
          wgmma_n72(d, da + 2 * astep, ahi, db + 2 * (6912 >> 4));
          uint32_t pv;
          const uint32_t dsc[6] = {da + 2 * astep, db + ((2 * 6912 + 1152) >> 4), da + 3 * astep, db + 3 * (6912 >> 4),
                                   da + 3 * astep, db + ((3 * 6912 + 1152) >> 4)};
          const uint32_t bar[4] = {sb + B_WFULL + 8 * nx, px ^ L, xfull + 8 * nx, px}, adr = pa + nx * XSTAGE;
          q_tail(d, &pv, ahi, dsc, bar, &adr);
          if (L == 1) check_stage(pv, xring + nx * XSTAGE, xsrc + (s + 1) * XSTAGE);
        }
        TRQ(7 + 9 * L);
        const uint32_t da7 = adesc + 3 * (XSTAGE >> 4), db7 = bdesc + 3 * (WSTAGE >> 4);
        asm volatile("wgmma.fence.sync.aligned;" ::: "memory");
        wgmma_n144(d + 36, da7, ahi, db7 + (1152 >> 4));
        wgmma_n144(d + 36, da7 + astep, ahi, db7 + ((6912 + 1152) >> 4));
        asm volatile("wgmma.commit_group.sync.aligned;" ::: "memory");
        asm volatile("wgmma.wait_group.sync.aligned 1;" ::: "memory");
        if (ln == 0) { mbar_arrive_pair(sb + B_WEMPTY + 16); mbar_arrive(xempty + 16); }
        {
          uint32_t v[2];
          const uint32_t dsc[4] = {da7 + 2 * astep, db7 + ((2 * 6912 + 1152) >> 4), da7 + 3 * astep, db7 + ((3 * 6912 + 1152) >> 4)};
          const uint32_t bar[6] = {sb + B_WFULL, (uint32_t)L, xfull, 0, sb + (L ? B_IDX : B_COLSUM), 0}, adr[2] = {pa, sb + SM_SEL + (ln >> 5)};
          kv_tail(d, v, ahi, dsc, bar, adr);
          if (L == 1) {
            if ((v[1] & 127) == cid) selrow = v[1] >> 7;
            tgtwg = ((v[1] & 127) >> 2) == (cid >> 2);
            check_stage(v[0], xring, xsrc + 8 * XSTAGE);
          }
        }
        TRQ(8 + 9 * L);
        const float m0 = ldsf(rowm + 8 * g), m1 = ldsf(rowm + 8 * g + 64);
        {
          uint32_t dsc[8];
#pragma unroll
          for (int kk = 0; kk < 4; kk++) { dsc[2 * kk] = adesc + kk * astep; dsc[2 * kk + 1] = bdesc + ((kk * 6912 + 1152) >> 4); }
          const uint32_t bar[2] = {xempty + 16, 1};
          asm volatile("wgmma.fence.sync.aligned;" ::: "memory");
          kv_last(d, nullptr, ahi, dsc, bar, nullptr);
        }
        if (L == 0) {
          split_mean(m0, m1);
          asm volatile("wgmma.fence.sync.aligned;" ::: "memory");
          wgmma_n144_add(d + 36, am, cdesc + 18);
          wgmma_n72_add(d, am, cdesc);
          asm volatile("wgmma.commit_group.sync.aligned;" ::: "memory");
        }
        auto qstep = [&](int k) {
          wgmma_n72(d, (k < 4 ? da7 : adesc) + (k & 3) * astep, ahi, (k < 4 ? db7 : bdesc) + (k & 3) * (6912 >> 4));
        };
#pragma unroll
        for (int k = 0; k < QPRE; k++) qstep(k);
        asm volatile("wgmma.commit_group.sync.aligned;" ::: "memory");
        if (tgtwg) {
          asm volatile("wgmma.fence.sync.aligned;" ::: "memory");
#pragma unroll
          for (int k = QPRE; k < 8; k++) qstep(k);
          asm volatile("wgmma.commit_group.sync.aligned;" ::: "memory");
        }
        asm volatile("wgmma.wait_group.sync.aligned 1;" ::: "memory");
#pragma unroll
        for (int i = 36; i < 108; i++) asm volatile("" : "+f"(d[i])::"memory");
        if (selrow >= 0) {
          mbar_wait(sb + B_FIX, 0);
          stsf(rowc + 4 * selrow, 1.f);
#pragma unroll
          for (int q = 18; q < 54; q++) lds64f_if(selrow == g + 8 * (q & 1), d[2 * q], d[2 * q + 1], sb + SM_FIXQ + 32 * (q >> 1) + 8 * t);
          __syncwarp();
        }
#pragma unroll
        for (int q = 26; q >= 9; q--) { P[q][1] = packbf(d[4 * q + 2], d[4 * q + 3]); P[q][0] = packbf(d[4 * q], d[4 * q + 1]); }
#pragma unroll
        for (int q = 26; q >= 18; q--) P[q][1] = movm(P[q][1]);
        const uint2 ck1 = lds64(rowc + 32 + 8 * t);
        uint8_t* ha = (j < 3 ? smem_raw + (SM_X + (4 * w + 2) * XSTAGE + j * 2560) : GC(halo, (4 * cta + 2 * L + w) * 2560)) + ln * 16;
        P[9][1] = nz(P[9][1]); P[13][1] = nz(P[13][1]); P[17][1] = nz(P[17][1]);
        st_gen(ha, P[9][1], P[10][1], P[11][1], P[12][1]);
        st_gen(ha + 512, P[13][1], P[14][1], P[15][1], P[16][1]);
        st_gen(ha + 2048, nz(ck1.y), P[24][1], P[25][1], P[26][1]);
        st_gen(ha + 1536, nz(ck1.x), P[21][1], P[22][1], P[23][1]);
        st_gen(ha + 1024, P[17][1], P[18][1], P[19][1], P[20][1]);
#pragma unroll
        for (int q = 9; q < 27; q++) asm volatile("" : "+r"(P[q][0]));
        if (j < 3) asm volatile("bar.arrive %0, 64;" ::"r"(5 + warp) : "memory");
        mbar_wait(sb + B_EP, 0);
#pragma unroll
        for (int q = 26; q >= 18; q--) P[q][0] = movm(P[q][0]);
        if (!tgtwg)
        {
          asm volatile("wgmma.fence.sync.aligned;" ::: "memory");
#pragma unroll
          for (int k = QPRE; k < 8; k++) qstep(k);
          asm volatile("wgmma.commit_group.sync.aligned;" ::: "memory");
        }
        hl = (j > 0 || m == 0 ? smem_raw + (SM_X + (4 * w + 2) * XSTAGE + max(j - 1, 0) * 2560)
                              : GC(halo, (4 * (cta - 8) + 2 * L + w) * 2560)) + ln * 16;
        if (j > 0) asm volatile("bar.sync %0, 64;" ::"r"(4 + warp) : "memory");
        asm volatile("wgmma.wait_group.sync.aligned 0;" ::: "memory");
#pragma unroll
        for (int i = 0; i < 36; i++) asm volatile("" : "+f"(d[i])::"memory");
        TRW(1 + 12 * L);
        if (selrow >= 0) {
#pragma unroll
          for (int q = 0; q < 18; q++) lds64f_if(selrow == g + 8 * (q & 1), d[2 * q], d[2 * q + 1], sb + SM_FIXQ + 32 * (q >> 1) + 8 * t);
        }
#pragma unroll
        for (int q = 0; q < 9; q++) { P[q][0] = packbf(d[4 * q], d[4 * q + 1]); P[q][1] = packbf(d[4 * q + 2], d[4 * q + 3]); }
      }
      TRW(2 + 12 * L);
      const uint32_t epoch = lds32(sb + SM_EP);
      uint8_t* fptr = GA(flagX, 128 * mw + 16 * r + 4 * j + ln0);
      {
        RELANE2;
        halo();
        if (ln == 0) { mbar_arrive(xempty + 24); mbar_arrive(xempty); }
        const bool le0 = 2 * t <= g, le1 = 2 * t + 1 <= g;
        uint32_t A0[4][2], A2[4][2];
        float s0[4][4], s1[4][4];
#pragma unroll
        for (int h = 0; h < 4; h++) {
          const int T = 2 * h;
          A0[h][0] = t >= h ? P[T][0] : 0u; A0[h][1] = t >= h ? P[T][1] : 0u;
          A2[h][0] = t <= h ? P[T + 2][0] : 0u; A2[h][1] = t <= h ? P[T + 2][1] : 0u;
          mma8z(s0[h], A2[h][0], A2[h][1], P[9 + T + 2][0]);
          mma8z(s1[h], A2[h][0], A2[h][1], P[9 + T + 2][1]);
        }
#pragma unroll
        for (int h = 0; h < 4; h++) {
          const int T = 2 * h;
          mma16(s0[h], A0[h][0], A0[h][1], P[T + 1][0], P[T + 1][1], P[9 + T][0], P[9 + T + 1][0]);
          mma16(s1[h], A0[h][0], A0[h][1], P[T + 1][0], P[T + 1][1], P[9 + T][1], P[9 + T + 1][1]);
        }
        const uint2 ck0 = lds64(rowc + 8 * t), ck1 = lds64(rowc + 32 + 8 * t);
        const float sc = 0.23570226039551584f * 1.4426950408889634f;
        const float cq0 = ldsf(rowc + 4 * g) * sc, cq1 = ldsf(rowc + 32 + 4 * g) * sc;
        uint8_t* ob = GC(act, 2 * L * ACT + mw * 73728 + r * 9216 + j * 256 + ln * 4);
        float l[2][4][2], ks[2][2], mx[2][4];
        ks[1][0] = __uint_as_float(le0 ? ck1.x : ck0.x); ks[1][1] = __uint_as_float(le1 ? ck1.y : ck0.y);
#pragma unroll
        for (int h = 0; h < 4; h++) {
          l[1][h][0] = (le0 ? s1[h][2] : s0[h][2]) * (cq1 * ks[1][0]); l[1][h][1] = (le1 ? s1[h][3] : s0[h][3]) * (cq1 * ks[1][1]);
          asm volatile("" : "+f"(l[1][h][0]), "+f"(l[1][h][1]));
        }
        asm volatile("" : "+l"(fptr), "+l"(ob));
        {
          uint32_t n = 0;
          _Pragma("unroll 1") while (__any_sync(0xffffffffu, min(min(min(H[0], H[4]), min(H[8], H[12])), H[16]) == 0)) {
            halo();
            spin_guard(n);
          }
        }
        if (ln == 0) mbar_arrive_pair(sb + B_WEMPTY + 24);
        TRW(3 + 12 * L);
        {
          float sm[4][4];
#pragma unroll
          for (int h = 0; h < 4; h++) mma8z(sm[h], A2[h][0], A2[h][1], H[2 * h + 2]);
#pragma unroll
          for (int h = 0; h < 4; h++) mma16(sm[h], A0[h][0], A0[h][1], P[2 * h + 1][0], P[2 * h + 1][1], H[2 * h], H[2 * h + 1]);
          ks[0][0] = __uint_as_float(le0 ? ck0.x : H[12]); ks[0][1] = __uint_as_float(le1 ? ck0.y : H[16]);
          const bool nohalo = (m == 0 && j == 0);
          const float b0 = (nohalo && !le0) ? -INFINITY : 0.f, b1 = (nohalo && !le1) ? -INFINITY : 0.f;
#pragma unroll
          for (int h = 0; h < 4; h++) {
            l[0][h][0] = fmaf(le0 ? s0[h][0] : sm[h][0], cq0 * ks[0][0], b0);
            l[0][h][1] = fmaf(le1 ? s0[h][1] : sm[h][1], cq0 * ks[0][1], b1);
          }
        }
#pragma unroll
        for (int i = 7; i >= 0; i--) mx[i >> 2][i & 3] = fmaxf(l[i >> 2][i & 3][0], l[i >> 2][i & 3][1]);
#pragma unroll
        for (int x = 1; x <= 2; x <<= 1) {
#pragma unroll
          for (int i = 7; i >= 0; i--) mx[i >> 2][i & 3] = fmaxf(mx[i >> 2][i & 3], shx(mx[i >> 2][i & 3], x));
        }
        const uint32_t mle = (le0 ? 0xffffu : 0u) | (le1 ? 0xffff0000u : 0u);
        uint32_t pp[2][4], pc[2][4];
#pragma unroll
        for (int i = 3; i >= 0; i--) {
          const int e = i >> 1, h = 2 * (i & 1);
          const float p0 = ex2(l[e][h][0] - mx[e][h]), p1 = ex2(l[e][h][1] - mx[e][h]);
          const float p2 = ex2(l[e][h + 1][0] - mx[e][h + 1]), p3 = ex2(l[e][h + 1][1] - mx[e][h + 1]);
          float sum[4];
          mma8z(sum, packbf(p0, p1), packbf(p2, p3), 0x3f803f80u);
          const float inv = rcp(sum[0] * sum[2]);
          const float ia = inv * sum[2], ib = inv * sum[0];
          const uint32_t u0 = packbf(p0 * ks[e][0] * ia, p1 * ks[e][1] * ia), u1 = packbf(p2 * ks[e][0] * ib, p3 * ks[e][1] * ib);
          pp[e][h] = u0 & ~mle; pc[e][h] = u0 & mle; pp[e][h + 1] = u1 & ~mle; pc[e][h + 1] = u1 & mle;
        }
#pragma unroll
        for (int e = 1; e >= 0; e--) {
#pragma unroll
          for (int q = 8; q >= 0; q--) {
            const int h = q < 4 ? 0 : q == 4 ? 1 : 2;
            float a[4];
            mma16z(a, pp[e][h], pp[e][h + 1], pc[e][h], pc[e][h + 1], e ? P[18 + q][0] : H[9 + q + q / 3], P[18 + q][e]);
            const bool second = q == 2 * h + 2 ? t > h : q > 2 * h + 2;
            st_rlx(ob + q * 1024 + e * 128, nz(packbf(second ? a[2] : a[0], second ? a[3] : a[1])));
          }
        }
        if (ln == 0) st_rlx(fptr, epoch * 4 + 1 + 2 * L);
        TRW(4 + 12 * L);
      }
      RELANE2;
      float d[36];
      uint32_t WB[9];
      {
        uint32_t R[10][2];
        const uint32_t qs = L == 0 ? 16 : 1024, ra = xring + (16 * j + (ln & 15)) * (L == 0 ? 144 : 16) + (ln >> 4) * qs;
        mbar_wait(sb + B_RES + 8 * w, L);
#pragma unroll
        for (int q = 0; q < 10; q += 2) ldsm4(&R[q][0], ra + q * qs);
        fence_async_smem();
        __syncwarp();
        if (ln == 0) mbar_arrive(sb + B_RC + 8 * w);
#pragma unroll
        for (int q = 0; q < 9; q++) WB[q] = ldg32(p.wr + (uint32_t)(r * 144 + 4 * t) + 16 * q);
#pragma unroll
        for (int h = 0; h < 2; h++) {
          const uint2 mf = lds64(rowm + 8 * g + 64 * h);
          const float f = __uint_as_float(mf.y), k = -__uint_as_float(mf.x) * f;
#pragma unroll
          for (int q = 0; q < 9; q++) { d[4 * q + 2 * h] = fmaf(blo(R[q][h]), f, k); d[4 * q + 2 * h + 1] = fmaf(bhi(R[q][h]), f, k); }
        }
        const uint32_t sel = lds32(sb + SM_SEL);
        if (L == 1 && (sel & 127) == cid) {
          const int selrow = sel >> 7;
#pragma unroll
          for (int q = 0; q < 18; q++) lds64f_if(selrow == g + 8 * (q & 1), d[2 * q], d[2 * q + 1], sb + SM_X2R + 32 * (q >> 1) + 8 * t);
        }
#pragma unroll
        for (int q = 0; q < 9; q++) WB[q] = (g & 1) ? WB[q] : 0x3f803f80u;
        __syncwarp();
      }
      uint8_t* xb = GC(act, ACT + mw * 73728 + r * 9216 + j * 256 + ln * 4);
      uint8_t* sst = GA(statsP, mw * 8192 + r * 1024 + (16 * j + g + 8 * t) * 16);
      const uint8_t* sld = GA(statsP, mw * 8192 + (ln >> 4) * 4096 + (16 * j + (ln & 15)) * 16);
      uint8_t* cptr = GA(cand, (8 * L + r) * 2048 + 16 * cid);
      uint8_t* crow = GC(candrow, (128 * L + cid) * 1152 + 144 * r + 4 * t);
      uint32_t tag = epoch * 2 + L, ktag = ((ln & 15) << 7) | (epoch & 0x7f);
      float wsum = ldsf(sb + SM_WSUM);
      float pivot = __uint_as_float(ld_rlx(GA(stats0, 16 * (16 * cid + (ln & 15)) + 4))) + (L ? ldsf(rowm + 8 * (ln & 15)) : 0.f);
      asm volatile("" : "+l"(xb), "+l"(sst), "+l"(sld), "+l"(cptr), "+l"(crow), "+r"(tag), "+r"(ktag), "+f"(wsum), "+f"(pivot));
      TRW(5 + 12 * L);
      {
        constexpr uint32_t bdesc = mkdesc(sbd + SM_W + WSTAGE, 1152);
        uint32_t adesc[3];
#pragma unroll
        for (int i = 0; i < 3; i++) adesc[i] = __shfl_sync(0xffffffffu, mkdesc(sbd + SM_X + w * 4 * XSTAGE, 1024) + (ln >> 2), i);
#pragma unroll
        for (int i = 0; i < 36; i++) asm volatile("" : "+f"(d[i])::"memory");
        const bool lead = warp == 0 && ln == 0;
        const uint8_t* osrc = GC(act, 2 * L * ACT + mw * 73728);
        mbar_wait2(sb + B_WFULL + 8, L, xfull, 1);
        check_stage(probe_stage(pa), xring, osrc);
        TRW(6 + 12 * L);
#pragma unroll
        for (int s = 0; s < 9; s++) {
          TRQ(18 + s);
          const uint32_t da = adesc[s >> 2] + (s & 3) * (XSTAGE >> 4), db = bdesc + s * (9216 >> 4);
          const uint32_t nx = (s + 1) & 3;
          asm volatile("wgmma.fence.sync.aligned;" ::: "memory");
          wgmma_n72(d, da, 8u, db);
          wgmma_n72(d, da + 128, 8u, db + (2304 >> 4));
          asm volatile("wgmma.commit_group.sync.aligned;" ::: "memory");
          if (s > 0) {
            asm volatile("wgmma.wait_group.sync.aligned 1;" ::: "memory");
            if (ln == 0) {
              mbar_arrive(xempty + 8 * ((s - 1) & 3));
              if ((s == 1 || s == 3 || s == 6) && L == 0) mbar_arrive_pair(sb + B_WEMPTY + (s / 3) * 8);
            }
          }
          const uint32_t px = (((s + 1) >> 2) + (nx == 0)) & 1;
          if ((s == 0 || s == 5) && lead) mbar_arrive(sb + (s ? B_EPI : B_OS));
          if (s < 8) {
            uint32_t pv;
            const uint32_t dsc[4] = {da + 256, db + (4608 >> 4), da + 384, db + (6912 >> 4)};
            const uint32_t bar[4] = {sb + B_WFULL + 8 + 8 * ((s + 1) / 3), (uint32_t)L, xfull + 8 * nx, px}, adr = pa + nx * XSTAGE;
            o_tail2(d, &pv, 8u, dsc, bar, &adr);
            check_stage(pv, xring + nx * XSTAGE, osrc + (s + 1) * XSTAGE);
          } else {
            wgmma_n72(d, da + 256, 8u, db + (4608 >> 4));
            wgmma_n72(d, da + 384, 8u, db + (6912 >> 4));
            asm volatile("wgmma.commit_group.sync.aligned;" ::: "memory");
          }
        }
        asm volatile("wgmma.wait_group.sync.aligned 0;" ::: "memory");
#pragma unroll
        for (int i = 0; i < 36; i++) asm volatile("" : "+f"(d[i])::"memory");
        if (ln == 0) { if (L == 0) mbar_arrive_pair(sb + B_WEMPTY + 24); mbar_arrive(xempty); }
      }
      TRW(7 + 12 * L);
      uint32_t R[9][2];
#pragma unroll
      for (int q = 0; q < 9; q++) { R[q][0] = packbf(d[4 * q], d[4 * q + 1]); R[q][1] = packbf(d[4 * q + 2], d[4 * q + 3]); }
      {
        float sa[4], sc[4];
        mma16z(sa, R[0][0], R[0][1], R[1][0], R[1][1], WB[0], WB[1]);
        mma16z(sc, R[2][0], R[2][1], R[3][0], R[3][1], WB[2], WB[3]);
        mma16(sa, R[4][0], R[4][1], R[5][0], R[5][1], WB[4], WB[5]);
        mma16(sc, R[6][0], R[6][1], R[7][0], R[7][1], WB[6], WB[7]);
        mma8(sa, R[8][0], R[8][1], WB[8]);
        float qq[4] = {0.f, 0.f, 0.f, 0.f};
#pragma unroll
        for (int q = 0; q < 36; q++) qq[q & 3] = fmaf(d[q], d[q], qq[q & 3]);
        const float qa = qq[0] + qq[1], qc = qq[2] + qq[3];
        const bool odd = t & 1;
        float q2 = (odd ? qc : qa) + shx(odd ? qa : qc, 1);
        q2 += shx(q2, 2);
        if (t < 2)
          st_msg(sst, __float_as_uint(odd ? sa[2] + sc[2] : sa[0] + sc[0]), __float_as_uint(q2),
                 __float_as_uint(odd ? sa[3] + sc[3] : sa[1] + sc[1]), tag);
      }
      if (L == 0) {
#pragma unroll
        for (int q = 0; q < 9; q++) { st_rlx(xb + q * 1024, nz(R[q][0])); st_rlx(xb + q * 1024 + 128, nz(R[q][1])); }
        if (ln == 0) st_rlx(fptr, epoch * 4 + 2);
      }
      TRW(8 + 12 * L);
      {
        uint4 u[4];
        uint32_t n = 0;
        _Pragma("unroll 1") while (true) {
#pragma unroll
          for (int i = 0; i < 4; i++) u[i] = ld_msg(sld + 1024 * i);
          if (!__any_sync(0xffffffffu, (u[0].w ^ tag) | (u[1].w ^ tag) | (u[2].w ^ tag) | (u[3].w ^ tag))) break;
          spin_guard(n);
        }
        TRW(9 + 12 * L);
        float s1 = (__uint_as_float(u[0].x) + __uint_as_float(u[1].x)) + (__uint_as_float(u[2].x) + __uint_as_float(u[3].x));
        float s2 = (__uint_as_float(u[0].y) + __uint_as_float(u[1].y)) + (__uint_as_float(u[2].y) + __uint_as_float(u[3].y));
        float s3 = (__uint_as_float(u[0].z) + __uint_as_float(u[1].z)) + (__uint_as_float(u[2].z) + __uint_as_float(u[3].z));
        s1 += shx(s1, 16); s2 += shx(s2, 16); s3 += shx(s3, 16);
        const float mu = s1 * (1.f / kD);
        const float var = fmaxf(fmaf(s2, 1.f / kD, -mu * mu), 0.f);
        const float sd = ln_sd(var), rho = rcp(sd);
        const float rr = (s3 - mu * wsum) * rho;
        const int key = __reduce_max_sync(0xffffffffu, (int)((fkey(rr) & ~0x7ff) | ktag));
        const int best = (key >> 7) & 15;
        if (ln == best) st_msg(cptr, key, __float_as_uint(rbf(sigmoidf(rbf(rr)))), __float_as_uint(1.f + sd), __float_as_uint(L ? pivot + mu : 0.f));
        const float rb = __shfl_sync(0xffffffffu, rho, best), nb = __shfl_sync(0xffffffffu, -mu * rho, best);
        if ((best & 7) == g) {
          const bool hi = best >= 8;
#pragma unroll
          for (int q = 0; q < 9; q++)
            st_rlx(crow + (((q ^ r) & 1) * (4 - 8 * (t & 1))) + 16 * q, nz(packbf(fmaf(hi ? d[4 * q + 2] : d[4 * q], rb, nb), fmaf(hi ? d[4 * q + 3] : d[4 * q + 1], rb, nb))));
        }
        const float f = 1.f + rho, k = pivot - mu * rho;
        sts32(rowc + 4 * (ln & 15), __float_as_uint(f * rcp(ln_sd(var * f * f))));
        sts64(rowm + 8 * (ln & 15), __float_as_uint(L == 0 ? mu : k), __float_as_uint(f));
        __syncwarp();
      }
      TRW(10 + 12 * L);
      if (L == 1) {
#pragma unroll
        for (int h = 0; h < 2; h++) {
          const uint2 kf = lds64(rowm + 8 * g + 64 * h);
          const float k = __uint_as_float(kf.x), f = __uint_as_float(kf.y);
#pragma unroll
          for (int q = 0; q < 9; q++) R[q][h] = packbf(fmaf(d[4 * q + 2 * h], f, k), fmaf(d[4 * q + 2 * h + 1], f, k));
        }
        mbar_wait(xempty + 16, 1);
        const uint32_t st = xring + XSTAGE + (16 * j + (ln & 15)) * 144;
#pragma unroll
        for (int q = 0; q < 8; q += 2) stsm4(st + (ln >> 4) * 16 + q * 16, R[q][0], R[q][1], R[q + 1][0], R[q + 1][1]);
        stsm2(st + 128, R[8][0], R[8][1]);
        fence_async_smem();
        __syncwarp();
        mbar_wait(sb + B_IDX + 8, 0);
        const uint32_t sel = lds32(sb + SM_SEL + 4);
        if ((sel & 127) != cid) {
          if (elect())
            asm volatile("cp.async.bulk.tensor.3d.global.shared::cta.bulk_group [%0, {%2,%3,%4}], [%1];" ::"l"(&tm.out),
                         "r"(xring + XSTAGE + 16 * j * 144), "r"(72 * r), "r"(w), "r"(64 * m + 16 * j) : "memory");
        } else if (ln < 16 && ln != (sel >> 7)) {
          bulk_s2g(p.out + (uint32_t)((128 * m + 2 * (16 * j + ln) + w) * 1152 + r * 144), st, 144);
        }
        asm volatile("cp.async.bulk.commit_group;" ::: "memory");
        asm volatile("cp.async.bulk.wait_group.read 0;" ::: "memory");
        TRW(11 + 12 * L);
        TRDUMP(w);
      }
    }
  }
}

typedef CUresult (*EncodeFn)(CUtensorMap*, CUtensorMapDataType, cuuint32_t, void*, const cuuint64_t*, const cuuint64_t*,
                             const cuuint32_t*, const cuuint32_t*, CUtensorMapInterleave, CUtensorMapSwizzle,
                             CUtensorMapL2promotion, CUtensorMapFloatOOBfill);

}

extern "C" void kernel_launch(void* const* d_in, const int* in_sizes, int n_in, void* d_out, int out_size) {
  static EncodeFn enc = nullptr;
  static Scratch* scratch = nullptr;
  if (!enc) {
    cudaDriverEntryPointQueryResult q;
    cudaGetDriverEntryPoint("cuTensorMapEncodeTiled", (void**)&enc, cudaEnableDefault, &q);
    cudaGetSymbolAddress((void**)&scratch, g_s);
    cudaFuncSetAttribute(fused_kernel, cudaFuncAttributeMaxDynamicSharedMemorySize, 232448);
  }
  Maps tm;
  auto mk = [&](CUtensorMap* t, void* ptr, int rank, const cuuint64_t* dims, const cuuint64_t* strides, const cuuint32_t* box,
                CUtensorMapSwizzle sw, CUtensorMapL2promotion pr) {
    const cuuint32_t es[4] = {1, 1, 1, 1};
    enc(t, CU_TENSOR_MAP_DATA_TYPE_BFLOAT16, rank, ptr, dims, strides, box, es, CU_TENSOR_MAP_INTERLEAVE_NONE, sw, pr,
        CU_TENSOR_MAP_FLOAT_OOB_FILL_NONE);
  };
  { const cuuint64_t d[3] = {576, 2, 1024}, st[2] = {1152, 2304}; const cuuint32_t bx[3] = {64, 1, 64};
    mk(&tm.x, d_in[0], 3, d, st, bx, CU_TENSOR_MAP_SWIZZLE_128B, CU_TENSOR_MAP_L2_PROMOTION_NONE);
    const cuuint32_t br[3] = {72, 1, 64};
    mk(&tm.xr, d_in[0], 3, d, st, br, CU_TENSOR_MAP_SWIZZLE_NONE, CU_TENSOR_MAP_L2_PROMOTION_NONE);
    const cuuint32_t bo[3] = {72, 1, 16};
    mk(&tm.out, d_out, 3, d, st, bo, CU_TENSOR_MAP_SWIZZLE_NONE, CU_TENSOR_MAP_L2_PROMOTION_NONE); }
  { const cuuint64_t d[3] = {576, 576, 3}, st[2] = {3456, 1152}; const cuuint32_t bx[3] = {72, 8, 2};
    mk(&tm.wq, d_in[1], 3, d, st, bx, CU_TENSOR_MAP_SWIZZLE_NONE, CU_TENSOR_MAP_L2_PROMOTION_NONE); }
  { const cuuint64_t d[2] = {576, 576}, st[1] = {1152}; const cuuint32_t bx[2] = {72, 16};
    mk(&tm.wo, d_in[2], 2, d, st, bx, CU_TENSOR_MAP_SWIZZLE_NONE, CU_TENSOR_MAP_L2_PROMOTION_NONE); }
  { const cuuint64_t d[2] = {4608, 576}, st[1] = {9216}; const cuuint32_t bx[2] = {48, 64};
    mk(&tm.wg, d_in[5], 2, d, st, bx, CU_TENSOR_MAP_SWIZZLE_128B, CU_TENSOR_MAP_L2_PROMOTION_L2_128B);
    mk(&tm.wu, d_in[6], 2, d, st, bx, CU_TENSOR_MAP_SWIZZLE_128B, CU_TENSOR_MAP_L2_PROMOTION_L2_128B); }
  Params p;
  p.x = (const uint8_t*)d_in[0]; p.wqkv = (const uint8_t*)d_in[1]; p.wo = (const uint8_t*)d_in[2];
  p.wr = (const uint8_t*)d_in[4]; p.wg = (const uint8_t*)d_in[5]; p.wu = (const uint8_t*)d_in[6]; p.wd = (const uint8_t*)d_in[7];
  p.out = (uint8_t*)d_out;
  p.g = scratch;
  fused_kernel<<<128, 512, 232448>>>(p, tm);
}
```

```cpp
#include <cuda_runtime.h>
#include <cuda_bf16.h>
#include <cuda.h>
#include <stdint.h>
#include <stddef.h>

#define DEVI __device__ __forceinline__

namespace {

constexpr int kD = 576, kF = 4608;
constexpr uint32_t WSTAGE = 27648, XSTAGE = 8192;
constexpr float kEps = 1e-5f;

constexpr uint32_t WDP = 1168;
constexpr uint32_t SM_W = 0;
constexpr uint32_t SM_X = 110592;
constexpr uint32_t SM_WD = 176128;
constexpr uint32_t SM_LEFT = SM_WD + 36 * WDP;
constexpr uint32_t SM_COLSUM = SM_LEFT + 9216;
constexpr uint32_t SM_ROWC = SM_COLSUM + 960;
constexpr uint32_t SM_ROWM = SM_ROWC + 512;
constexpr uint32_t SM_PART = SM_ROWM + 1024;
constexpr uint32_t SM_FIXQ = SM_PART;
constexpr uint32_t SM_X2R = SM_PART + 864;
constexpr uint32_t SM_H = SM_PART + 1152;
constexpr uint32_t SM_GEMV = SM_H;
constexpr uint32_t SM_RED = SM_H + 320;
constexpr uint32_t SM_SEL = SM_RED + 256;
constexpr uint32_t SM_EP = SM_SEL + 8, SM_WSUM = SM_SEL + 12;
constexpr uint32_t SM_BAR = SM_SEL + 16;
constexpr uint32_t B_WFULL = SM_BAR, B_WEMPTY = B_WFULL + 32, B_XFULL = B_WEMPTY + 32, B_XEMPTY = B_XFULL + 64;
constexpr uint32_t B_RC = B_XEMPTY + 64;
constexpr uint32_t B_COLSUM = B_RC + 16, B_PKF = B_COLSUM + 8, B_FIX = B_PKF + 8, B_DONE = B_FIX + 8;
constexpr uint32_t B_FF = B_DONE + 8;
constexpr uint32_t B_IDX = B_FF + 24;
constexpr uint32_t B_WD = B_IDX + 16, B_WANT = B_WD + 8, B_EPI = B_WANT + 8, B_EP = B_EPI + 8, B_OS = B_EP + 8, B_FD = B_OS + 8;
constexpr uint32_t B_WL = B_FD + 8;
constexpr uint32_t B_RES = B_WL + 32;
constexpr uint32_t B_XE = B_RES + 16;
constexpr uint32_t SM_TOTAL = B_XE + 16;
constexpr int NBAR = (SM_TOTAL - SM_BAR) / 8, NBAR4 = (B_FF - SM_BAR) / 8;
static_assert(((B_EP - SM_BAR) / 8 * 4) / NBAR == 3, "warp 15 initialises B_EP");
constexpr uint32_t FSLOT = 16384;
static_assert(SM_TOTAL + 256 <= 232448, "smem");

struct __align__(1024) Checked {
  uint32_t candrow[2][128][288];
  uint4 halo[128][2][2][5][32];
  uint8_t wpack[8][12 * WSTAGE];
  uint8_t act[3][16][2][73728];
};
struct __align__(1024) Scratch {
  uint4 cand[2][8][128];
  uint4 ypart[72][128][2];
  uint32_t x2msg[8][576];
  uint32_t fixmsg[8][256];
  uint32_t flagP[8][12][32];
  uint32_t flagX[16][2][32];
  uint32_t epoch[128][8];
  uint4 stats0[16][2][64];
  uint4 statsP[16][2][8][64];
  float colpart[8][8][216];
  Checked chk[2];
};
__device__ Scratch g_s;
#define GA(member, off) (gb + offsetof(Scratch, member) + (uint32_t)(off))
#define GC(member, off) (gb + offsetof(Scratch, chk) + offsetof(Checked, member) + (uint32_t)((off) + (epoch & 1) * (uint32_t)sizeof(Checked)))
constexpr uint32_t ACT = 16 * 2 * 73728;

#define TR(role, i)
#define TRL(role, i)
#define TRDUMP(role)
#define TRW(i)
#define TRZ(i)
#define TRQ(i)

__device__ __forceinline__ void wgmma_n144(float* d, uint32_t alo, uint32_t ahi, uint32_t blo) {
  asm volatile("{\n.reg .b64 da, db;\nmov.b64 da, {%72, %73};\nmov.b64 db, {%74, 8};\n"
    "wgmma.mma_async.sync.aligned.m64n144k16.f32.bf16.bf16 "
    "{%0, %1, %2, %3, %4, %5, %6, %7, %8, %9, %10, %11, %12, %13, %14, %15, %16, %17, %18, %19, %20, %21, %22, %23, %24, %25, %26, %27, %28, %29, %30, %31, %32, %33, %34, %35, %36, %37, %38, %39, %40, %41, %42, %43, %44, %45, %46, %47, %48, %49, %50, %51, %52, %53, %54, %55, %56, %57, %58, %59, %60, %61, %62, %63, %64, %65, %66, %67, %68, %69, %70, %71}, da, db, 1, 1, 1, 0, 1;\n}\n"
    : "+f"(d[0]), "+f"(d[1]), "+f"(d[2]), "+f"(d[3]), "+f"(d[4]), "+f"(d[5]), "+f"(d[6]), "+f"(d[7]), "+f"(d[8]),
      "+f"(d[9]), "+f"(d[10]), "+f"(d[11]), "+f"(d[12]), "+f"(d[13]), "+f"(d[14]), "+f"(d[15]), "+f"(d[16]), "+f"(d[17]),
      "+f"(d[18]), "+f"(d[19]), "+f"(d[20]), "+f"(d[21]), "+f"(d[22]), "+f"(d[23]), "+f"(d[24]), "+f"(d[25]), "+f"(d[26]),
      "+f"(d[27]), "+f"(d[28]), "+f"(d[29]), "+f"(d[30]), "+f"(d[31]), "+f"(d[32]), "+f"(d[33]), "+f"(d[34]), "+f"(d[35]),
      "+f"(d[36]), "+f"(d[37]), "+f"(d[38]), "+f"(d[39]), "+f"(d[40]), "+f"(d[41]), "+f"(d[42]), "+f"(d[43]), "+f"(d[44]),
      "+f"(d[45]), "+f"(d[46]), "+f"(d[47]), "+f"(d[48]), "+f"(d[49]), "+f"(d[50]), "+f"(d[51]), "+f"(d[52]), "+f"(d[53]),
      "+f"(d[54]), "+f"(d[55]), "+f"(d[56]), "+f"(d[57]), "+f"(d[58]), "+f"(d[59]), "+f"(d[60]), "+f"(d[61]), "+f"(d[62]),
      "+f"(d[63]), "+f"(d[64]), "+f"(d[65]), "+f"(d[66]), "+f"(d[67]), "+f"(d[68]), "+f"(d[69]), "+f"(d[70]), "+f"(d[71])
    : "r"(alo), "r"(ahi), "r"(blo));
}
__device__ __forceinline__ void wgmma_n144_set(float* d, const uint32_t* a, uint32_t blo) {
  asm volatile("{\n.reg .b64 db;\nmov.b64 db, {%76, 2};\n"
    "wgmma.mma_async.sync.aligned.m64n144k16.f32.bf16.bf16 "
    "{%0, %1, %2, %3, %4, %5, %6, %7, %8, %9, %10, %11, %12, %13, %14, %15, %16, %17, %18, %19, %20, %21, %22, %23, %24, %25, %26, %27, %28, %29, %30, %31, %32, %33, %34, %35, %36, %37, %38, %39, %40, %41, %42, %43, %44, %45, %46, %47, %48, %49, %50, %51, %52, %53, %54, %55, %56, %57, %58, %59, %60, %61, %62, %63, %64, %65, %66, %67, %68, %69, %70, %71}, {%72, %73, %74, %75}, db, 0, -1, 1, 1;\n}\n"
    : "=f"(d[0]), "=f"(d[1]), "=f"(d[2]), "=f"(d[3]), "=f"(d[4]), "=f"(d[5]), "=f"(d[6]), "=f"(d[7]), "=f"(d[8]),
      "=f"(d[9]), "=f"(d[10]), "=f"(d[11]), "=f"(d[12]), "=f"(d[13]), "=f"(d[14]), "=f"(d[15]), "=f"(d[16]), "=f"(d[17]),
      "=f"(d[18]), "=f"(d[19]), "=f"(d[20]), "=f"(d[21]), "=f"(d[22]), "=f"(d[23]), "=f"(d[24]), "=f"(d[25]), "=f"(d[26]),
      "=f"(d[27]), "=f"(d[28]), "=f"(d[29]), "=f"(d[30]), "=f"(d[31]), "=f"(d[32]), "=f"(d[33]), "=f"(d[34]), "=f"(d[35]),
      "=f"(d[36]), "=f"(d[37]), "=f"(d[38]), "=f"(d[39]), "=f"(d[40]), "=f"(d[41]), "=f"(d[42]), "=f"(d[43]), "=f"(d[44]),
      "=f"(d[45]), "=f"(d[46]), "=f"(d[47]), "=f"(d[48]), "=f"(d[49]), "=f"(d[50]), "=f"(d[51]), "=f"(d[52]), "=f"(d[53]),
      "=f"(d[54]), "=f"(d[55]), "=f"(d[56]), "=f"(d[57]), "=f"(d[58]), "=f"(d[59]), "=f"(d[60]), "=f"(d[61]), "=f"(d[62]),
      "=f"(d[63]), "=f"(d[64]), "=f"(d[65]), "=f"(d[66]), "=f"(d[67]), "=f"(d[68]), "=f"(d[69]), "=f"(d[70]), "=f"(d[71])
    : "r"(a[0]), "r"(a[1]), "r"(a[2]), "r"(a[3]), "r"(blo));
}
__device__ __forceinline__ void wgmma_n144_add(float* d, const uint32_t* a, uint32_t blo) {
  asm volatile("{\n.reg .b64 db;\nmov.b64 db, {%76, 2};\n"
    "wgmma.mma_async.sync.aligned.m64n144k16.f32.bf16.bf16 "
    "{%0, %1, %2, %3, %4, %5, %6, %7, %8, %9, %10, %11, %12, %13, %14, %15, %16, %17, %18, %19, %20, %21, %22, %23, %24, %25, %26, %27, %28, %29, %30, %31, %32, %33, %34, %35, %36, %37, %38, %39, %40, %41, %42, %43, %44, %45, %46, %47, %48, %49, %50, %51, %52, %53, %54, %55, %56, %57, %58, %59, %60, %61, %62, %63, %64, %65, %66, %67, %68, %69, %70, %71}, {%72, %73, %74, %75}, db, 1, -1, 1, 1;\n}\n"
    : "+f"(d[0]), "+f"(d[1]), "+f"(d[2]), "+f"(d[3]), "+f"(d[4]), "+f"(d[5]), "+f"(d[6]), "+f"(d[7]), "+f"(d[8]),
      "+f"(d[9]), "+f"(d[10]), "+f"(d[11]), "+f"(d[12]), "+f"(d[13]), "+f"(d[14]), "+f"(d[15]), "+f"(d[16]), "+f"(d[17]),
      "+f"(d[18]), "+f"(d[19]), "+f"(d[20]), "+f"(d[21]), "+f"(d[22]), "+f"(d[23]), "+f"(d[24]), "+f"(d[25]), "+f"(d[26]),
      "+f"(d[27]), "+f"(d[28]), "+f"(d[29]), "+f"(d[30]), "+f"(d[31]), "+f"(d[32]), "+f"(d[33]), "+f"(d[34]), "+f"(d[35]),
      "+f"(d[36]), "+f"(d[37]), "+f"(d[38]), "+f"(d[39]), "+f"(d[40]), "+f"(d[41]), "+f"(d[42]), "+f"(d[43]), "+f"(d[44]),
      "+f"(d[45]), "+f"(d[46]), "+f"(d[47]), "+f"(d[48]), "+f"(d[49]), "+f"(d[50]), "+f"(d[51]), "+f"(d[52]), "+f"(d[53]),
      "+f"(d[54]), "+f"(d[55]), "+f"(d[56]), "+f"(d[57]), "+f"(d[58]), "+f"(d[59]), "+f"(d[60]), "+f"(d[61]), "+f"(d[62]),
      "+f"(d[63]), "+f"(d[64]), "+f"(d[65]), "+f"(d[66]), "+f"(d[67]), "+f"(d[68]), "+f"(d[69]), "+f"(d[70]), "+f"(d[71])
    : "r"(a[0]), "r"(a[1]), "r"(a[2]), "r"(a[3]), "r"(blo));
}
__device__ __forceinline__ void wgmma_n72(float* d, uint32_t alo, uint32_t ahi, uint32_t blo) {
  asm volatile("{\n.reg .b64 da, db;\nmov.b64 da, {%36, %37};\nmov.b64 db, {%38, 8};\n"
    "wgmma.mma_async.sync.aligned.m64n72k16.f32.bf16.bf16 "
    "{%0, %1, %2, %3, %4, %5, %6, %7, %8, %9, %10, %11, %12, %13, %14, %15, %16, %17, %18, %19, %20, %21, %22, %23, %24, %25, %26, %27, %28, %29, %30, %31, %32, %33, %34, %35}, da, db, 1, 1, 1, 0, 1;\n}\n"
    : "+f"(d[0]), "+f"(d[1]), "+f"(d[2]), "+f"(d[3]), "+f"(d[4]), "+f"(d[5]), "+f"(d[6]), "+f"(d[7]), "+f"(d[8]),
      "+f"(d[9]), "+f"(d[10]), "+f"(d[11]), "+f"(d[12]), "+f"(d[13]), "+f"(d[14]), "+f"(d[15]), "+f"(d[16]), "+f"(d[17]),
      "+f"(d[18]), "+f"(d[19]), "+f"(d[20]), "+f"(d[21]), "+f"(d[22]), "+f"(d[23]), "+f"(d[24]), "+f"(d[25]), "+f"(d[26]),
      "+f"(d[27]), "+f"(d[28]), "+f"(d[29]), "+f"(d[30]), "+f"(d[31]), "+f"(d[32]), "+f"(d[33]), "+f"(d[34]), "+f"(d[35])
    : "r"(alo), "r"(ahi), "r"(blo));
}
__device__ __forceinline__ void wgmma_n72_set(float* d, const uint32_t* a, uint32_t blo) {
  asm volatile("{\n.reg .b64 db;\nmov.b64 db, {%40, 2};\n"
    "wgmma.mma_async.sync.aligned.m64n72k16.f32.bf16.bf16 "
    "{%0, %1, %2, %3, %4, %5, %6, %7, %8, %9, %10, %11, %12, %13, %14, %15, %16, %17, %18, %19, %20, %21, %22, %23, %24, %25, %26, %27, %28, %29, %30, %31, %32, %33, %34, %35}, {%36, %37, %38, %39}, db, 0, -1, 1, 1;\n}\n"
    : "=f"(d[0]), "=f"(d[1]), "=f"(d[2]), "=f"(d[3]), "=f"(d[4]), "=f"(d[5]), "=f"(d[6]), "=f"(d[7]), "=f"(d[8]),
      "=f"(d[9]), "=f"(d[10]), "=f"(d[11]), "=f"(d[12]), "=f"(d[13]), "=f"(d[14]), "=f"(d[15]), "=f"(d[16]), "=f"(d[17]),
      "=f"(d[18]), "=f"(d[19]), "=f"(d[20]), "=f"(d[21]), "=f"(d[22]), "=f"(d[23]), "=f"(d[24]), "=f"(d[25]), "=f"(d[26]),
      "=f"(d[27]), "=f"(d[28]), "=f"(d[29]), "=f"(d[30]), "=f"(d[31]), "=f"(d[32]), "=f"(d[33]), "=f"(d[34]), "=f"(d[35])
    : "r"(a[0]), "r"(a[1]), "r"(a[2]), "r"(a[3]), "r"(blo));
}
__device__ __forceinline__ void wgmma_n72_add(float* d, const uint32_t* a, uint32_t blo) {
  asm volatile("{\n.reg .b64 db;\nmov.b64 db, {%40, 2};\n"
    "wgmma.mma_async.sync.aligned.m64n72k16.f32.bf16.bf16 "
    "{%0, %1, %2, %3, %4, %5, %6, %7, %8, %9, %10, %11, %12, %13, %14, %15, %16, %17, %18, %19, %20, %21, %22, %23, %24, %25, %26, %27, %28, %29, %30, %31, %32, %33, %34, %35}, {%36, %37, %38, %39}, db, 1, -1, 1, 1;\n}\n"
    : "+f"(d[0]), "+f"(d[1]), "+f"(d[2]), "+f"(d[3]), "+f"(d[4]), "+f"(d[5]), "+f"(d[6]), "+f"(d[7]), "+f"(d[8]),
      "+f"(d[9]), "+f"(d[10]), "+f"(d[11]), "+f"(d[12]), "+f"(d[13]), "+f"(d[14]), "+f"(d[15]), "+f"(d[16]), "+f"(d[17]),
      "+f"(d[18]), "+f"(d[19]), "+f"(d[20]), "+f"(d[21]), "+f"(d[22]), "+f"(d[23]), "+f"(d[24]), "+f"(d[25]), "+f"(d[26]),
      "+f"(d[27]), "+f"(d[28]), "+f"(d[29]), "+f"(d[30]), "+f"(d[31]), "+f"(d[32]), "+f"(d[33]), "+f"(d[34]), "+f"(d[35])
    : "r"(a[0]), "r"(a[1]), "r"(a[2]), "r"(a[3]), "r"(blo));
}
__device__ __forceinline__ void q_tail(float* d, uint32_t* v, uint32_t ahi, const uint32_t* dsc, const uint32_t* bar, const uint32_t* adr) {
  asm volatile(
    "{\n.reg .pred p<2>, q;\n.reg .b64 da, db;\n.reg .u32 n;\n"
    "mbarrier.test_wait.parity.shared::cta.b64 p0, [%116], %117;\n"
    "mbarrier.test_wait.parity.shared::cta.b64 p1, [%118], %119;\n"
    "ld.volatile.shared.u32 %108, [%120];\n"
    "mov.b64 da, {%110, %109};\nmov.b64 db, {%111, 8};\n"
    "wgmma.mma_async.sync.aligned.m64n144k16.f32.bf16.bf16 {%36, %37, %38, %39, %40, %41, %42, %43, %44, %45, %46, %47, %48, %49, %50, %51, %52, %53, %54, %55, %56, %57, %58, %59, %60, %61, %62, %63, %64, %65, %66, %67, %68, %69, %70, %71, %72, %73, %74, %75, %76, %77, %78, %79, %80, %81, %82, %83, %84, %85, %86, %87, %88, %89, %90, %91, %92, %93, %94, %95, %96, %97, %98, %99, %100, %101, %102, %103, %104, %105, %106, %107}, da, db, 1, 1, 1, 0, 1;\n"
    "mov.b64 da, {%112, %109};\nmov.b64 db, {%113, 8};\n"
    "wgmma.mma_async.sync.aligned.m64n72k16.f32.bf16.bf16 {%0, %1, %2, %3, %4, %5, %6, %7, %8, %9, %10, %11, %12, %13, %14, %15, %16, %17, %18, %19, %20, %21, %22, %23, %24, %25, %26, %27, %28, %29, %30, %31, %32, %33, %34, %35}, da, db, 1, 1, 1, 0, 1;\n"
    "mov.b64 da, {%114, %109};\nmov.b64 db, {%115, 8};\n"
    "wgmma.mma_async.sync.aligned.m64n144k16.f32.bf16.bf16 {%36, %37, %38, %39, %40, %41, %42, %43, %44, %45, %46, %47, %48, %49, %50, %51, %52, %53, %54, %55, %56, %57, %58, %59, %60, %61, %62, %63, %64, %65, %66, %67, %68, %69, %70, %71, %72, %73, %74, %75, %76, %77, %78, %79, %80, %81, %82, %83, %84, %85, %86, %87, %88, %89, %90, %91, %92, %93, %94, %95, %96, %97, %98, %99, %100, %101, %102, %103, %104, %105, %106, %107}, da, db, 1, 1, 1, 0, 1;\n"
    "wgmma.commit_group.sync.aligned;\n"
    "@p0 bra.uni D0;\nmov.u32 n, 0;\nW0:\nmbarrier.try_wait.parity.shared::cta.b64 q, [%116], %117;\n@q bra.uni R0;\nadd.u32 n, n, 1;\nsetp.lt.u32 q, n, 8192;\n@q bra.uni W0;\nR0:\n"
    "D0:\n"
    "@p1 bra.uni D1;\nmov.u32 n, 0;\nW1:\nmbarrier.try_wait.parity.shared::cta.b64 q, [%118], %119;\n@q bra.uni R1;\nadd.u32 n, n, 1;\nsetp.lt.u32 q, n, 8192;\n@q bra.uni W1;\nR1:\n"
    "ld.volatile.shared.u32 %108, [%120];\n"
    "D1:\n"
    "}\n"
    : "+f"(d[0]), "+f"(d[1]), "+f"(d[2]), "+f"(d[3]), "+f"(d[4]), "+f"(d[5]), "+f"(d[6]), "+f"(d[7]), "+f"(d[8]),
      "+f"(d[9]), "+f"(d[10]), "+f"(d[11]), "+f"(d[12]), "+f"(d[13]), "+f"(d[14]), "+f"(d[15]), "+f"(d[16]), "+f"(d[17]),
      "+f"(d[18]), "+f"(d[19]), "+f"(d[20]), "+f"(d[21]), "+f"(d[22]), "+f"(d[23]), "+f"(d[24]), "+f"(d[25]), "+f"(d[26]),
      "+f"(d[27]), "+f"(d[28]), "+f"(d[29]), "+f"(d[30]), "+f"(d[31]), "+f"(d[32]), "+f"(d[33]), "+f"(d[34]), "+f"(d[35]),
      "+f"(d[36]), "+f"(d[37]), "+f"(d[38]), "+f"(d[39]), "+f"(d[40]), "+f"(d[41]), "+f"(d[42]), "+f"(d[43]), "+f"(d[44]),
      "+f"(d[45]), "+f"(d[46]), "+f"(d[47]), "+f"(d[48]), "+f"(d[49]), "+f"(d[50]), "+f"(d[51]), "+f"(d[52]), "+f"(d[53]),
      "+f"(d[54]), "+f"(d[55]), "+f"(d[56]), "+f"(d[57]), "+f"(d[58]), "+f"(d[59]), "+f"(d[60]), "+f"(d[61]), "+f"(d[62]),
      "+f"(d[63]), "+f"(d[64]), "+f"(d[65]), "+f"(d[66]), "+f"(d[67]), "+f"(d[68]), "+f"(d[69]), "+f"(d[70]), "+f"(d[71]),
      "+f"(d[72]), "+f"(d[73]), "+f"(d[74]), "+f"(d[75]), "+f"(d[76]), "+f"(d[77]), "+f"(d[78]), "+f"(d[79]), "+f"(d[80]),
      "+f"(d[81]), "+f"(d[82]), "+f"(d[83]), "+f"(d[84]), "+f"(d[85]), "+f"(d[86]), "+f"(d[87]), "+f"(d[88]), "+f"(d[89]),
      "+f"(d[90]), "+f"(d[91]), "+f"(d[92]), "+f"(d[93]), "+f"(d[94]), "+f"(d[95]), "+f"(d[96]), "+f"(d[97]), "+f"(d[98]),
      "+f"(d[99]), "+f"(d[100]), "+f"(d[101]), "+f"(d[102]), "+f"(d[103]), "+f"(d[104]), "+f"(d[105]), "+f"(d[106]), "+f"(d[107]),
      "=&r"(v[0])
    : "r"(ahi), "r"(dsc[0]), "r"(dsc[1]), "r"(dsc[2]), "r"(dsc[3]), "r"(dsc[4]), "r"(dsc[5]), "r"(bar[0]), "r"(bar[1]), "r"(bar[2]), "r"(bar[3]), "r"(adr[0]) : "memory");
}
__device__ __forceinline__ void kv_tail(float* d, uint32_t* v, uint32_t ahi, const uint32_t* dsc, const uint32_t* bar, const uint32_t* adr) {
  asm volatile(
    "{\n.reg .pred p<3>, q;\n.reg .b64 da, db;\n.reg .u32 n;\n"
    "mbarrier.test_wait.parity.shared::cta.b64 p0, [%79], %80;\n"
    "mbarrier.test_wait.parity.shared::cta.b64 p1, [%81], %82;\n"
    "mbarrier.test_wait.parity.shared::cta.b64 p2, [%83], %84;\n"
    "ld.volatile.shared.u32 %72, [%85];\n"
    "ld.volatile.shared.u32 %73, [%86];\n"
    "mov.b64 da, {%75, %74};\nmov.b64 db, {%76, 8};\n"
    "wgmma.mma_async.sync.aligned.m64n144k16.f32.bf16.bf16 {%0, %1, %2, %3, %4, %5, %6, %7, %8, %9, %10, %11, %12, %13, %14, %15, %16, %17, %18, %19, %20, %21, %22, %23, %24, %25, %26, %27, %28, %29, %30, %31, %32, %33, %34, %35, %36, %37, %38, %39, %40, %41, %42, %43, %44, %45, %46, %47, %48, %49, %50, %51, %52, %53, %54, %55, %56, %57, %58, %59, %60, %61, %62, %63, %64, %65, %66, %67, %68, %69, %70, %71}, da, db, 1, 1, 1, 0, 1;\n"
    "mov.b64 da, {%77, %74};\nmov.b64 db, {%78, 8};\n"
    "wgmma.mma_async.sync.aligned.m64n144k16.f32.bf16.bf16 {%0, %1, %2, %3, %4, %5, %6, %7, %8, %9, %10, %11, %12, %13, %14, %15, %16, %17, %18, %19, %20, %21, %22, %23, %24, %25, %26, %27, %28, %29, %30, %31, %32, %33, %34, %35, %36, %37, %38, %39, %40, %41, %42, %43, %44, %45, %46, %47, %48, %49, %50, %51, %52, %53, %54, %55, %56, %57, %58, %59, %60, %61, %62, %63, %64, %65, %66, %67, %68, %69, %70, %71}, da, db, 1, 1, 1, 0, 1;\n"
    "wgmma.commit_group.sync.aligned;\n"
    "@p0 bra.uni D0;\nmov.u32 n, 0;\nW0:\nmbarrier.try_wait.parity.shared::cta.b64 q, [%79], %80;\n@q bra.uni R0;\nadd.u32 n, n, 1;\nsetp.lt.u32 q, n, 8192;\n@q bra.uni W0;\nR0:\n"
    "D0:\n"
    "@p1 bra.uni D1;\nmov.u32 n, 0;\nW1:\nmbarrier.try_wait.parity.shared::cta.b64 q, [%81], %82;\n@q bra.uni R1;\nadd.u32 n, n, 1;\nsetp.lt.u32 q, n, 8192;\n@q bra.uni W1;\nR1:\n"
    "ld.volatile.shared.u32 %72, [%85];\n"
    "D1:\n"
    "@p2 bra.uni D2;\nmov.u32 n, 0;\nW2:\nmbarrier.try_wait.parity.shared::cta.b64 q, [%83], %84;\n@q bra.uni R2;\nadd.u32 n, n, 1;\nsetp.lt.u32 q, n, 8192;\n@q bra.uni W2;\nR2:\n"
    "ld.volatile.shared.u32 %73, [%86];\n"
    "D2:\n"
    "}\n"
    : "+f"(d[36]), "+f"(d[37]), "+f"(d[38]), "+f"(d[39]), "+f"(d[40]), "+f"(d[41]), "+f"(d[42]), "+f"(d[43]), "+f"(d[44]),
      "+f"(d[45]), "+f"(d[46]), "+f"(d[47]), "+f"(d[48]), "+f"(d[49]), "+f"(d[50]), "+f"(d[51]), "+f"(d[52]), "+f"(d[53]),
      "+f"(d[54]), "+f"(d[55]), "+f"(d[56]), "+f"(d[57]), "+f"(d[58]), "+f"(d[59]), "+f"(d[60]), "+f"(d[61]), "+f"(d[62]),
      "+f"(d[63]), "+f"(d[64]), "+f"(d[65]), "+f"(d[66]), "+f"(d[67]), "+f"(d[68]), "+f"(d[69]), "+f"(d[70]), "+f"(d[71]),
      "+f"(d[72]), "+f"(d[73]), "+f"(d[74]), "+f"(d[75]), "+f"(d[76]), "+f"(d[77]), "+f"(d[78]), "+f"(d[79]), "+f"(d[80]),
      "+f"(d[81]), "+f"(d[82]), "+f"(d[83]), "+f"(d[84]), "+f"(d[85]), "+f"(d[86]), "+f"(d[87]), "+f"(d[88]), "+f"(d[89]),
      "+f"(d[90]), "+f"(d[91]), "+f"(d[92]), "+f"(d[93]), "+f"(d[94]), "+f"(d[95]), "+f"(d[96]), "+f"(d[97]), "+f"(d[98]),
      "+f"(d[99]), "+f"(d[100]), "+f"(d[101]), "+f"(d[102]), "+f"(d[103]), "+f"(d[104]), "+f"(d[105]), "+f"(d[106]), "+f"(d[107]),
      "=&r"(v[0]), "=&r"(v[1])
    : "r"(ahi), "r"(dsc[0]), "r"(dsc[1]), "r"(dsc[2]), "r"(dsc[3]), "r"(bar[0]), "r"(bar[1]), "r"(bar[2]), "r"(bar[3]), "r"(bar[4]), "r"(bar[5]), "r"(adr[0]), "r"(adr[1]) : "memory");
}
__device__ __forceinline__ void kv_last(float* d, uint32_t* v, uint32_t ahi, const uint32_t* dsc, const uint32_t* bar, const uint32_t* adr) {
  asm volatile(
    "{\n.reg .pred p<1>, q;\n.reg .b64 da, db;\n.reg .u32 n;\n"
    "mbarrier.test_wait.parity.shared::cta.b64 p0, [%81], %82;\n"
    "mov.b64 da, {%73, %72};\nmov.b64 db, {%74, 8};\n"
    "wgmma.mma_async.sync.aligned.m64n144k16.f32.bf16.bf16 {%0, %1, %2, %3, %4, %5, %6, %7, %8, %9, %10, %11, %12, %13, %14, %15, %16, %17, %18, %19, %20, %21, %22, %23, %24, %25, %26, %27, %28, %29, %30, %31, %32, %33, %34, %35, %36, %37, %38, %39, %40, %41, %42, %43, %44, %45, %46, %47, %48, %49, %50, %51, %52, %53, %54, %55, %56, %57, %58, %59, %60, %61, %62, %63, %64, %65, %66, %67, %68, %69, %70, %71}, da, db, 1, 1, 1, 0, 1;\n"
    "mov.b64 da, {%75, %72};\nmov.b64 db, {%76, 8};\n"
    "wgmma.mma_async.sync.aligned.m64n144k16.f32.bf16.bf16 {%0, %1, %2, %3, %4, %5, %6, %7, %8, %9, %10, %11, %12, %13, %14, %15, %16, %17, %18, %19, %20, %21, %22, %23, %24, %25, %26, %27, %28, %29, %30, %31, %32, %33, %34, %35, %36, %37, %38, %39, %40, %41, %42, %43, %44, %45, %46, %47, %48, %49, %50, %51, %52, %53, %54, %55, %56, %57, %58, %59, %60, %61, %62, %63, %64, %65, %66, %67, %68, %69, %70, %71}, da, db, 1, 1, 1, 0, 1;\n"
    "mov.b64 da, {%77, %72};\nmov.b64 db, {%78, 8};\n"
    "wgmma.mma_async.sync.aligned.m64n144k16.f32.bf16.bf16 {%0, %1, %2, %3, %4, %5, %6, %7, %8, %9, %10, %11, %12, %13, %14, %15, %16, %17, %18, %19, %20, %21, %22, %23, %24, %25, %26, %27, %28, %29, %30, %31, %32, %33, %34, %35, %36, %37, %38, %39, %40, %41, %42, %43, %44, %45, %46, %47, %48, %49, %50, %51, %52, %53, %54, %55, %56, %57, %58, %59, %60, %61, %62, %63, %64, %65, %66, %67, %68, %69, %70, %71}, da, db, 1, 1, 1, 0, 1;\n"
    "mov.b64 da, {%79, %72};\nmov.b64 db, {%80, 8};\n"
    "wgmma.mma_async.sync.aligned.m64n144k16.f32.bf16.bf16 {%0, %1, %2, %3, %4, %5, %6, %7, %8, %9, %10, %11, %12, %13, %14, %15, %16, %17, %18, %19, %20, %21, %22, %23, %24, %25, %26, %27, %28, %29, %30, %31, %32, %33, %34, %35, %36, %37, %38, %39, %40, %41, %42, %43, %44, %45, %46, %47, %48, %49, %50, %51, %52, %53, %54, %55, %56, %57, %58, %59, %60, %61, %62, %63, %64, %65, %66, %67, %68, %69, %70, %71}, da, db, 1, 1, 1, 0, 1;\n"
    "wgmma.commit_group.sync.aligned;\n"
    "@p0 bra.uni D0;\nmov.u32 n, 0;\nW0:\nmbarrier.try_wait.parity.shared::cta.b64 q, [%81], %82;\n@q bra.uni R0;\nadd.u32 n, n, 1;\nsetp.lt.u32 q, n, 8192;\n@q bra.uni W0;\nR0:\n"
    "D0:\n"
    "}\n"
    : "+f"(d[36]), "+f"(d[37]), "+f"(d[38]), "+f"(d[39]), "+f"(d[40]), "+f"(d[41]), "+f"(d[42]), "+f"(d[43]), "+f"(d[44]),
      "+f"(d[45]), "+f"(d[46]), "+f"(d[47]), "+f"(d[48]), "+f"(d[49]), "+f"(d[50]), "+f"(d[51]), "+f"(d[52]), "+f"(d[53]),
      "+f"(d[54]), "+f"(d[55]), "+f"(d[56]), "+f"(d[57]), "+f"(d[58]), "+f"(d[59]), "+f"(d[60]), "+f"(d[61]), "+f"(d[62]),
      "+f"(d[63]), "+f"(d[64]), "+f"(d[65]), "+f"(d[66]), "+f"(d[67]), "+f"(d[68]), "+f"(d[69]), "+f"(d[70]), "+f"(d[71]),
      "+f"(d[72]), "+f"(d[73]), "+f"(d[74]), "+f"(d[75]), "+f"(d[76]), "+f"(d[77]), "+f"(d[78]), "+f"(d[79]), "+f"(d[80]),
      "+f"(d[81]), "+f"(d[82]), "+f"(d[83]), "+f"(d[84]), "+f"(d[85]), "+f"(d[86]), "+f"(d[87]), "+f"(d[88]), "+f"(d[89]),
      "+f"(d[90]), "+f"(d[91]), "+f"(d[92]), "+f"(d[93]), "+f"(d[94]), "+f"(d[95]), "+f"(d[96]), "+f"(d[97]), "+f"(d[98]),
      "+f"(d[99]), "+f"(d[100]), "+f"(d[101]), "+f"(d[102]), "+f"(d[103]), "+f"(d[104]), "+f"(d[105]), "+f"(d[106]), "+f"(d[107])
    : "r"(ahi), "r"(dsc[0]), "r"(dsc[1]), "r"(dsc[2]), "r"(dsc[3]), "r"(dsc[4]), "r"(dsc[5]), "r"(dsc[6]), "r"(dsc[7]), "r"(bar[0]), "r"(bar[1]) : "memory");
}
__device__ __forceinline__ void o_tail(float* d, uint32_t* v, uint32_t ahi, const uint32_t* dsc, const uint32_t* bar, const uint32_t* adr) {
  asm volatile(
    "{\n.reg .pred p<1>, q;\n.reg .b64 da, db;\n.reg .u32 n;\n"
    "mbarrier.test_wait.parity.shared::cta.b64 p0, [%42], %43;\n"
    "ld.volatile.shared.u32 %36, [%44];\n"
    "mov.b64 da, {%38, %37};\nmov.b64 db, {%39, 8};\n"
    "wgmma.mma_async.sync.aligned.m64n72k16.f32.bf16.bf16 {%0, %1, %2, %3, %4, %5, %6, %7, %8, %9, %10, %11, %12, %13, %14, %15, %16, %17, %18, %19, %20, %21, %22, %23, %24, %25, %26, %27, %28, %29, %30, %31, %32, %33, %34, %35}, da, db, 1, 1, 1, 0, 1;\n"
    "mov.b64 da, {%40, %37};\nmov.b64 db, {%41, 8};\n"
    "wgmma.mma_async.sync.aligned.m64n72k16.f32.bf16.bf16 {%0, %1, %2, %3, %4, %5, %6, %7, %8, %9, %10, %11, %12, %13, %14, %15, %16, %17, %18, %19, %20, %21, %22, %23, %24, %25, %26, %27, %28, %29, %30, %31, %32, %33, %34, %35}, da, db, 1, 1, 1, 0, 1;\n"
    "wgmma.commit_group.sync.aligned;\n"
    "@p0 bra.uni D0;\nmov.u32 n, 0;\nW0:\nmbarrier.try_wait.parity.shared::cta.b64 q, [%42], %43;\n@q bra.uni R0;\nadd.u32 n, n, 1;\nsetp.lt.u32 q, n, 8192;\n@q bra.uni W0;\nR0:\n"
    "ld.volatile.shared.u32 %36, [%44];\n"
    "D0:\n"
    "}\n"
    : "+f"(d[0]), "+f"(d[1]), "+f"(d[2]), "+f"(d[3]), "+f"(d[4]), "+f"(d[5]), "+f"(d[6]), "+f"(d[7]), "+f"(d[8]),
      "+f"(d[9]), "+f"(d[10]), "+f"(d[11]), "+f"(d[12]), "+f"(d[13]), "+f"(d[14]), "+f"(d[15]), "+f"(d[16]), "+f"(d[17]),
      "+f"(d[18]), "+f"(d[19]), "+f"(d[20]), "+f"(d[21]), "+f"(d[22]), "+f"(d[23]), "+f"(d[24]), "+f"(d[25]), "+f"(d[26]),
      "+f"(d[27]), "+f"(d[28]), "+f"(d[29]), "+f"(d[30]), "+f"(d[31]), "+f"(d[32]), "+f"(d[33]), "+f"(d[34]), "+f"(d[35]),
      "=&r"(v[0])
    : "r"(ahi), "r"(dsc[0]), "r"(dsc[1]), "r"(dsc[2]), "r"(dsc[3]), "r"(bar[0]), "r"(bar[1]), "r"(adr[0]) : "memory");
}
__device__ __forceinline__ void o_tail2(float* d, uint32_t* v, uint32_t ahi, const uint32_t* dsc, const uint32_t* bar, const uint32_t* adr) {
  asm volatile(
    "{\n.reg .pred p<2>, q;\n.reg .b64 da, db;\n.reg .u32 n;\n"
    "mbarrier.test_wait.parity.shared::cta.b64 p0, [%42], %43;\n"
    "mbarrier.test_wait.parity.shared::cta.b64 p1, [%44], %45;\n"
    "ld.volatile.shared.u32 %36, [%46];\n"
    "mov.b64 da, {%38, %37};\nmov.b64 db, {%39, 8};\n"
    "wgmma.mma_async.sync.aligned.m64n72k16.f32.bf16.bf16 {%0, %1, %2, %3, %4, %5, %6, %7, %8, %9, %10, %11, %12, %13, %14, %15, %16, %17, %18, %19, %20, %21, %22, %23, %24, %25, %26, %27, %28, %29, %30, %31, %32, %33, %34, %35}, da, db, 1, 1, 1, 0, 1;\n"
    "mov.b64 da, {%40, %37};\nmov.b64 db, {%41, 8};\n"
    "wgmma.mma_async.sync.aligned.m64n72k16.f32.bf16.bf16 {%0, %1, %2, %3, %4, %5, %6, %7, %8, %9, %10, %11, %12, %13, %14, %15, %16, %17, %18, %19, %20, %21, %22, %23, %24, %25, %26, %27, %28, %29, %30, %31, %32, %33, %34, %35}, da, db, 1, 1, 1, 0, 1;\n"
    "wgmma.commit_group.sync.aligned;\n"
    "@p0 bra.uni D0;\nmov.u32 n, 0;\nW0:\nmbarrier.try_wait.parity.shared::cta.b64 q, [%42], %43;\n@q bra.uni R0;\nadd.u32 n, n, 1;\nsetp.lt.u32 q, n, 8192;\n@q bra.uni W0;\nR0:\n"
    "D0:\n"
    "@p1 bra.uni D1;\nmov.u32 n, 0;\nW1:\nmbarrier.try_wait.parity.shared::cta.b64 q, [%44], %45;\n@q bra.uni R1;\nadd.u32 n, n, 1;\nsetp.lt.u32 q, n, 8192;\n@q bra.uni W1;\nR1:\n"
    "ld.volatile.shared.u32 %36, [%46];\n"
    "D1:\n"
    "}\n"
    : "+f"(d[0]), "+f"(d[1]), "+f"(d[2]), "+f"(d[3]), "+f"(d[4]), "+f"(d[5]), "+f"(d[6]), "+f"(d[7]), "+f"(d[8]),
      "+f"(d[9]), "+f"(d[10]), "+f"(d[11]), "+f"(d[12]), "+f"(d[13]), "+f"(d[14]), "+f"(d[15]), "+f"(d[16]), "+f"(d[17]),
      "+f"(d[18]), "+f"(d[19]), "+f"(d[20]), "+f"(d[21]), "+f"(d[22]), "+f"(d[23]), "+f"(d[24]), "+f"(d[25]), "+f"(d[26]),
      "+f"(d[27]), "+f"(d[28]), "+f"(d[29]), "+f"(d[30]), "+f"(d[31]), "+f"(d[32]), "+f"(d[33]), "+f"(d[34]), "+f"(d[35]),
      "=&r"(v[0])
    : "r"(ahi), "r"(dsc[0]), "r"(dsc[1]), "r"(dsc[2]), "r"(dsc[3]), "r"(bar[0]), "r"(bar[1]), "r"(bar[2]), "r"(bar[3]), "r"(adr[0]) : "memory");
}

DEVI void mbar_init(uint32_t b, int c) { asm volatile("mbarrier.init.shared::cta.b64 [%0], %1;" ::"r"(b), "r"(c)); }
DEVI void mbar_arrive(uint32_t b) { asm volatile("mbarrier.arrive.shared::cta.b64 _, [%0];" ::"r"(b) : "memory"); }
DEVI void mbar_expect(uint32_t b, uint32_t tx) {
  asm volatile("mbarrier.arrive.expect_tx.shared::cta.b64 _, [%0], %1;" ::"r"(b), "r"(tx) : "memory");
}
DEVI void mbar_wait(uint32_t b, uint32_t ph) {
  asm volatile(
      "{\n.reg .pred p;\n.reg .u32 n;\nmov.u32 n, 0;\n"
      "LW:\nmbarrier.try_wait.parity.shared::cta.b64 p, [%0], %1;\n"
      "@p bra LD;\nadd.u32 n, n, 1;\nsetp.lt.u32 p, n, 8192;\n@p bra LW;\nLD:\n}\n" ::"r"(b), "r"(ph)
      : "memory");
}
DEVI void mbar_wait2(uint32_t a, uint32_t pa, uint32_t b, uint32_t pb) {
  asm volatile(
      "{\n.reg .pred p, q;\n.reg .u32 n;\nmov.u32 n, 0;\n"
      "LW:\nmbarrier.try_wait.parity.shared::cta.b64 p, [%0], %1;\nmbarrier.try_wait.parity.shared::cta.b64 q, [%2], %3;\n"
      "and.pred p, p, q;\n@p bra LD;\nadd.u32 n, n, 1;\nsetp.lt.u32 p, n, 8192;\n@p bra LW;\nLD:\n}\n" ::"r"(a), "r"(pa), "r"(b), "r"(pb)
      : "memory");
}
DEVI bool elect() {
  uint32_t el;
  asm volatile("{\n.reg .pred p;\nelect.sync _|p, 0xffffffff;\nselp.u32 %0,1,0,p;\n}\n" : "=r"(el));
  return el;
}
DEVI void bulk_g2s(uint32_t dst, const void* src, uint32_t bytes, uint32_t bar) {
  asm volatile("cp.async.bulk.shared::cluster.global.mbarrier::complete_tx::bytes [%0], [%1], %2, [%3];" ::"r"(dst),
               "l"(src), "r"(bytes), "r"(bar)
               : "memory");
}
DEVI void bulk_g2s_pair(uint32_t dst, const void* src, uint32_t bytes, uint32_t bar) {
  asm volatile("cp.async.bulk.shared::cluster.global.mbarrier::complete_tx::bytes.multicast::cluster [%0], [%1], %2, [%3], %4;" ::"r"(dst),
               "l"(src), "r"(bytes), "r"(bar), "h"((uint16_t)3)
               : "memory");
}
DEVI void mbar_arrive_pair(uint32_t b) {
  asm volatile("mbarrier.arrive.shared::cta.b64 _, [%0];\nmbarrier.arrive.shared::cluster.b64 _, [%1];\n" ::"r"(b), "r"(b ^ 0x1000000u) : "memory");
}
DEVI void cluster_arrive() { asm volatile("barrier.cluster.arrive.relaxed.aligned;" ::: "memory"); }
DEVI void cluster_wait() { asm volatile("barrier.cluster.wait.aligned;" ::: "memory"); }
DEVI void tma3(uint32_t dst, const CUtensorMap* m, int c0, int c1, int c2, uint32_t bar) {
  asm volatile(
      "cp.async.bulk.tensor.3d.shared::cluster.global.mbarrier::complete_tx::bytes [%0], [%1, {%3,%4,%5}], [%2];" ::"r"(dst),
      "l"(m), "r"(bar), "r"(c0), "r"(c1), "r"(c2)
      : "memory");
}
DEVI constexpr uint32_t mkdesc(uint32_t addr, uint32_t lbo) { return ((addr & 0x3FFFF) >> 4) | ((lbo >> 4) << 16); }
DEVI void bar_sync(int id) { asm volatile("bar.sync %0, 128;" ::"r"(id) : "memory"); }
DEVI uint4 ld_msg(const void* p) {
  uint4 v;
  asm volatile("ld.relaxed.gpu.global.v4.u32 {%0,%1,%2,%3}, [%4];" : "=r"(v.x), "=r"(v.y), "=r"(v.z), "=r"(v.w) : "l"(p) : "memory");
  return v;
}
DEVI void st_msg(void* p, uint32_t a, uint32_t b, uint32_t c, uint32_t d) {
  asm volatile("st.relaxed.gpu.global.v4.u32 [%0], {%1,%2,%3,%4};" ::"l"(p), "r"(a), "r"(b), "r"(c), "r"(d) : "memory");
}
DEVI uint4 ld_gen(const void* p) {
  uint4 v;
  asm volatile("ld.relaxed.gpu.v4.u32 {%0,%1,%2,%3}, [%4];" : "=r"(v.x), "=r"(v.y), "=r"(v.z), "=r"(v.w) : "l"(p) : "memory");
  return v;
}
DEVI void st_gen(void* p, uint32_t a, uint32_t b, uint32_t c, uint32_t d) {
  asm volatile("st.relaxed.gpu.v4.u32 [%0], {%1,%2,%3,%4};" ::"l"(p), "r"(a), "r"(b), "r"(c), "r"(d) : "memory");
}
DEVI uint32_t ld_rlx(const void* p) {
  uint32_t v;
  asm volatile("ld.relaxed.gpu.global.u32 %0, [%1];" : "=r"(v) : "l"(p) : "memory");
  return v;
}
DEVI uint2 ld_rlx2(const void* p) {
  uint2 v;
  asm volatile("ld.relaxed.gpu.global.v2.u32 {%0,%1}, [%2];" : "=r"(v.x), "=r"(v.y) : "l"(p) : "memory");
  return v;
}
DEVI void st_rlx(void* p, uint32_t v) { asm volatile("st.relaxed.gpu.global.u32 [%0], %1;" ::"l"(p), "r"(v) : "memory"); }
#define spin_guard(n) if (++n > (1u << 16)) break
DEVI void wait_flags(const uint8_t* p, int word, uint32_t target) {
  uint32_t n = 0;
  p += 4 * word;
  _Pragma("unroll 1") while (__any_sync(0xffffffffu, (int)(ld_rlx(p) - target) < 0)) spin_guard(n);
  asm volatile("fence.acquire.gpu;" ::: "memory");
  asm volatile("fence.proxy.async.global;" ::: "memory");
}
DEVI void bulk_s2g(void* dst, uint32_t src, uint32_t bytes) {
  asm volatile("cp.async.bulk.global.shared::cta.bulk_group [%0], [%1], %2;" ::"l"(dst), "r"(src), "r"(bytes) : "memory");
}
#define ABL 0
DEVI void l2_prefetch(const void* p, uint32_t bytes) { if (!(ABL & 2)) asm volatile("cp.async.bulk.prefetch.L2.global [%0], %1;" ::"l"(p), "r"(bytes) : "memory"); }
DEVI void fence_async_smem() { asm volatile("fence.proxy.async.shared::cta;" ::: "memory"); }
DEVI void tma2(uint32_t dst, const CUtensorMap* m, int c0, int c1, uint32_t bar) {
  asm volatile("cp.async.bulk.tensor.2d.shared::cluster.global.mbarrier::complete_tx::bytes [%0], [%1, {%3,%4}], [%2];" ::"r"(dst),
               "l"(m), "r"(bar), "r"(c0), "r"(c1) : "memory");
}
DEVI void stsm4(uint32_t a, uint32_t r0, uint32_t r1, uint32_t r2, uint32_t r3) {
  asm volatile("stmatrix.sync.aligned.m8n8.x4.shared.b16 [%0], {%1,%2,%3,%4};" ::"r"(a), "r"(r0), "r"(r1), "r"(r2), "r"(r3) : "memory");
}
DEVI void stsm2(uint32_t a, uint32_t r0, uint32_t r1) {
  asm volatile("stmatrix.sync.aligned.m8n8.x2.shared.b16 [%0], {%1,%2};" ::"r"(a), "r"(r0), "r"(r1) : "memory");
}
DEVI uint32_t mbar_test(uint32_t b, uint32_t ph) {
  uint32_t ok;
  asm volatile("{\n.reg .pred p;\nmbarrier.test_wait.parity.shared::cta.b64 p, [%1], %2;\nselp.u32 %0,1,0,p;\n}\n"
               : "=r"(ok) : "r"(b), "r"(ph) : "memory");
  return ok;
}
DEVI void st_rlx2(void* p, uint32_t a, uint32_t b) {
  asm volatile("{\n.reg .b64 v;\nmov.b64 v, {%1,%2};\nst.relaxed.gpu.global.b64 [%0], v;\n}\n" ::"l"(p), "r"(a), "r"(b) : "memory");
}
DEVI float selp(int c, float a, float b) {
  float y;
  asm("{\n.reg .pred p;\nsetp.ne.s32 p, %3, 0;\nselp.f32 %0, %1, %2, p;\n}\n" : "=f"(y) : "f"(a), "f"(b), "r"(c));
  return y;
}
DEVI float ex2(float x) { float y; asm("ex2.approx.ftz.f32 %0, %1;" : "=f"(y) : "f"(x)); return y; }
DEVI float rcp(float x) { float y; asm("rcp.approx.ftz.f32 %0, %1;" : "=f"(y) : "f"(x)); return y; }
DEVI float sqrt_a(float x) { float y; asm("sqrt.approx.ftz.f32 %0, %1;" : "=f"(y) : "f"(x)); return y; }
DEVI void ldsm4t(uint32_t* r, uint32_t a) {
  asm volatile("ldmatrix.sync.aligned.m8n8.x4.trans.shared.b16 {%0,%1,%2,%3}, [%4];"
               : "=r"(r[0]), "=r"(r[1]), "=r"(r[2]), "=r"(r[3]) : "r"(a) : "memory");
}
DEVI void ldsm4(uint32_t* r, uint32_t a) {
  asm volatile("ldmatrix.sync.aligned.m8n8.x4.shared.b16 {%0,%1,%2,%3}, [%4];"
               : "=r"(r[0]), "=r"(r[1]), "=r"(r[2]), "=r"(r[3]) : "r"(a) : "memory");
}
DEVI uint32_t lds16(uint32_t a) {
  uint32_t v;
  asm volatile("ld.shared.u16 %0, [%1];" : "=r"(v) : "r"(a) : "memory");
  return v;
}
DEVI void sts16(uint32_t a, uint32_t x) { asm volatile("st.shared.u16 [%0], %1;" ::"r"(a), "r"(x) : "memory"); }
DEVI uint4 ldg128(const void* p) {
  uint4 v;
  asm volatile("ld.global.nc.v4.u32 {%0,%1,%2,%3}, [%4];" : "=r"(v.x), "=r"(v.y), "=r"(v.z), "=r"(v.w) : "l"(p));
  return v;
}
DEVI uint2 ldg64(const void* p) {
  uint2 v;
  asm volatile("ld.global.nc.v2.u32 {%0,%1}, [%2];" : "=r"(v.x), "=r"(v.y) : "l"(p));
  return v;
}
DEVI uint32_t ldg32(const void* p) {
  uint32_t v;
  asm volatile("ld.global.nc.u32 %0, [%1];" : "=r"(v) : "l"(p));
  return v;
}
DEVI uint4 ldcg128(const void* p) {
  uint4 v;
  asm volatile("ld.global.cg.v4.u32 {%0,%1,%2,%3}, [%4];" : "=r"(v.x), "=r"(v.y), "=r"(v.z), "=r"(v.w) : "l"(p) : "memory");
  return v;
}
DEVI uint2 ldcg64(const void* p) {
  uint2 v;
  asm volatile("ld.global.cg.v2.u32 {%0,%1}, [%2];" : "=r"(v.x), "=r"(v.y) : "l"(p) : "memory");
  return v;
}
DEVI uint32_t ldcg32(const void* p) {
  uint32_t v;
  asm volatile("ld.global.cg.u32 %0, [%1];" : "=r"(v) : "l"(p) : "memory");
  return v;
}
DEVI void stg128(void* p, uint32_t a, uint32_t b, uint32_t c, uint32_t d) {
  asm volatile("st.global.v4.u32 [%0], {%1,%2,%3,%4};" ::"l"(p), "r"(a), "r"(b), "r"(c), "r"(d) : "memory");
}
DEVI void stg32(void* p, uint32_t a) { asm volatile("st.global.u32 [%0], %1;" ::"l"(p), "r"(a) : "memory"); }
DEVI uint4 lds128(uint32_t a) {
  uint4 v;
  asm volatile("ld.shared.v4.u32 {%0,%1,%2,%3}, [%4];" : "=r"(v.x), "=r"(v.y), "=r"(v.z), "=r"(v.w) : "r"(a) : "memory");
  return v;
}
DEVI uint2 lds64(uint32_t a) {
  uint2 v;
  asm volatile("ld.shared.v2.u32 {%0,%1}, [%2];" : "=r"(v.x), "=r"(v.y) : "r"(a) : "memory");
  return v;
}
DEVI uint32_t lds32(uint32_t a) {
  uint32_t v;
  asm volatile("ld.shared.u32 %0, [%1];" : "=r"(v) : "r"(a) : "memory");
  return v;
}
DEVI void lds64f_if(bool p, float& a, float& b, uint32_t addr) {
  asm volatile("{\n.reg .pred p;\nsetp.ne.u32 p, %3, 0;\n@p ld.shared.v2.f32 {%0,%1}, [%2];\n}\n"
               : "+f"(a), "+f"(b) : "r"(addr), "r"((uint32_t)p) : "memory");
}
DEVI float ldsf(uint32_t a) { return __uint_as_float(lds32(a)); }
DEVI void sts128(uint32_t a, uint32_t x, uint32_t y, uint32_t z, uint32_t w) {
  asm volatile("st.shared.v4.u32 [%0], {%1,%2,%3,%4};" ::"r"(a), "r"(x), "r"(y), "r"(z), "r"(w) : "memory");
}
DEVI void sts64(uint32_t a, uint32_t x, uint32_t y) { asm volatile("st.shared.v2.u32 [%0], {%1,%2};" ::"r"(a), "r"(x), "r"(y) : "memory"); }
DEVI void sts32(uint32_t a, uint32_t x) { asm volatile("st.shared.u32 [%0], %1;" ::"r"(a), "r"(x) : "memory"); }
DEVI void stsf(uint32_t a, float x) { sts32(a, __float_as_uint(x)); }
DEVI uint32_t packbf(float lo, float hi) {
  uint32_t r;
  asm("cvt.rn.bf16x2.f32 %0, %1, %2;" : "=r"(r) : "f"(hi), "f"(lo));
  return r;
}
DEVI uint32_t nz(uint32_t w) { uint32_t y; asm("max.u32 %0, %1, 1;" : "=r"(y) : "r"(w)); return y; }
DEVI float blo(uint32_t w) { return __uint_as_float(w << 16); }
DEVI float bhi(uint32_t w) { return __uint_as_float(w & 0xffff0000u); }
DEVI float rbf(float x) { return __uint_as_float(packbf(0.f, x)); }
DEVI float shx(float v, int m) { return __shfl_xor_sync(0xffffffffu, v, m); }
DEVI float quad_sum(float v) { v += shx(v, 1); v += shx(v, 2); return v; }
DEVI uint32_t movm(uint32_t a) {
  uint32_t d;
  asm volatile("movmatrix.sync.aligned.m8n8.trans.b16 %0, %1;" : "=r"(d) : "r"(a));
  return d;
}
DEVI void mma16(float* d, uint32_t a0, uint32_t a1, uint32_t a2, uint32_t a3, uint32_t b0, uint32_t b1) {
  asm("mma.sync.aligned.m16n8k16.row.col.f32.bf16.bf16.f32 {%0,%1,%2,%3},{%4,%5,%6,%7},{%8,%9},{%0,%1,%2,%3};"
      : "+f"(d[0]), "+f"(d[1]), "+f"(d[2]), "+f"(d[3])
      : "r"(a0), "r"(a1), "r"(a2), "r"(a3), "r"(b0), "r"(b1));
}
DEVI void mma8z(float* d, uint32_t a0, uint32_t a1, uint32_t b0) {
  asm("mma.sync.aligned.m16n8k8.row.col.f32.bf16.bf16.f32 {%0,%1,%2,%3},{%4,%5},{%6},{%7,%7,%7,%7};"
      : "=f"(d[0]), "=f"(d[1]), "=f"(d[2]), "=f"(d[3])
      : "r"(a0), "r"(a1), "r"(b0), "f"(0.f));
}
DEVI void mma8(float* d, uint32_t a0, uint32_t a1, uint32_t b0) {
  asm("mma.sync.aligned.m16n8k8.row.col.f32.bf16.bf16.f32 {%0,%1,%2,%3},{%4,%5},{%6},{%0,%1,%2,%3};"
      : "+f"(d[0]), "+f"(d[1]), "+f"(d[2]), "+f"(d[3])
      : "r"(a0), "r"(a1), "r"(b0));
}
DEVI void mma16z(float* d, uint32_t a0, uint32_t a1, uint32_t a2, uint32_t a3, uint32_t b0, uint32_t b1) {
  asm("mma.sync.aligned.m16n8k16.row.col.f32.bf16.bf16.f32 {%0,%1,%2,%3},{%4,%5,%6,%7},{%8,%9},{%10,%10,%10,%10};"
      : "=f"(d[0]), "=f"(d[1]), "=f"(d[2]), "=f"(d[3])
      : "r"(a0), "r"(a1), "r"(a2), "r"(a3), "r"(b0), "r"(b1), "f"(0.f));
}
DEVI void mma16a(float* d, const uint32_t* a, uint32_t b0, uint32_t b1) { mma16(d, a[0], a[1], a[2], a[3], b0, b1); }
DEVI float ln_sd(float var) { return rbf(sqrt_a(rbf(rbf(var) + kEps))); }
DEVI int fkey(float f) { int i = __float_as_int(f); return i ^ ((i >> 31) & 0x7fffffff); }
DEVI float sigmoidf(float x) { return rcp(1.f + ex2(-1.4426950408889634f * x)); }

DEVI uint32_t probe_stage(uint32_t pa) { return lds32(pa); }
DEVI void check_stage(uint32_t pv, uint32_t fa, const uint8_t* src) {
  if (__any_sync(0xffffffffu, pv == 0)) {
    uint32_t n = 0, tid;
    asm volatile("mov.u32 %0, %%tid.x;" : "=r"(tid));
    const uint32_t fo = (tid & 96) * 8 + (tid & 16) * 64 + (tid & 15) * 16;
    fa += fo; src += fo;
#pragma unroll 1
    for (uint32_t o = 0; o < 8192;) {
      const uint4 v = ld_msg(src + o);
      sts128(fa + o, v.x, v.y, v.z, v.w);
      if (!__any_sync(0xffffffffu, min(min(v.x, v.y), min(v.z, v.w)) == 0) || ++n > (1u << 16)) o += 2048;
    }
    fence_async_smem();
    __syncwarp();
  }
}

struct Params {
  const uint8_t *x, *wqkv, *wo, *wr, *wg, *wu, *wd;
  uint8_t* out;
  Scratch* g;
};

struct Maps { CUtensorMap wq, x, wo, xr, wg, wu, out; };
#define QPRE 2
#define FDEPTH 2
#define PFSTART 700
#define PFPRE 0
#define PFPER 3
#define PFNS 200
#define XSTART 100
#define XSTEP 300
#define PKSTEP 350
#define WPOLL 300
#define CSROUND 0
#define XLROUND 0
#define CLNS 20
#define FSTART 4000
#define XLSTART 3000
#define WGAP0 0
#define XGAP 150
#define WEARLY 1

__global__ void __cluster_dims__(2, 1, 1) __launch_bounds__(512, 1) fused_kernel(const Params p, const __grid_constant__ Maps tm) {
  extern __shared__ __align__(1024) uint8_t smem_raw[];
  constexpr uint32_t sbd = 1024;
  int cta;
  uint32_t rank;
  {
    asm volatile("mov.u32 %0, %%cluster_ctarank;" : "=r"(rank));
    const int c = blockIdx.x >> 1, t = c - 4, u = c - 36, uq = (u * 37) >> 8;
    const int gpc = c < 4 ? 0 : c < 36 ? t & 7 : 1 + u - 7 * uq, idx = c < 4 ? 4 + c : c < 36 ? t >> 3 : 4 + uq;
    cta = __shfl_sync(0xffffffffu, (2 * gpc + (int)rank) * 8 + idx, 0);
  }
  const uint32_t sb = sbd | (rank << 24);
  if ((uint32_t)__cvta_generic_to_shared(smem_raw) != sb) return;
  if (threadIdx.x < 27) asm volatile("prefetch.global.L2 [%0];" ::"l"(p.wqkv + blockIdx.x * 3456 + threadIdx.x * 128));
  const int m = cta >> 3, r = cta & 7;
  const int warp = __shfl_sync(0xffffffffu, (int)(threadIdx.x >> 5), 0);
  const int lane = threadIdx.x & 31;
  uint8_t* const gb = reinterpret_cast<uint8_t*>(p.g);
  auto pack = [&]() -> uint32_t {
    const uint32_t t0 = clock();
    const uint32_t tp = sb + SM_WD + warp * 2304, bar = sb + SM_PART + 8 * warp;
    uint8_t* flag = GA(flagP, (12 * r + warp) * 128 + 4 * m);
    if (warp > 1) {
      asm volatile("bar.sync 4, 512;" ::: "memory");
      cluster_arrive();
      while ((uint32_t)clock() - t0 < (warp - 1) * PKSTEP) {}
    }
    if (elect()) {
      mbar_init(bar, 1);
      asm volatile("fence.mbarrier_init.release.cluster;" ::: "memory");
      mbar_expect(bar, 2304);
      if (warp < 9) tma3(tp, &tm.wq, 72 * r, 64 * warp + 8 * (m >> 1), m & 1, bar);
      else tma2(tp, &tm.wo, 72 * r, 192 * (warp - 9) + 24 * (m >> 1) + 8 * (m & 1), bar);
    }
    __syncwarp();
    if (lane == 0) st_rlx(flag, 0);
    if (warp <= 1) { asm volatile("bar.sync 4, 512;" ::: "memory"); cluster_arrive(); }
    mbar_wait(sb + B_EP, 0);
    const uint32_t epoch = lds32(sb + SM_EP);
    uint8_t* dst = GC(wpack, (r * 12 + warp) * WSTAGE + (27 * (m >> 1) + 14 * (m & 1)) * 128 + lane * 16);
    mbar_wait(bar, 0);
#pragma unroll
    for (int i = 0; i < 4; i++) {
      const int u = 4 * i + (lane >> 3) + 5 * (m & 1);
      const uint4 x = lds128(tp + (lane & 7) * 144 + u * 16 + (u >= 9 ? 1008 : 0));
      if (u < 14 + 4 * (m & 1)) stg128(dst + 512 * i, nz(x.x), nz(x.y), nz(x.z), nz(x.w));
    }
    if (lane == 0) st_rlx(flag, epoch);
    fence_async_smem();
    __syncwarp();
    if (elect()) asm volatile("mbarrier.inval.shared::cta.b64 [%0];" ::"r"(bar) : "memory");
    cluster_wait();
    return epoch;
  };

  if (warp >= 12) {
    asm volatile("setmaxnreg.dec.sync.aligned.u32 24;");
    uint32_t e0 = 0;
    if (elect()) {
#pragma unroll
      for (int i = 0; i < NBAR; i++)
        if (warp - 12 == (i * 4) / NBAR)
          mbar_init(sb + SM_BAR + 8 * i, i < 4 ? 1 : i < 8 ? 16 : i < 16 ? 2 : i < NBAR4 ? 4 : 1);
      asm volatile("fence.mbarrier_init.release.cluster;" ::: "memory");
    }
    __syncwarp();
    if (warp == 15) asm volatile("bar.arrive 4, 512;" ::: "memory");
    else asm volatile("bar.sync 4, 512;" ::: "memory");
    cluster_arrive();
    if (warp == 15) e0 = ld_rlx(GA(epoch, 32 * cta));
    if (warp == 12) {
      mbar_wait(sb + B_EP, 0);
      cluster_wait();
      const uint32_t epoch = lds32(sb + SM_EP);
      const uint32_t half = (m & 1) * (WSTAGE / 2);
      const uint8_t* src = GC(wpack, r * 12 * WSTAGE + half);
      __nanosleep(WPOLL);
#pragma unroll 1
      for (int g = 0; g < 24; g++) {
        const uint32_t slot = g & 3;
        if (g < 12) wait_flags(GA(flagP, (12 * r + g) * 128), lane & 15, epoch);
        if (g == 0) TRL(3, 0);
        if (g >= 4) mbar_wait(sb + B_WEMPTY + 8 * slot, ((g >> 2) - 1) & 1);
        if (elect()) {
          const uint32_t bar = sb + (g < 12 ? B_WL : B_WFULL) + 8 * slot;
          mbar_expect(bar, WSTAGE);
          bulk_g2s_pair(sb + SM_W + slot * WSTAGE + half, src + (g >= 12 ? g - 12 : g) * WSTAGE, WSTAGE / 2, bar);
        }
      }
    } else if (warp <= 14) {
      const int w = warp - 13;
      const uint32_t full = sb + B_XFULL + 32 * w, empty = sb + B_XEMPTY + 32 * w, ring = sb + SM_X + w * 4 * XSTAGE;
      mbar_wait(sb + B_EP, 0);
      cluster_wait();
      const uint32_t epoch = lds32(sb + SM_EP);
      if (lane < 4) st_rlx(GA(flagX, 128 * (2 * m + w) + 16 * r + 4 * lane), epoch * 4);
#pragma unroll 1
      for (int gemm = 0; gemm < 4; gemm++) {
        const uint8_t* src = GC(act, (gemm - 1) * ACT + (2 * m + w) * 73728);
        if (gemm & 1) {
          mbar_wait(empty, 0);
          if (elect()) {
            mbar_expect(sb + B_RES + 8 * w, 9216);
            if (gemm == 1) tma3(ring, &tm.xr, 72 * r, w, m * 64, sb + B_RES + 8 * w);
            else bulk_g2s(ring, GC(act, ACT + (2 * m + w) * 73728 + r * 9216), 9216, sb + B_RES + 8 * w);
          }
        }
        if (gemm > 0) {
          mbar_wait(gemm & 1 ? sb + B_RC + 8 * w : empty, gemm & 1 ? gemm >> 1 : 1);
          TRL(3, 11 + w * 4 + gemm);
          wait_flags(GA(flagX, 128 * (2 * m + w)), lane, epoch * 4 + gemm);
          TRL(3, 1 + w * 4 + gemm);
        }
        if (gemm & 1) {
          if (elect()) {
#pragma unroll
            for (int s = 0; s < 9; s++) {
              if (s == 4) {
                mbar_wait(sb + B_RC + 8 * (w ^ 1), gemm >> 1);
                mbar_expect(sb + B_XE + 8 * w, XSTAGE);
                bulk_g2s(sb + SM_W + w * XSTAGE, src + 4 * XSTAGE, XSTAGE, sb + B_XE + 8 * w);
                continue;
              }
              const int sl = s < 4 ? s : s - 5;
              if (s >= 5) mbar_wait(empty + 8 * sl, s == 5);
              mbar_expect(full + 8 * sl, XSTAGE);
              bulk_g2s(ring + sl * XSTAGE, src + s * XSTAGE, XSTAGE, full + 8 * sl);
              mbar_arrive(full + 8 * sl);
            }
            mbar_wait(empty, 0);
            mbar_arrive(full);
            mbar_arrive(full);
          }
          __syncwarp();
          continue;
        }
        bool gate = gemm == 2;
#pragma unroll 1
        for (int s = 0; s < (gemm == 2 ? 11 : 9); s++) {
          const uint32_t slot = s & 3;
          if (gemm == 0 && s < 4) __nanosleep(s ? XSTEP : XSTART);
          if (gemm == 2 && s > 0 && s < 4) __nanosleep(XGAP);
          if (s >= 4) mbar_wait(empty + 8 * slot, s >> 3);
          const bool hold = gate && s >= 4 && mbar_test(sb + B_WANT, 0);
          if (lane == 0 && !hold && (gemm != 2 || (s & ~1) != 2)) mbar_arrive(full + 8 * (gemm == 2 && s >= 4 ? (s - 2) & 3 : slot));
          if (s < 9 && elect()) {
            mbar_expect(full + 8 * slot, XSTAGE);
            if (gemm == 0) tma3(ring + slot * XSTAGE, &tm.x, s * 64, w, m * 64, full + 8 * slot);
            else bulk_g2s(ring + slot * XSTAGE, src + s * XSTAGE, XSTAGE, full + 8 * slot);
          }
          if (hold) {
            mbar_wait(sb + B_DONE, 0);
            gate = false;
            if (lane == 0) mbar_arrive(full + 8 * ((s - 2) & 3));
          }
        }
      }
    } else {
      const uint32_t epoch = e0 + 1;
      if (lane == 0) {
        sts32(sb + SM_EP, epoch);
        mbar_arrive(sb + B_EP);
      }
      __syncwarp();
      cluster_wait();
      int pi = lane;
      auto prefetch = [&]() {
        const uint8_t* pp = pi < 648 ? ((cta & 1) ? p.wu : p.wg) + (uint32_t)(((pi / 72) * 63 + (cta >> 1)) * 9216 + pi * 128)
                                     : p.wd + (uint32_t)((cta * 324 + pi - 648) * 128);
        if (pi < 972 && !(ABL & 2)) asm volatile("prefetch.global.L2 [%0];" ::"l"(pp));
        pi += 32;
      };
      __nanosleep(PFSTART);
#pragma unroll 1
      for (int i = 0; i < PFPRE; i++) { prefetch(); __nanosleep(PFNS); }
      uint32_t ph = 0;
#pragma unroll 1
      for (int g = 0; g < 12; g++) {
        const uint32_t slot = g & 3;
#pragma unroll 1
        for (int n = 0; n < 4096; n++) {
          mbar_wait(sb + B_WL + 8 * slot, (ph >> slot) & 1);
          ph ^= 1 << slot;
          const uint32_t a = sb + SM_W + slot * WSTAGE + lane * 128 + (lane & 3) * 32 + (lane >> 2) * 4;
          uint32_t mn = lds32(a + (lane < 24 ? 6 * 4096 : 0));
#pragma unroll
          for (int u = 0; u < 6; u++) mn = min(mn, lds32(a + u * 4096));
          if (!__any_sync(0xffffffffu, mn == 0) || (ABL & 32)) break;
          fence_async_smem();
          __syncwarp();
          if (elect()) {
            mbar_expect(sb + B_WL + 8 * slot, WSTAGE);
            bulk_g2s(sb + SM_W + slot * WSTAGE, GC(wpack, (r * 12 + g) * WSTAGE), WSTAGE, sb + B_WL + 8 * slot);
          }
        }
        if (lane == 0) mbar_arrive(sb + B_WFULL + 8 * slot);
#pragma unroll 1
        for (int i = 0; i < PFPER; i++) prefetch();
      }
      TRL(3, 22);
      mbar_wait(sb + B_FD, 0);
      TRL(3, 20);
      if (elect()) {
        mbar_expect(sb + B_WD, (ABL & 64) ? 0 : 41472);
#pragma unroll 4
        for (int i = 0; i < 36; i++)
          if (!(ABL & 64)) bulk_g2s(sb + SM_WD + i * WDP, p.wd + (uint32_t)(cta * 36 + i) * 1152u, 1152, sb + B_WD);
      }
      __syncwarp();
      TRL(3, 21);
      {
        const uint32_t epoch = e0, h = (lane >> 1) * 128 + (lane & 1) * 16;
        mbar_wait(sb + B_OS, 0);
#pragma unroll 1
        for (int i = cta; i < 1296; i += 128) { stg128(GC(wpack, i * 2048 + (lane & 6) * 16 + h), 0, 0, 0, 0); __nanosleep(CLNS); }
#pragma unroll 1
        for (int i = 0; i < 5; i++) {
          stg128(GC(halo, (cta * 5 + i) * 2048 + h), 0, 0, 0, 0);
          if (i < 4 || lane < 16) stg128(GC(candrow, cta * 2304 + i * 512 + lane * 16), 0, 0, 0, 0);
          stg128(GC(act, (cta * 27 + i) * 2048 + 96 + h), 0, 0, 0, 0);
          __nanosleep(CLNS);
        }
        mbar_wait(sb + B_OS, 1);
#pragma unroll 1
        for (int i = 5; i < 27; i++) { stg128(GC(act, (cta * 27 + i) * 2048 + 96 + h), 0, 0, 0, 0); __nanosleep(CLNS); }
      }
      TRL(3, 23);
    }
  } else if (warp >= 8) {
    asm volatile("setmaxnreg.inc.sync.aligned.u32 200;");
    const int sw = warp - 8, s = threadIdx.x - 256;
    const uint32_t t0 = clock();
    const uint32_t epoch = pack();
    TR(2, 0);
    auto ffn_round = [&](int u) {
      const uint32_t bar = sb + B_FF + 8 * (u % FDEPTH), dst = sb + SM_WD + (u % FDEPTH) * FSLOT;
      if (ABL & 4) { mbar_arrive(bar); return; }
      mbar_expect(bar, 12288);
      tma2(dst, &tm.wg, ((cta * 72) >> 5) << 4, 64 * u, bar);
      tma2(dst + FSLOT / 2, &tm.wu, ((cta * 72) >> 5) << 4, 64 * u, bar);
    };
    const int xi = 8 * r + 4 * (sw >> 1) + (lane >> 3);
    uint4 xv[9];
    uint32_t wr[9];
        {
          const uint8_t* xsrc = p.x + (uint32_t)((128 * m + 2 * xi + (sw & 1)) * 1152 + (lane & 7) * 16);
#pragma unroll
          for (int u = 0; u < 9; u++) xv[u] = ldg128(xsrc + u * 128);
#pragma unroll
          for (int u = 0; u < 9; u++) wr[u] = sw == 0 ? ldg32(p.wr + 128 * u + 4 * lane) : 0u;
        }
    {
      asm volatile("bar.sync 15, 384;" ::: "memory");
      const int u = (s >> 3) + 5 * (m & 1);
      uint4 v[9];
#pragma unroll
      for (int g = 0; g < 9; g++) v[g] = lds128(sb + SM_WD + g * 2304 + u * 16 + (u >= 9 ? 1008 : 0) + (s & 7) * 144);
      fence_async_smem();
      bar_sync(3);
      float a[8] = {};
#pragma unroll
      for (int g = 0; g < 9; g++) {
        a[0] += blo(v[g].x); a[1] += bhi(v[g].x); a[2] += blo(v[g].y); a[3] += bhi(v[g].y);
        a[4] += blo(v[g].z); a[5] += bhi(v[g].z); a[6] += blo(v[g].w); a[7] += bhi(v[g].w);
      }
      const bool b4 = s & 4, b2 = s & 2;
      float b[4];
#pragma unroll
      for (int e = 0; e < 4; e++) b[e] = (b4 ? a[4 + e] : a[e]) + shx(b4 ? a[e] : a[4 + e], 4);
      float c0 = (b2 ? b[2] : b[0]) + shx(b2 ? b[0] : b[2], 2), c1 = (b2 ? b[3] : b[1]) + shx(b2 ? b[1] : b[3], 2);
      c0 += shx(c0, 1); c1 += shx(c1, 1);
      if (!(s & 1) && (s >> 3) < 14 - (m & 1))
        st_rlx2(GA(colpart, (8 * r + (m >> 1)) * 864 + 14 * (m & 1) * 32 + 4 * s), __float_as_uint(c0), (__float_as_uint(c1) & ~15u) | (epoch & 15));
      TR(2, 1);
    }
    if (sw == 0) {
      while ((uint32_t)clock() - t0 < FSTART) {}
      if (elect()) {
#pragma unroll
        for (int u = 0; u < FDEPTH; u++) ffn_round(u);
      }
      __syncwarp();
    }
        {
          float sum = 0.f;
#pragma unroll
          for (int u = 0; u < 9; u++)
            sum += (blo(xv[u].x) + bhi(xv[u].x)) + (blo(xv[u].y) + bhi(xv[u].y)) + (blo(xv[u].z) + bhi(xv[u].z)) + (blo(xv[u].w) + bhi(xv[u].w));
          sum += shx(sum, 1); sum += shx(sum, 2); sum += shx(sum, 4);
          const float mu = sum * (1.f / kD);
          float q = 0.f;
#pragma unroll
          for (int u = 0; u < 9; u++) {
            const uint32_t ww[4] = {xv[u].x, xv[u].y, xv[u].z, xv[u].w};
#pragma unroll
            for (int e = 0; e < 4; e++) {
              const float d0 = blo(ww[e]) - mu, d1 = bhi(ww[e]) - mu;
              q = fmaf(d0, d0, q); q = fmaf(d1, d1, q);
            }
          }
          q += shx(q, 1); q += shx(q, 2); q += shx(q, 4);
          const float rho = rcp(ln_sd(q * (1.f / kD)));
          if ((lane & 7) == 0) st_msg(GA(stats0, 16 * (128 * m + 64 * (sw & 1) + xi)), __float_as_uint(rho), __float_as_uint(mu), 0, epoch);
          if (sw == 0) {
            float wsum = 0.f;
#pragma unroll
            for (int u = 0; u < 9; u++) wsum += blo(wr[u]) + bhi(wr[u]);
#pragma unroll
            for (int o = 1; o < 32; o <<= 1) wsum += shx(wsum, o);
            if (lane == 0) stsf(sb + SM_WSUM, wsum);
          }
          TR(2, 3);
        }
    uint32_t WF[9][4][4];
    {
      const int g = lane >> 2, t = lane & 3;
      const uint32_t c0 = (cta * 72) & 31, ra = 2 * (lane & 6) + (lane & 1) + 2 * ((lane >> 4) ^ ((lane >> 2) & 1));
      const uint32_t fa = sb + SM_WD + (16 * sw + ra) * 128 + ((((c0 + 8) >> 4) + ((lane >> 3) & 1)) << 4);
      const uint32_t fa0 = fa ^ ((ra & 7) << 4), fa1 = (fa + 32) ^ ((ra & 7) << 4);
      const uint32_t rl = 2 * (g & 6) + (g & 1) + 2 * (g >> 2);
      const uint32_t fl = sb + SM_WD + 16 * sw * 128 + (t >> 1) * (FSLOT / 2) + c0 + 64 * (~cta & 1) + 4 * (t & 1);
      const uint32_t fl0 = (fl + rl * 128) ^ ((rl & 7) << 4), fl1 = (fl + (rl ^ 2) * 128) ^ (((rl ^ 2) & 7) << 4);
#pragma unroll
      for (int i = 0; i < 9; i++) {
        mbar_wait(sb + B_FF + 8 * (i % FDEPTH), (i / FDEPTH) & 1);
#pragma unroll
        for (int e = 0; e < 4; e++) ldsm4t(WF[i][e], ((e & 1) ? fa1 : fa0) + (e >> 1) * (FSLOT / 2) + (i % FDEPTH) * FSLOT);
        const uint32_t v0 = lds32(fl0 + (i % FDEPTH) * FSLOT), v1 = lds32(fl1 + (i % FDEPTH) * FSLOT);
        if (i + FDEPTH < 9 || i == 8) {
          fence_async_smem();
          bar_sync(3);
          if (sw == 0 && elect()) {
            if (i < 8) ffn_round(i + FDEPTH);
            else mbar_arrive(sb + B_FD);
          }
        }
        sts64(sb + SM_LEFT + i * 1024 + s * 8, movm(v0), movm(v1));
        if (i == CSROUND) {
          TR(2, 21);
          float c0, c1;
          uint4 s0;
          uint32_t nc = 0;
          _Pragma("unroll 1") while (true) {
            s0 = ld_msg(GA(stats0, 16 * (128 * m + s)));
            uint32_t bad = s0.w != epoch;
            c0 = 0.f; c1 = 0.f;
#pragma unroll
            for (int mm = 0; mm < 8; mm++) {
              const uint2 v = ld_rlx2(GA(colpart, 8 * 864 * r + 8 * min(s, 107)) + mm * 864);
              c0 += __uint_as_float(v.x); c1 += __uint_as_float(v.y & ~15u);
              bad |= v.y ^ epoch;
            }
            if (!__any_sync(0xffffffffu, bad & 15)) break;
            spin_guard(nc);
          }
          if (s < 108) {
            const uint32_t hi = packbf(c0, c1);
            sts32(sb + SM_COLSUM + 32 * (s >> 2) + 4 * (s & 3), hi);
            sts32(sb + SM_COLSUM + 32 * (s >> 2) + 4 * (s & 3) + 16, packbf(c0 - blo(hi), c1 - bhi(hi)));
          }
          sts32(sb + SM_ROWC + 4 * s, s0.x);
          sts64(sb + SM_ROWM + 8 * s, s0.y, __float_as_uint(1.f));
          fence_async_smem();
          __syncwarp();
          if (lane == 0) mbar_arrive(sb + B_COLSUM);
          TR(2, 13);
        }
      }
      TR(2, 4);
    }
    {
      const uint32_t y = epoch * 2 - 1;
      st_msg(GA(ypart, (s >> 1) * 4096 + cta * 32 + (s & 1) * 16), y, y, y, y);
      if (s < 16) {
        st_msg(GA(ypart, (64 + (s >> 1)) * 4096 + cta * 32 + (s & 1) * 16), y, y, y, y);
        st_rlx(GA(fixmsg, 1024 * r + 64 * m + 4 * s), epoch - 1);
      }
      if (s < 64 && cta < 72) st_rlx(GA(x2msg, (s >> 3) * 2304 + 32 * cta + 4 * (s & 7)), epoch - 1);
    }
#pragma unroll 1
    for (int L = 0; L < 2; L++) {
      const uint32_t tag = epoch * 2 + L;
      int s0 = __shfl_sync(0xffffffffu, (int)threadIdx.x + L, threadIdx.x & 31) - L - 256;
#define RELANE asm volatile("" : "+r"(s0)); const int s = s0, lane = s & 31, g = lane >> 2, t = lane & 3; (void)g; (void)t
      RELANE;
      const uint8_t* crow = GC(candrow, L * 128 * 1152);
      const uint8_t* cptr = GA(cand, (8 * L + r) * 2048 + 16 * s);
      asm volatile("" : "+l"(crow), "+l"(cptr));
      mbar_wait2(sb + B_WD, 0, sb + B_EPI, L);
      uint32_t win;
      {
        uint32_t c, n = 0;
        _Pragma("unroll 1") while (true) {
          c = ld_rlx(cptr) ^ (epoch & 0x7f);
          if (!__any_sync(0xffffffffu, c & 0x7f)) break;
          spin_guard(n);
        }
        const int wm = __reduce_max_sync(0xffffffffu, (int)(c | s));
        if (lane == 0) sts32(sb + SM_RED + 4 * sw, wm);
        bar_sync(3);
        const uint4 v = lds128(sb + SM_RED);
        win = max(max((int)v.x, (int)v.y), max((int)v.z, (int)v.w));
      }
      crow += (win & 127) * 1152;
      if (s == 0) {
        if (L == 0 && WEARLY) mbar_arrive(sb + B_WANT);
        sts32(sb + SM_SEL + 4 * L, win & 0x7ff);
        mbar_arrive(sb + B_IDX + 8 * L);
      }
      TR(2, 5 + 10 * L);
      uint2 xw[9];
      {
        if (sw < 3) {
          uint4 v;
          uint32_t n = 0;
          _Pragma("unroll 1") while (true) {
            v = ld_msg(crow + 16 * min(s, 71));
            if (!__any_sync(0xffffffffu, min(min(v.x, v.y), min(v.z, v.w)) == 0)) break;
            spin_guard(n);
          }
          if (s < 72) sts128(sb + SM_PART + 16 * s, v.x, v.y, v.z, v.w);
        }
        bar_sync(3);
#pragma unroll
        for (int i = 0; i < 9; i++) xw[i] = lds64(sb + SM_PART + 128 * i + 32 * sw + 8 * t);
      }
      if (L == 0 && !WEARLY && s == 0) mbar_arrive(sb + B_WANT);
      TR(2, 6 + 10 * L);
      {
        float a[4][4] = {}, al[4] = {};
#pragma unroll
        for (int i = 0; i < 9; i++) {
          const uint2 wl = lds64(sb + SM_LEFT + s * 8 + i * 1024);
#pragma unroll
          for (int e = 0; e < 4; e++) mma16a(a[e], WF[i][e], xw[i].x, xw[i].y);
          mma8(al, wl.x, wl.y, (g & 1) ? xw[i].y : xw[i].x);
        }
        bar_sync(3);
        const uint32_t pp = sb + SM_PART + ((t >> 1) * 36 + 16 * (t & 1) + g + 4 * (cta & 1)) * 16 + 4 * sw;
        stsf(pp, selp(t & 2, selp(t & 1, a[3][0], a[2][0]), selp(t & 1, a[1][0], a[0][0])));
        stsf(pp + 128, selp(t & 2, selp(t & 1, a[3][2], a[2][2]), selp(t & 1, a[1][2], a[0][2])));
        stsf(sb + SM_PART + ((g >> 2) * 36 + 32 * (~cta & 1) + (g & 3)) * 16 + 4 * sw, al[0] + al[3]);
      }
      {
        RELANE;
        const uint32_t wa = sb + SM_WD + 288 * sw + ((lane >> 3) & 1) * 16 + ((lane & 7) + 8 * (lane >> 4)) * WDP;
        const uint32_t wb = sb + SM_WD + 288 * sw + ((lane >> 3) & 1) * 16 + (32 + (lane & 3)) * WDP;
        uint32_t f[4][4];
#pragma unroll
        for (int u = 0; u < 4; u++) ldsm4t(f[u], wa + 32 * (u & 1) + (u >> 1) * 16 * WDP);
        bar_sync(3);
        {
          float hv[2];
#pragma unroll
          for (int e = 0; e < 2; e++) {
            const uint32_t pp = sb + SM_PART + 16 * (e ? 32 + t : lane);
            const uint4 pg = lds128(pp), pu = lds128(pp + 576);
            const float gp = rbf((__uint_as_float(pg.x) + __uint_as_float(pg.y)) + (__uint_as_float(pg.z) + __uint_as_float(pg.w)));
            const float u = rbf((__uint_as_float(pu.x) + __uint_as_float(pu.y)) + (__uint_as_float(pu.z) + __uint_as_float(pu.w)));
            hv[e] = rbf(gp * sigmoidf(gp)) * u;
          }
          const uint32_t hh = packbf(hv[0], hv[1]);
          sts16(sb + SM_H + 80 * sw + 2 * lane, hh);
          sts16(sb + SM_H + 80 * sw + 64 + 2 * t, hh >> 16);
          __syncwarp();
        }
        TR(2, 7 + 10 * L);
        uint32_t hp[5];
#pragma unroll
        for (int i = 0; i < 4; i++) hp[i] = lds32(sb + SM_H + 80 * sw + 16 * i + 4 * t);
        hp[4] = lds32(sb + SM_H + 80 * sw + 64 + 4 * (t & 1));
        float Y[4] = {}, Z[4] = {}, C[4] = {};
        {
          uint32_t e0[4], e1[4], e2[4];
          const uint32_t wq = wb + 32 * (((lane >> 2) & 1) + 2 * (lane >> 4));
          ldsm4t(e0, wq); ldsm4t(e1, wq + 128); ldsm4t(e2, wb + 256);
          mma16a(Y, e0, g == (t >> 1) ? hp[4] : 0u, g == 2 + (t >> 1) ? hp[4] : 0u);
          mma16a(Z, e1, g == 4 + (t >> 1) ? hp[4] : 0u, g == 6 + (t >> 1) ? hp[4] : 0u);
          mma8(C, e2[0], e2[1], t < 2 ? hp[4] : 0u);
        }
#pragma unroll
        for (int u = 0; u < 4; u++) {
          const uint32_t wn = wa + 64 * (u + 1);
          const bool p0 = g == 2 * u, p1 = g == 2 * u + 1;
          mma16a(Y, f[0], p0 ? hp[0] : 0u, p0 ? hp[1] : 0u);
          mma16a(Z, f[1], p1 ? hp[0] : 0u, p1 ? hp[1] : 0u);
          ldsm4t(f[0], wn);
          if (u < 3) ldsm4t(f[1], wn + 32);
          mma16a(Y, f[2], p0 ? hp[2] : 0u, p0 ? hp[3] : 0u);
          mma16a(Z, f[3], p1 ? hp[2] : 0u, p1 ? hp[3] : 0u);
          ldsm4t(f[2], wn + 16 * WDP);
          if (u < 3) ldsm4t(f[3], wn + 32 + 16 * WDP);
        }
        mma16a(C, f[0], hp[0], hp[1]);
        mma16a(C, f[2], hp[2], hp[3]);
#pragma unroll
        for (int e = 0; e < 4; e++) Y[e] += Z[e];
        const uint32_t t4 = tag & 15;
        {
          uint8_t* yo = GA(ypart, (18 * sw + 4 * t) * 4096 + cta * 32 + 4 * g);
#pragma unroll
          for (int e = 0; e < 4; e++) st_rlx(yo + (2 * (e & 1) + (e >> 1)) * 4096, (__float_as_uint(Y[e]) & ~15u) | t4);
          if (t < 2) st_rlx(yo + (16 - 3 * t) * 4096, (__float_as_uint(t ? C[2] : C[0]) & ~15u) | t4);
          if (L == 0 && lane == 0) mbar_arrive(sb + B_DONE);
        }
      }
      TR(2, 8 + 10 * L);
      if (cta < 72) {
        RELANE;
        const uint32_t xn = ld_rlx(GC(candrow, (L * 128 + (win & 127)) * 1152 + 16 * cta + 2 * ((s & 6) ^ (2 * (cta & 1)))));
        const uint4 cm = ld_msg(GA(cand, (8 * L + r) * 2048 + 16 * (win & 127)));
        const uint8_t* yp = GA(ypart, cta * 4096 + s * 16);
        uint4 u0, u1;
        uint32_t n = 0;
        _Pragma("unroll 1") while (true) {
          u0 = ld_msg(yp);
          u1 = ld_msg(yp + 2048);
          const uint32_t t4 = tag & 15;
          u0.x ^= t4; u0.y ^= t4; u0.z ^= t4; u0.w ^= t4; u1.x ^= t4; u1.y ^= t4; u1.z ^= t4; u1.w ^= t4;
          if (!__any_sync(0xffffffffu, (u0.x | u0.y | u0.z | u0.w | u1.x | u1.y | u1.z | u1.w) & 15)) break;
          spin_guard(n);
        }
        const float a0 = __uint_as_float(u0.x) + __uint_as_float(u1.x), a1 = __uint_as_float(u0.y) + __uint_as_float(u1.y);
        const float a2 = __uint_as_float(u0.z) + __uint_as_float(u1.z), a3 = __uint_as_float(u0.w) + __uint_as_float(u1.w);
        const bool b4 = lane & 4, b2 = lane & 2;
        const float c0 = (b4 ? a2 : a0) + shx(b4 ? a0 : a2, 4), c1 = (b4 ? a3 : a1) + shx(b4 ? a1 : a3, 4);
        float d = (b2 ? c1 : c0) + shx(b2 ? c0 : c1, 2);
        d += shx(d, 8);
        if (!(lane & 8)) stsf(sb + SM_RED + 32 * (4 * (lane & 1) + ((lane >> 1) & 3)) + 8 * sw + 4 * (lane >> 4), d);
        bar_sync(3);
        if (s < 64) {
          const uint4 p0 = lds128(sb + SM_RED + 32 * (s & 7)), p1 = lds128(sb + SM_RED + 32 * (s & 7) + 16);
          const float y = rbf(((__uint_as_float(p0.x) + __uint_as_float(p0.y)) + (__uint_as_float(p0.z) + __uint_as_float(p0.w))) +
                              ((__uint_as_float(p1.x) + __uint_as_float(p1.y)) + (__uint_as_float(p1.z) + __uint_as_float(p1.w))));
          const uint32_t v = packbf(0.f, fmaf((s & 1) ? bhi(xn) : blo(xn), __uint_as_float(cm.z), __uint_as_float(cm.w)) + rbf(y * __uint_as_float(cm.y)));
          if (L == 0) st_rlx(GA(x2msg, (s >> 3) * 2304 + 32 * cta + 4 * (s & 7)), v | (epoch & 0xffff));
          const int tok = 128 * ((win >> 3) & 15) + 2 * (16 * (win & 3) + ((win >> 7) & 15)) + ((win >> 2) & 1);
          if (L == 1 && s < 8) *reinterpret_cast<uint16_t*>(p.out + (uint32_t)(tok * 1152 + 16 * cta + 2 * s)) = (uint16_t)(v >> 16);
        }
      }
      TR(2, 9 + 10 * L);
      if (L == 0 && m < 14) {
        RELANE;
        const int c = min(2 * m + ((s >> 3) & 1), 26);
        const uint8_t* wsrc = GC(wpack, r * 12 * WSTAGE + (s >> 4) * 3456 + c * 128 + (s & 7) * 16);
        const int k0 = 8 * (s >> 4) + (s & 7);
        uint4 wv[5];
#pragma unroll
        for (int i = 0; i < 5; i++) wv[i] = ldcg128(wsrc + i * WSTAGE);
        uint32_t xv[9];
        {
          uint32_t n = 0;
          _Pragma("unroll 1") while (true) {
            uint32_t bad = 0;
#pragma unroll
            for (int i = 0; i < 9; i++) { xv[i] = ld_rlx(GA(x2msg, r * 2304 + 4 * k0) + 256 * i); bad |= xv[i] ^ epoch; }
            if (!__any_sync(0xffffffffu, bad & 0xffff)) break;
            spin_guard(n);
          }
        }
        TR(2, 10);
        float a[8], z = 0.f;
#pragma unroll
        for (int e = 0; e < 8; e++) a[e] = 0.f;
#pragma unroll
        for (int i = 0; i < 9; i++) {
          const float xx = bhi(xv[i]);
          const uint4 w4 = wv[i % 5];
          if (i < 4) wv[i] = ldcg128(wsrc + (i + 5) * WSTAGE);
          z = fmaf(xx, (lane & 8) ? xx : 1.f, z);
          a[0] = fmaf(xx, blo(w4.x), a[0]); a[1] = fmaf(xx, bhi(w4.x), a[1]);
          a[2] = fmaf(xx, blo(w4.y), a[2]); a[3] = fmaf(xx, bhi(w4.y), a[3]);
          a[4] = fmaf(xx, blo(w4.z), a[4]); a[5] = fmaf(xx, bhi(w4.z), a[5]);
          a[6] = fmaf(xx, blo(w4.w), a[6]); a[7] = fmaf(xx, bhi(w4.w), a[7]);
        }
        const bool b4 = lane & 4, b2 = lane & 2, b1 = lane & 1;
        float b[4];
#pragma unroll
        for (int e = 0; e < 4; e++) b[e] = (b4 ? a[4 + e] : a[e]) + shx(b4 ? a[e] : a[4 + e], 4);
        z += shx(z, 4);
        const float c0 = (b2 ? b[2] : b[0]) + shx(b2 ? b[0] : b[2], 2);
        const float c1 = (b2 ? b[3] : b[1]) + shx(b2 ? b[1] : b[3], 2);
        z += shx(z, 2);
        float d = (b1 ? c1 : c0) + shx(b1 ? c0 : c1, 1);
        z += shx(z, 1);
        d += shx(d, 16);
        z += shx(z, 16);
        if (lane < 16) stsf(sb + SM_GEMV + 16 * lane + 4 * sw, d);
        if ((lane & 23) == 0) stsf(sb + SM_GEMV + 256 + 2 * lane + 4 * sw, z);
        bar_sync(3);
        if (s < 16) {
          const uint4 pd = lds128(sb + SM_GEMV + 16 * s), p1 = lds128(sb + SM_GEMV + 256), p2 = lds128(sb + SM_GEMV + 272);
          const float acc = (__uint_as_float(pd.x) + __uint_as_float(pd.y)) + (__uint_as_float(pd.z) + __uint_as_float(pd.w));
          const float m1 = ((__uint_as_float(p1.x) + __uint_as_float(p1.y)) + (__uint_as_float(p1.z) + __uint_as_float(p1.w))) * (1.f / kD);
          const float m2 = ((__uint_as_float(p2.x) + __uint_as_float(p2.y)) + (__uint_as_float(p2.z) + __uint_as_float(p2.w))) * (1.f / kD);
          const float cs = blo(lds16(sb + SM_COLSUM + 32 * c + 2 * (s & 7))) + blo(lds16(sb + SM_COLSUM + 32 * c + 2 * (s & 7) + 16));
          const float v = (acc - m1 * cs) * rcp(ln_sd(fmaxf(m2 - m1 * m1, 0.f)));
          st_rlx(GA(fixmsg, 1024 * r + 64 * m + 4 * s), __float_as_uint(rbf(v)) | (epoch & 0xffff));
        }
        TR(2, 11);
      }
      {
        if (L == 0 && (int)((win >> 3) & 15) == m) {
          RELANE;
          if (s < 72) {
            const uint8_t* fp = s < 54 ? GA(fixmsg, 1024 * r + 16 * s) : GA(x2msg, r * (2304 + 288) + 16 * (s - 54));
            uint4 v;
            uint32_t n = 0;
            _Pragma("unroll 1") while (true) {
              v = ld_msg(fp);
              if ((((v.x ^ epoch) | (v.y ^ epoch) | (v.z ^ epoch) | (v.w ^ epoch)) & 0xffff) == 0) break;
              spin_guard(n);
            }
            sts128(sb + SM_FIXQ + 16 * s, v.x & 0xffff0000u, v.y & 0xffff0000u, v.z & 0xffff0000u, v.w & 0xffff0000u);
          }
          __syncwarp();
          if (lane == 0) mbar_arrive(sb + B_FIX);
          TR(2, 12);
        }
      }
    }
    if (s == 0) st_rlx(GA(epoch, 32 * cta), epoch);
  } else {
    asm volatile("setmaxnreg.inc.sync.aligned.u32 144;");
    const int w = warp >> 2, j = warp & 3;
    const uint32_t xfull = sb + B_XFULL + 32 * w, xempty = sb + B_XEMPTY + 32 * w, xring = sb + SM_X + w * 4 * XSTAGE;
    if (threadIdx.x >= 128 && threadIdx.x < 188) { sts128(sb + SM_COLSUM + 16 * (threadIdx.x - 128), 0, 0, 0, 0); fence_async_smem(); }
    {
      const uint32_t epoch = pack();
      asm volatile("bar.arrive 15, 384;" ::: "memory");
      TRW(24);
      if (!(ABL & 8)) {
        if (lane < 16) st_msg(GA(statsP, (2 * m + w) * 8192 + r * 1024 + (16 * j + lane) * 16), 0, 0, 0, 0);
        if (lane < 2) st_msg(GA(cand, (8 * lane + r) * 2048 + 16 * (8 * m + warp)), ~epoch, 0, 0, 0);
        if (j == 3) {
#pragma unroll
          for (int u = 0; u < 10; u++) st_msg(GC(halo, (4 * cta + w) * 2560 + lane * 16) + (u / 5) * 5120 + (u % 5) * 512, 0, 0, 0, 0);
        }
        __syncwarp();
      }
      TRW(11);
    }
    const uint32_t mw = 2 * m + w, cid = 8 * m + warp;
    const uint32_t rowc = sb + SM_ROWC + 64 * warp, rowm = sb + SM_ROWM + 128 * warp;
#pragma unroll 1
    for (int L = 0; L < 2; L++) {
      int ln0 = __shfl_sync(0xffffffffu, lane + L, lane) - L;
#define RELANE2 asm volatile("" : "+r"(ln0)); const int ln = ln0, g = ln >> 2, t = ln & 3; \
      const uint32_t pa = xring + j * 256 + (ln & 7) * 1028 + ((ln >> 3) & 1) * 128 + 96; (void)pa
      uint32_t P[27][2], H[20];
      const uint8_t* hl;
      auto halo = [&]() {
#pragma unroll
        for (int u = 0; u < 5; u++) {
          const uint4 v = ld_gen(hl + u * 512);
          H[4 * u] = v.x; H[4 * u + 1] = v.y; H[4 * u + 2] = v.z; H[4 * u + 3] = v.w;
        }
      };
      {
        RELANE2;
        const uint32_t epoch = __shfl_sync(0xffffffffu, lds32(sb + SM_EP), 0);
        int selrow = -1;
        bool tgtwg = false;
        float d[108];
        uint32_t am[4];
        auto split_mean = [&](float m0, float m1) {
          const uint32_t h0 = packbf(m0, m0), h1 = packbf(m1, m1);
          const float l0 = m0 - bhi(h0), l1 = m1 - bhi(h1);
          am[0] = t ? 0u : h0; am[1] = t ? 0u : h1; am[2] = t ? 0u : packbf(l0, l0); am[3] = t ? 0u : packbf(l1, l1);
        };
        const uint32_t cdesc = mkdesc(sbd + SM_COLSUM, 0);
        am[0] = am[1] = am[2] = am[3] = 0;
        if (L == 1) split_mean(ldsf(rowm + 8 * g), ldsf(rowm + 8 * g + 64));
        asm volatile("wgmma.fence.sync.aligned;" ::: "memory");
        wgmma_n144_set(d + 36, am, cdesc + 18);
        wgmma_n72_set(d, am, cdesc);
        asm volatile("wgmma.commit_group.sync.aligned;" ::: "memory");
        const uint32_t adesc = mkdesc(sbd + SM_X + w * 4 * XSTAGE, 1024), ahi = L == 0 ? 0x40000040u : 8u, astep = L == 0 ? 2 : 128;
        const uint32_t bdesc = mkdesc(sbd + SM_W, 3456);
        const uint8_t* xsrc = GC(act, ACT + mw * 73728);
        mbar_wait2(sb + B_WFULL, L, xfull, 0);
        if (L == 1) check_stage(probe_stage(pa), xring, xsrc);
        TRW(0 + 12 * L);
#pragma unroll 1
        for (int s = 0; s < 7; s++) {
          TRQ(s + 9 * L);
          const uint32_t da = adesc + (s & 3) * (XSTAGE >> 4), db = bdesc + (s & 3) * (WSTAGE >> 4);
          const uint32_t nx = (s + 1) & 3, px = ((s + 1) >> 2) & 1;
          asm volatile("wgmma.fence.sync.aligned;" ::: "memory");
          wgmma_n72(d, da, ahi, db);
          wgmma_n144(d + 36, da, ahi, db + (1152 >> 4));
          wgmma_n72(d, da + astep, ahi, db + (6912 >> 4));
          asm volatile("wgmma.commit_group.sync.aligned;" ::: "memory");
          asm volatile("wgmma.wait_group.sync.aligned 1;" ::: "memory");
          if (s > 0 && ln == 0) {
            mbar_arrive_pair(sb + B_WEMPTY + 8 * ((s - 1) & 3));
            mbar_arrive(xempty + 8 * ((s - 1) & 3));
          }
          wgmma_n144(d + 36, da + astep, ahi, db + ((6912 + 1152) >> 4));
          wgmma_n72(d, da + 2 * astep, ahi, db + 2 * (6912 >> 4));
          uint32_t pv;
          const uint32_t dsc[6] = {da + 2 * astep, db + ((2 * 6912 + 1152) >> 4), da + 3 * astep, db + 3 * (6912 >> 4),
                                   da + 3 * astep, db + ((3 * 6912 + 1152) >> 4)};
          const uint32_t bar[4] = {sb + B_WFULL + 8 * nx, px ^ L, xfull + 8 * nx, px}, adr = pa + nx * XSTAGE;
          q_tail(d, &pv, ahi, dsc, bar, &adr);
          if (L == 1) check_stage(pv, xring + nx * XSTAGE, xsrc + (s + 1) * XSTAGE);
        }
        TRQ(7 + 9 * L);
        const uint32_t da7 = adesc + 3 * (XSTAGE >> 4), db7 = bdesc + 3 * (WSTAGE >> 4);
        asm volatile("wgmma.fence.sync.aligned;" ::: "memory");
        wgmma_n144(d + 36, da7, ahi, db7 + (1152 >> 4));
        wgmma_n144(d + 36, da7 + astep, ahi, db7 + ((6912 + 1152) >> 4));
        asm volatile("wgmma.commit_group.sync.aligned;" ::: "memory");
        asm volatile("wgmma.wait_group.sync.aligned 1;" ::: "memory");
        if (ln == 0) { mbar_arrive_pair(sb + B_WEMPTY + 16); mbar_arrive(xempty + 16); }
        {
          uint32_t v[2];
          const uint32_t dsc[4] = {da7 + 2 * astep, db7 + ((2 * 6912 + 1152) >> 4), da7 + 3 * astep, db7 + ((3 * 6912 + 1152) >> 4)};
          const uint32_t bar[6] = {sb + B_WFULL, (uint32_t)L, xfull, 0, sb + (L ? B_IDX : B_COLSUM), 0}, adr[2] = {pa, sb + SM_SEL + (ln >> 5)};
          kv_tail(d, v, ahi, dsc, bar, adr);
          if (L == 1) {
            if ((v[1] & 127) == cid) selrow = v[1] >> 7;
            tgtwg = ((v[1] & 127) >> 2) == (cid >> 2);
            check_stage(v[0], xring, xsrc + 8 * XSTAGE);
          }
        }
        TRQ(8 + 9 * L);
        const float m0 = ldsf(rowm + 8 * g), m1 = ldsf(rowm + 8 * g + 64);
        {
          uint32_t dsc[8];
#pragma unroll
          for (int kk = 0; kk < 4; kk++) { dsc[2 * kk] = adesc + kk * astep; dsc[2 * kk + 1] = bdesc + ((kk * 6912 + 1152) >> 4); }
          const uint32_t bar[2] = {xempty + 16, 1};
          asm volatile("wgmma.fence.sync.aligned;" ::: "memory");
          kv_last(d, nullptr, ahi, dsc, bar, nullptr);
        }
        if (L == 0) {
          split_mean(m0, m1);
          asm volatile("wgmma.fence.sync.aligned;" ::: "memory");
          wgmma_n144_add(d + 36, am, cdesc + 18);
          wgmma_n72_add(d, am, cdesc);
          asm volatile("wgmma.commit_group.sync.aligned;" ::: "memory");
        }
        auto qstep = [&](int k) {
          wgmma_n72(d, (k < 4 ? da7 : adesc) + (k & 3) * astep, ahi, (k < 4 ? db7 : bdesc) + (k & 3) * (6912 >> 4));
        };
#pragma unroll
        for (int k = 0; k < QPRE; k++) qstep(k);
        asm volatile("wgmma.commit_group.sync.aligned;" ::: "memory");
        if (tgtwg) {
          asm volatile("wgmma.fence.sync.aligned;" ::: "memory");
#pragma unroll
          for (int k = QPRE; k < 8; k++) qstep(k);
          asm volatile("wgmma.commit_group.sync.aligned;" ::: "memory");
        }
        asm volatile("wgmma.wait_group.sync.aligned 1;" ::: "memory");
#pragma unroll
        for (int i = 36; i < 108; i++) asm volatile("" : "+f"(d[i])::"memory");
        if (selrow >= 0) {
          mbar_wait(sb + B_FIX, 0);
          stsf(rowc + 4 * selrow, 1.f);
#pragma unroll
          for (int q = 18; q < 54; q++) lds64f_if(selrow == g + 8 * (q & 1), d[2 * q], d[2 * q + 1], sb + SM_FIXQ + 32 * (q >> 1) + 8 * t);
          __syncwarp();
        }
#pragma unroll
        for (int q = 26; q >= 9; q--) { P[q][1] = packbf(d[4 * q + 2], d[4 * q + 3]); P[q][0] = packbf(d[4 * q], d[4 * q + 1]); }
#pragma unroll
        for (int q = 26; q >= 18; q--) P[q][1] = movm(P[q][1]);
        const uint2 ck1 = lds64(rowc + 32 + 8 * t);
        uint8_t* ha = (j < 3 ? smem_raw + (SM_X + (4 * w + 2) * XSTAGE + j * 2560) : GC(halo, (4 * cta + 2 * L + w) * 2560)) + ln * 16;
        P[9][1] = nz(P[9][1]); P[13][1] = nz(P[13][1]); P[17][1] = nz(P[17][1]);
        st_gen(ha, P[9][1], P[10][1], P[11][1], P[12][1]);
        st_gen(ha + 512, P[13][1], P[14][1], P[15][1], P[16][1]);
        st_gen(ha + 2048, nz(ck1.y), P[24][1], P[25][1], P[26][1]);
        st_gen(ha + 1536, nz(ck1.x), P[21][1], P[22][1], P[23][1]);
        st_gen(ha + 1024, P[17][1], P[18][1], P[19][1], P[20][1]);
#pragma unroll
        for (int q = 9; q < 27; q++) asm volatile("" : "+r"(P[q][0]));
        if (j < 3) asm volatile("bar.arrive %0, 64;" ::"r"(5 + warp) : "memory");
        mbar_wait(sb + B_EP, 0);
#pragma unroll
        for (int q = 26; q >= 18; q--) P[q][0] = movm(P[q][0]);
        if (!tgtwg)
        {
          asm volatile("wgmma.fence.sync.aligned;" ::: "memory");
#pragma unroll
          for (int k = QPRE; k < 8; k++) qstep(k);
          asm volatile("wgmma.commit_group.sync.aligned;" ::: "memory");
        }
        hl = (j > 0 || m == 0 ? smem_raw + (SM_X + (4 * w + 2) * XSTAGE + max(j - 1, 0) * 2560)
                              : GC(halo, (4 * (cta - 8) + 2 * L + w) * 2560)) + ln * 16;
        if (j > 0) asm volatile("bar.sync %0, 64;" ::"r"(4 + warp) : "memory");
        asm volatile("wgmma.wait_group.sync.aligned 0;" ::: "memory");
#pragma unroll
        for (int i = 0; i < 36; i++) asm volatile("" : "+f"(d[i])::"memory");
        TRW(1 + 12 * L);
        if (selrow >= 0) {
#pragma unroll
          for (int q = 0; q < 18; q++) lds64f_if(selrow == g + 8 * (q & 1), d[2 * q], d[2 * q + 1], sb + SM_FIXQ + 32 * (q >> 1) + 8 * t);
        }
#pragma unroll
        for (int q = 0; q < 9; q++) { P[q][0] = packbf(d[4 * q], d[4 * q + 1]); P[q][1] = packbf(d[4 * q + 2], d[4 * q + 3]); }
      }
      TRW(2 + 12 * L);
      const uint32_t epoch = lds32(sb + SM_EP);
      uint8_t* fptr = GA(flagX, 128 * mw + 16 * r + 4 * j + ln0);
      {
        RELANE2;
        halo();
        if (ln == 0) { mbar_arrive(xempty + 24); mbar_arrive(xempty); }
        const bool le0 = 2 * t <= g, le1 = 2 * t + 1 <= g;
        uint32_t A0[4][2], A2[4][2];
        float s0[4][4], s1[4][4];
#pragma unroll
        for (int h = 0; h < 4; h++) {
          const int T = 2 * h;
          A0[h][0] = t >= h ? P[T][0] : 0u; A0[h][1] = t >= h ? P[T][1] : 0u;
          A2[h][0] = t <= h ? P[T + 2][0] : 0u; A2[h][1] = t <= h ? P[T + 2][1] : 0u;
          mma8z(s0[h], A2[h][0], A2[h][1], P[9 + T + 2][0]);
          mma8z(s1[h], A2[h][0], A2[h][1], P[9 + T + 2][1]);
        }
#pragma unroll
        for (int h = 0; h < 4; h++) {
          const int T = 2 * h;
          mma16(s0[h], A0[h][0], A0[h][1], P[T + 1][0], P[T + 1][1], P[9 + T][0], P[9 + T + 1][0]);
          mma16(s1[h], A0[h][0], A0[h][1], P[T + 1][0], P[T + 1][1], P[9 + T][1], P[9 + T + 1][1]);
        }
        const uint2 ck0 = lds64(rowc + 8 * t), ck1 = lds64(rowc + 32 + 8 * t);
        const float sc = 0.23570226039551584f * 1.4426950408889634f;
        const float cq0 = ldsf(rowc + 4 * g) * sc, cq1 = ldsf(rowc + 32 + 4 * g) * sc;
        uint8_t* ob = GC(act, 2 * L * ACT + mw * 73728 + r * 9216 + j * 256 + ln * 4);
        float l[2][4][2], ks[2][2], mx[2][4];
        ks[1][0] = __uint_as_float(le0 ? ck1.x : ck0.x); ks[1][1] = __uint_as_float(le1 ? ck1.y : ck0.y);
#pragma unroll
        for (int h = 0; h < 4; h++) {
          l[1][h][0] = (le0 ? s1[h][2] : s0[h][2]) * (cq1 * ks[1][0]); l[1][h][1] = (le1 ? s1[h][3] : s0[h][3]) * (cq1 * ks[1][1]);
          asm volatile("" : "+f"(l[1][h][0]), "+f"(l[1][h][1]));
        }
        asm volatile("" : "+l"(fptr), "+l"(ob));
        {
          uint32_t n = 0;
          _Pragma("unroll 1") while (__any_sync(0xffffffffu, min(min(min(H[0], H[4]), min(H[8], H[12])), H[16]) == 0)) {
            halo();
            spin_guard(n);
          }
        }
        if (ln == 0) mbar_arrive_pair(sb + B_WEMPTY + 24);
        TRW(3 + 12 * L);
        {
          float sm[4][4];
#pragma unroll
          for (int h = 0; h < 4; h++) mma8z(sm[h], A2[h][0], A2[h][1], H[2 * h + 2]);
#pragma unroll
          for (int h = 0; h < 4; h++) mma16(sm[h], A0[h][0], A0[h][1], P[2 * h + 1][0], P[2 * h + 1][1], H[2 * h], H[2 * h + 1]);
          ks[0][0] = __uint_as_float(le0 ? ck0.x : H[12]); ks[0][1] = __uint_as_float(le1 ? ck0.y : H[16]);
          const bool nohalo = (m == 0 && j == 0);
          const float b0 = (nohalo && !le0) ? -INFINITY : 0.f, b1 = (nohalo && !le1) ? -INFINITY : 0.f;
#pragma unroll
          for (int h = 0; h < 4; h++) {
            l[0][h][0] = fmaf(le0 ? s0[h][0] : sm[h][0], cq0 * ks[0][0], b0);
            l[0][h][1] = fmaf(le1 ? s0[h][1] : sm[h][1], cq0 * ks[0][1], b1);
          }
        }
#pragma unroll
        for (int i = 7; i >= 0; i--) mx[i >> 2][i & 3] = fmaxf(l[i >> 2][i & 3][0], l[i >> 2][i & 3][1]);
#pragma unroll
        for (int x = 1; x <= 2; x <<= 1) {
#pragma unroll
          for (int i = 7; i >= 0; i--) mx[i >> 2][i & 3] = fmaxf(mx[i >> 2][i & 3], shx(mx[i >> 2][i & 3], x));
        }
        const uint32_t mle = (le0 ? 0xffffu : 0u) | (le1 ? 0xffff0000u : 0u);
        uint32_t pp[2][4], pc[2][4];
#pragma unroll
        for (int i = 3; i >= 0; i--) {
          const int e = i >> 1, h = 2 * (i & 1);
          const float p0 = ex2(l[e][h][0] - mx[e][h]), p1 = ex2(l[e][h][1] - mx[e][h]);
          const float p2 = ex2(l[e][h + 1][0] - mx[e][h + 1]), p3 = ex2(l[e][h + 1][1] - mx[e][h + 1]);
          float sum[4];
          mma8z(sum, packbf(p0, p1), packbf(p2, p3), 0x3f803f80u);
          const float inv = rcp(sum[0] * sum[2]);
          const float ia = inv * sum[2], ib = inv * sum[0];
          const uint32_t u0 = packbf(p0 * ks[e][0] * ia, p1 * ks[e][1] * ia), u1 = packbf(p2 * ks[e][0] * ib, p3 * ks[e][1] * ib);
          pp[e][h] = u0 & ~mle; pc[e][h] = u0 & mle; pp[e][h + 1] = u1 & ~mle; pc[e][h + 1] = u1 & mle;
        }
#pragma unroll
        for (int e = 1; e >= 0; e--) {
#pragma unroll
          for (int q = 8; q >= 0; q--) {
            const int h = q < 4 ? 0 : q == 4 ? 1 : 2;
            float a[4];
            mma16z(a, pp[e][h], pp[e][h + 1], pc[e][h], pc[e][h + 1], e ? P[18 + q][0] : H[9 + q + q / 3], P[18 + q][e]);
            const bool second = q == 2 * h + 2 ? t > h : q > 2 * h + 2;
            st_rlx(ob + q * 1024 + e * 128, nz(packbf(second ? a[2] : a[0], second ? a[3] : a[1])));
          }
        }
        if (ln == 0) st_rlx(fptr, epoch * 4 + 1 + 2 * L);
        TRW(4 + 12 * L);
      }
      RELANE2;
      float d[36];
      uint32_t WB[9];
      {
        uint32_t R[10][2];
        const uint32_t qs = L == 0 ? 16 : 1024, ra = xring + (16 * j + (ln & 15)) * (L == 0 ? 144 : 16) + (ln >> 4) * qs;
        mbar_wait(sb + B_RES + 8 * w, L);
#pragma unroll
        for (int q = 0; q < 10; q += 2) ldsm4(&R[q][0], ra + q * qs);
        fence_async_smem();
        __syncwarp();
        if (ln == 0) mbar_arrive(sb + B_RC + 8 * w);
#pragma unroll
        for (int q = 0; q < 9; q++) WB[q] = ldg32(p.wr + (uint32_t)(r * 144 + 4 * t) + 16 * q);
#pragma unroll
        for (int h = 0; h < 2; h++) {
          const uint2 mf = lds64(rowm + 8 * g + 64 * h);
          const float f = __uint_as_float(mf.y), k = -__uint_as_float(mf.x) * f;
#pragma unroll
          for (int q = 0; q < 9; q++) { d[4 * q + 2 * h] = fmaf(blo(R[q][h]), f, k); d[4 * q + 2 * h + 1] = fmaf(bhi(R[q][h]), f, k); }
        }
        const uint32_t sel = lds32(sb + SM_SEL);
        if (L == 1 && (sel & 127) == cid) {
          const int selrow = sel >> 7;
#pragma unroll
          for (int q = 0; q < 18; q++) lds64f_if(selrow == g + 8 * (q & 1), d[2 * q], d[2 * q + 1], sb + SM_X2R + 32 * (q >> 1) + 8 * t);
        }
#pragma unroll
        for (int q = 0; q < 9; q++) WB[q] = (g & 1) ? WB[q] : 0x3f803f80u;
        __syncwarp();
      }
      uint8_t* xb = GC(act, ACT + mw * 73728 + r * 9216 + j * 256 + ln * 4);
      uint8_t* sst = GA(statsP, mw * 8192 + r * 1024 + (16 * j + g + 8 * t) * 16);
      const uint8_t* sld = GA(statsP, mw * 8192 + (ln >> 4) * 4096 + (16 * j + (ln & 15)) * 16);
      uint8_t* cptr = GA(cand, (8 * L + r) * 2048 + 16 * cid);
      uint8_t* crow = GC(candrow, (128 * L + cid) * 1152 + 144 * r + 4 * t);
      uint32_t tag = epoch * 2 + L, ktag = ((ln & 15) << 7) | (epoch & 0x7f);
      float wsum = ldsf(sb + SM_WSUM);
      float pivot = __uint_as_float(ld_rlx(GA(stats0, 16 * (16 * cid + (ln & 15)) + 4))) + (L ? ldsf(rowm + 8 * (ln & 15)) : 0.f);
      asm volatile("" : "+l"(xb), "+l"(sst), "+l"(sld), "+l"(cptr), "+l"(crow), "+r"(tag), "+r"(ktag), "+f"(wsum), "+f"(pivot));
      TRW(5 + 12 * L);
      {
        constexpr uint32_t bdesc = mkdesc(sbd + SM_W + WSTAGE, 1152);
        uint32_t adesc[3];
#pragma unroll
        for (int i = 0; i < 3; i++) adesc[i] = __shfl_sync(0xffffffffu, mkdesc(sbd + SM_X + w * 4 * XSTAGE, 1024) + (ln >> 2), i);
#pragma unroll
        for (int i = 0; i < 36; i++) asm volatile("" : "+f"(d[i])::"memory");
        const bool lead = warp == 0 && ln == 0;
        const uint8_t* osrc = GC(act, 2 * L * ACT + mw * 73728);
        mbar_wait2(sb + B_WFULL + 8, L, xfull, 1);
        check_stage(probe_stage(pa), xring, osrc);
        TRW(6 + 12 * L);
#pragma unroll
        for (int s = 0; s < 9; s++) {
          TRQ(18 + s);
          const uint32_t da = s == 4 ? adesc[1] - ((SM_X - SM_W) >> 4) - w * 3 * (XSTAGE >> 4) : adesc[s >> 2] + (s < 4 ? s : s - 5) * (XSTAGE >> 4);
          const uint32_t db = bdesc + s * (9216 >> 4);
          const int n1 = s + 1, nx = n1 < 4 ? n1 : n1 - 5;
          const uint32_t xoff = n1 == 4 ? SM_W - SM_X - w * 3 * XSTAGE : nx * XSTAGE;
          asm volatile("wgmma.fence.sync.aligned;" ::: "memory");
          wgmma_n72(d, da, 8u, db);
          wgmma_n72(d, da + 128, 8u, db + (2304 >> 4));
          asm volatile("wgmma.commit_group.sync.aligned;" ::: "memory");
          if (s > 0) {
            asm volatile("wgmma.wait_group.sync.aligned 1;" ::: "memory");
            if (ln == 0) {
              if (s != 5) mbar_arrive(xempty + 8 * (s < 5 ? s - 1 : s - 6));
              if ((s == 5 || s == 3 || s == 6) && L == 0) mbar_arrive_pair(sb + B_WEMPTY + (s == 5 ? 0 : (s / 3) * 8));
            }
          }
          const uint32_t xbar = n1 == 4 ? sb + B_XE + 8 * w : xfull + 8 * nx, px = n1 == 4 ? L : n1 >= 6;
          if ((s == 0 || s == 5) && lead) mbar_arrive(sb + (s ? B_EPI : B_OS));
          if (s < 8) {
            uint32_t pv;
            const uint32_t dsc[4] = {da + 256, db + (4608 >> 4), da + 384, db + (6912 >> 4)};
            const uint32_t bar[4] = {sb + B_WFULL + 8 + 8 * ((s + 1) / 3), (uint32_t)L, xbar, px}, adr = pa + xoff;
            o_tail2(d, &pv, 8u, dsc, bar, &adr);
            check_stage(pv, xring + xoff, osrc + (s + 1) * XSTAGE);
          } else {
            wgmma_n72(d, da + 256, 8u, db + (4608 >> 4));
            wgmma_n72(d, da + 384, 8u, db + (6912 >> 4));
            asm volatile("wgmma.commit_group.sync.aligned;" ::: "memory");
          }
        }
        asm volatile("wgmma.wait_group.sync.aligned 0;" ::: "memory");
#pragma unroll
        for (int i = 0; i < 36; i++) asm volatile("" : "+f"(d[i])::"memory");
        mbar_wait(xfull, 1);
        if (ln == 0) { if (L == 0) mbar_arrive_pair(sb + B_WEMPTY + 24); mbar_arrive(xempty + 24); mbar_arrive(xempty); }
      }
      TRW(7 + 12 * L);
      uint32_t R[9][2];
#pragma unroll
      for (int q = 0; q < 9; q++) { R[q][0] = packbf(d[4 * q], d[4 * q + 1]); R[q][1] = packbf(d[4 * q + 2], d[4 * q + 3]); }
      {
        float sa[4], sc[4];
        mma16z(sa, R[0][0], R[0][1], R[1][0], R[1][1], WB[0], WB[1]);
        mma16z(sc, R[2][0], R[2][1], R[3][0], R[3][1], WB[2], WB[3]);
        mma16(sa, R[4][0], R[4][1], R[5][0], R[5][1], WB[4], WB[5]);
        mma16(sc, R[6][0], R[6][1], R[7][0], R[7][1], WB[6], WB[7]);
        mma8(sa, R[8][0], R[8][1], WB[8]);
        float qq[4] = {0.f, 0.f, 0.f, 0.f};
#pragma unroll
        for (int q = 0; q < 36; q++) qq[q & 3] = fmaf(d[q], d[q], qq[q & 3]);
        const float qa = qq[0] + qq[1], qc = qq[2] + qq[3];
        const bool odd = t & 1;
        float q2 = (odd ? qc : qa) + shx(odd ? qa : qc, 1);
        q2 += shx(q2, 2);
        if (t < 2)
          st_msg(sst, __float_as_uint(odd ? sa[2] + sc[2] : sa[0] + sc[0]), __float_as_uint(q2),
                 __float_as_uint(odd ? sa[3] + sc[3] : sa[1] + sc[1]), tag);
      }
      if (L == 0) {
#pragma unroll
        for (int q = 0; q < 9; q++) { st_rlx(xb + q * 1024, nz(R[q][0])); st_rlx(xb + q * 1024 + 128, nz(R[q][1])); }
        if (ln == 0) st_rlx(fptr, epoch * 4 + 2);
      }
      TRW(8 + 12 * L);
      {
        uint4 u[4];
        uint32_t n = 0;
        _Pragma("unroll 1") while (true) {
#pragma unroll
          for (int i = 0; i < 4; i++) u[i] = ld_msg(sld + 1024 * i);
          if (!__any_sync(0xffffffffu, (u[0].w ^ tag) | (u[1].w ^ tag) | (u[2].w ^ tag) | (u[3].w ^ tag))) break;
          spin_guard(n);
        }
        TRW(9 + 12 * L);
        float s1 = (__uint_as_float(u[0].x) + __uint_as_float(u[1].x)) + (__uint_as_float(u[2].x) + __uint_as_float(u[3].x));
        float s2 = (__uint_as_float(u[0].y) + __uint_as_float(u[1].y)) + (__uint_as_float(u[2].y) + __uint_as_float(u[3].y));
        float s3 = (__uint_as_float(u[0].z) + __uint_as_float(u[1].z)) + (__uint_as_float(u[2].z) + __uint_as_float(u[3].z));
        s1 += shx(s1, 16); s2 += shx(s2, 16); s3 += shx(s3, 16);
        const float mu = s1 * (1.f / kD);
        const float var = fmaxf(fmaf(s2, 1.f / kD, -mu * mu), 0.f);
        const float sd = ln_sd(var), rho = rcp(sd);
        const float rr = (s3 - mu * wsum) * rho;
        const int key = __reduce_max_sync(0xffffffffu, (int)((fkey(rr) & ~0x7ff) | ktag));
        const int best = (key >> 7) & 15;
        if (ln == best) st_msg(cptr, key, __float_as_uint(rbf(sigmoidf(rbf(rr)))), __float_as_uint(1.f + sd), __float_as_uint(L ? pivot + mu : 0.f));
        const float rb = __shfl_sync(0xffffffffu, rho, best), nb = __shfl_sync(0xffffffffu, -mu * rho, best);
        if ((best & 7) == g) {
          const bool hi = best >= 8;
#pragma unroll
          for (int q = 0; q < 9; q++)
            st_rlx(crow + (((q ^ r) & 1) * (4 - 8 * (t & 1))) + 16 * q, nz(packbf(fmaf(hi ? d[4 * q + 2] : d[4 * q], rb, nb), fmaf(hi ? d[4 * q + 3] : d[4 * q + 1], rb, nb))));
        }
        const float f = 1.f + rho, k = pivot - mu * rho;
        sts32(rowc + 4 * (ln & 15), __float_as_uint(f * rcp(ln_sd(var * f * f))));
        sts64(rowm + 8 * (ln & 15), __float_as_uint(L == 0 ? mu : k), __float_as_uint(f));
        __syncwarp();
      }
      TRW(10 + 12 * L);
      if (L == 1) {
#pragma unroll
        for (int h = 0; h < 2; h++) {
          const uint2 kf = lds64(rowm + 8 * g + 64 * h);
          const float k = __uint_as_float(kf.x), f = __uint_as_float(kf.y);
#pragma unroll
          for (int q = 0; q < 9; q++) R[q][h] = packbf(fmaf(d[4 * q + 2 * h], f, k), fmaf(d[4 * q + 2 * h + 1], f, k));
        }
        mbar_wait(xempty + 16, 1);
        const uint32_t st = xring + XSTAGE + (16 * j + (ln & 15)) * 144;
#pragma unroll
        for (int q = 0; q < 8; q += 2) stsm4(st + (ln >> 4) * 16 + q * 16, R[q][0], R[q][1], R[q + 1][0], R[q + 1][1]);
        stsm2(st + 128, R[8][0], R[8][1]);
        fence_async_smem();
        __syncwarp();
        mbar_wait(sb + B_IDX + 8, 0);
        const uint32_t sel = lds32(sb + SM_SEL + 4);
        if ((sel & 127) != cid) {
          if (elect())
            asm volatile("cp.async.bulk.tensor.3d.global.shared::cta.bulk_group [%0, {%2,%3,%4}], [%1];" ::"l"(&tm.out),
                         "r"(xring + XSTAGE + 16 * j * 144), "r"(72 * r), "r"(w), "r"(64 * m + 16 * j) : "memory");
        } else if (ln < 16 && ln != (sel >> 7)) {
          bulk_s2g(p.out + (uint32_t)((128 * m + 2 * (16 * j + ln) + w) * 1152 + r * 144), st, 144);
        }
        asm volatile("cp.async.bulk.commit_group;" ::: "memory");
        asm volatile("cp.async.bulk.wait_group.read 0;" ::: "memory");
        TRW(11 + 12 * L);
        TRDUMP(w);
      }
    }
  }
}

typedef CUresult (*EncodeFn)(CUtensorMap*, CUtensorMapDataType, cuuint32_t, void*, const cuuint64_t*, const cuuint64_t*,
                             const cuuint32_t*, const cuuint32_t*, CUtensorMapInterleave, CUtensorMapSwizzle,
                             CUtensorMapL2promotion, CUtensorMapFloatOOBfill);

}

extern "C" void kernel_launch(void* const* d_in, const int* in_sizes, int n_in, void* d_out, int out_size) {
  static EncodeFn enc = nullptr;
  static Scratch* scratch = nullptr;
  if (!enc) {
    cudaDriverEntryPointQueryResult q;
    cudaGetDriverEntryPoint("cuTensorMapEncodeTiled", (void**)&enc, cudaEnableDefault, &q);
    cudaGetSymbolAddress((void**)&scratch, g_s);
    cudaFuncSetAttribute(fused_kernel, cudaFuncAttributeMaxDynamicSharedMemorySize, 232448);
  }
  Maps tm;
  auto mk = [&](CUtensorMap* t, void* ptr, int rank, const cuuint64_t* dims, const cuuint64_t* strides, const cuuint32_t* box,
                CUtensorMapSwizzle sw, CUtensorMapL2promotion pr) {
    const cuuint32_t es[4] = {1, 1, 1, 1};
    enc(t, CU_TENSOR_MAP_DATA_TYPE_BFLOAT16, rank, ptr, dims, strides, box, es, CU_TENSOR_MAP_INTERLEAVE_NONE, sw, pr,
        CU_TENSOR_MAP_FLOAT_OOB_FILL_NONE);
  };
  { const cuuint64_t d[3] = {576, 2, 1024}, st[2] = {1152, 2304}; const cuuint32_t bx[3] = {64, 1, 64};
    mk(&tm.x, d_in[0], 3, d, st, bx, CU_TENSOR_MAP_SWIZZLE_128B, CU_TENSOR_MAP_L2_PROMOTION_NONE);
    const cuuint32_t br[3] = {72, 1, 64};
    mk(&tm.xr, d_in[0], 3, d, st, br, CU_TENSOR_MAP_SWIZZLE_NONE, CU_TENSOR_MAP_L2_PROMOTION_NONE);
    const cuuint32_t bo[3] = {72, 1, 16};
    mk(&tm.out, d_out, 3, d, st, bo, CU_TENSOR_MAP_SWIZZLE_NONE, CU_TENSOR_MAP_L2_PROMOTION_NONE); }
  { const cuuint64_t d[3] = {576, 576, 3}, st[2] = {3456, 1152}; const cuuint32_t bx[3] = {72, 8, 2};
    mk(&tm.wq, d_in[1], 3, d, st, bx, CU_TENSOR_MAP_SWIZZLE_NONE, CU_TENSOR_MAP_L2_PROMOTION_NONE); }
  { const cuuint64_t d[2] = {576, 576}, st[1] = {1152}; const cuuint32_t bx[2] = {72, 16};
    mk(&tm.wo, d_in[2], 2, d, st, bx, CU_TENSOR_MAP_SWIZZLE_NONE, CU_TENSOR_MAP_L2_PROMOTION_NONE); }
  { const cuuint64_t d[2] = {4608, 576}, st[1] = {9216}; const cuuint32_t bx[2] = {48, 64};
    mk(&tm.wg, d_in[5], 2, d, st, bx, CU_TENSOR_MAP_SWIZZLE_128B, CU_TENSOR_MAP_L2_PROMOTION_L2_128B);
    mk(&tm.wu, d_in[6], 2, d, st, bx, CU_TENSOR_MAP_SWIZZLE_128B, CU_TENSOR_MAP_L2_PROMOTION_L2_128B); }
  Params p;
  p.x = (const uint8_t*)d_in[0]; p.wqkv = (const uint8_t*)d_in[1]; p.wo = (const uint8_t*)d_in[2];
  p.wr = (const uint8_t*)d_in[4]; p.wg = (const uint8_t*)d_in[5]; p.wu = (const uint8_t*)d_in[6]; p.wd = (const uint8_t*)d_in[7];
  p.out = (uint8_t*)d_out;
  p.g = scratch;
  fused_kernel<<<128, 512, 232448>>>(p, tm);
}
```

```cpp
#include <cuda_runtime.h>
#include <cuda_bf16.h>
#include <cuda.h>
#include <stdint.h>
#include <stddef.h>

#define DEVI __device__ __forceinline__

namespace {

constexpr int kD = 576, kF = 4608;
constexpr uint32_t WSTAGE = 27648, XSTAGE = 8192;
constexpr float kEps = 1e-5f;

constexpr uint32_t WDP = 1168;
constexpr uint32_t SM_W = 0;
constexpr uint32_t SM_X = 110592;
constexpr uint32_t SM_WD = 176128;
constexpr uint32_t SM_LEFT = SM_WD + 36 * WDP;
constexpr uint32_t SM_COLSUM = SM_LEFT + 9216;
constexpr uint32_t SM_ROWC = SM_COLSUM + 960;
constexpr uint32_t SM_ROWM = SM_ROWC + 512;
constexpr uint32_t SM_PART = SM_ROWM + 1024;
constexpr uint32_t SM_FIXQ = SM_PART;
constexpr uint32_t SM_X2R = SM_PART + 864;
constexpr uint32_t SM_H = SM_PART + 1152;
constexpr uint32_t SM_GEMV = SM_H;
constexpr uint32_t SM_RED = SM_H + 320;
constexpr uint32_t SM_SEL = SM_RED + 256;
constexpr uint32_t SM_EP = SM_SEL + 8, SM_WSUM = SM_SEL + 12;
constexpr uint32_t SM_BAR = SM_SEL + 16;
constexpr uint32_t B_WFULL = SM_BAR, B_WEMPTY = B_WFULL + 32, B_XFULL = B_WEMPTY + 32, B_XEMPTY = B_XFULL + 64;
constexpr uint32_t B_RC = B_XEMPTY + 64;
constexpr uint32_t B_COLSUM = B_RC + 16, B_PKF = B_COLSUM + 8, B_FIX = B_PKF + 8, B_DONE = B_FIX + 8;
constexpr uint32_t B_FF = B_DONE + 8;
constexpr uint32_t B_IDX = B_FF + 24;
constexpr uint32_t B_WD = B_IDX + 16, B_WANT = B_WD + 8, B_EPI = B_WANT + 8, B_EP = B_EPI + 8, B_OS = B_EP + 8, B_FD = B_OS + 8;
constexpr uint32_t B_WL = B_FD + 8;
constexpr uint32_t B_RES = B_WL + 32;
constexpr uint32_t B_XE = B_RES + 16;
constexpr uint32_t SM_TOTAL = B_XE + 16;
constexpr int NBAR = (SM_TOTAL - SM_BAR) / 8, NBAR4 = (B_FF - SM_BAR) / 8;
static_assert(((B_EP - SM_BAR) / 8 * 4) / NBAR == 3, "warp 15 initialises B_EP");
constexpr uint32_t FSLOT = 16384;
static_assert(SM_TOTAL + 256 <= 232448, "smem");

struct __align__(1024) Checked {
  uint32_t candrow[2][128][288];
  uint4 halo[128][2][2][5][32];
  uint8_t wpack[8][12 * WSTAGE];
  uint8_t act[3][16][2][73728];
};
struct __align__(1024) Scratch {
  uint4 cand[2][8][128];
  uint4 ypart[72][128][2];
  uint32_t x2msg[8][576];
  uint32_t fixmsg[8][256];
  uint32_t flagP[8][12][32];
  uint32_t flagX[16][2][32];
  uint32_t epoch[128][8];
  uint4 stats0[16][2][64];
  uint4 statsP[16][2][8][64];
  float colpart[8][8][216];
  Checked chk[2];
};
__device__ Scratch g_s;
#define GA(member, off) (gb + offsetof(Scratch, member) + (uint32_t)(off))
#define GC(member, off) (gb + offsetof(Scratch, chk) + offsetof(Checked, member) + (uint32_t)((off) + (epoch & 1) * (uint32_t)sizeof(Checked)))
constexpr uint32_t ACT = 16 * 2 * 73728;

#define TR(role, i)
#define TRL(role, i)
#define TRDUMP(role)
#define TRW(i)
#define TRZ(i)
#define TRQ(i)

__device__ __forceinline__ void wgmma_n144(float* d, uint32_t alo, uint32_t ahi, uint32_t blo) {
  asm volatile("{\n.reg .b64 da, db;\nmov.b64 da, {%72, %73};\nmov.b64 db, {%74, 8};\n"
    "wgmma.mma_async.sync.aligned.m64n144k16.f32.bf16.bf16 "
    "{%0, %1, %2, %3, %4, %5, %6, %7, %8, %9, %10, %11, %12, %13, %14, %15, %16, %17, %18, %19, %20, %21, %22, %23, %24, %25, %26, %27, %28, %29, %30, %31, %32, %33, %34, %35, %36, %37, %38, %39, %40, %41, %42, %43, %44, %45, %46, %47, %48, %49, %50, %51, %52, %53, %54, %55, %56, %57, %58, %59, %60, %61, %62, %63, %64, %65, %66, %67, %68, %69, %70, %71}, da, db, 1, 1, 1, 0, 1;\n}\n"
    : "+f"(d[0]), "+f"(d[1]), "+f"(d[2]), "+f"(d[3]), "+f"(d[4]), "+f"(d[5]), "+f"(d[6]), "+f"(d[7]), "+f"(d[8]),
      "+f"(d[9]), "+f"(d[10]), "+f"(d[11]), "+f"(d[12]), "+f"(d[13]), "+f"(d[14]), "+f"(d[15]), "+f"(d[16]), "+f"(d[17]),
      "+f"(d[18]), "+f"(d[19]), "+f"(d[20]), "+f"(d[21]), "+f"(d[22]), "+f"(d[23]), "+f"(d[24]), "+f"(d[25]), "+f"(d[26]),
      "+f"(d[27]), "+f"(d[28]), "+f"(d[29]), "+f"(d[30]), "+f"(d[31]), "+f"(d[32]), "+f"(d[33]), "+f"(d[34]), "+f"(d[35]),
      "+f"(d[36]), "+f"(d[37]), "+f"(d[38]), "+f"(d[39]), "+f"(d[40]), "+f"(d[41]), "+f"(d[42]), "+f"(d[43]), "+f"(d[44]),
      "+f"(d[45]), "+f"(d[46]), "+f"(d[47]), "+f"(d[48]), "+f"(d[49]), "+f"(d[50]), "+f"(d[51]), "+f"(d[52]), "+f"(d[53]),
      "+f"(d[54]), "+f"(d[55]), "+f"(d[56]), "+f"(d[57]), "+f"(d[58]), "+f"(d[59]), "+f"(d[60]), "+f"(d[61]), "+f"(d[62]),
      "+f"(d[63]), "+f"(d[64]), "+f"(d[65]), "+f"(d[66]), "+f"(d[67]), "+f"(d[68]), "+f"(d[69]), "+f"(d[70]), "+f"(d[71])
    : "r"(alo), "r"(ahi), "r"(blo));
}
__device__ __forceinline__ void wgmma_n144_set(float* d, const uint32_t* a, uint32_t blo) {
  asm volatile("{\n.reg .b64 db;\nmov.b64 db, {%76, 2};\n"
    "wgmma.mma_async.sync.aligned.m64n144k16.f32.bf16.bf16 "
    "{%0, %1, %2, %3, %4, %5, %6, %7, %8, %9, %10, %11, %12, %13, %14, %15, %16, %17, %18, %19, %20, %21, %22, %23, %24, %25, %26, %27, %28, %29, %30, %31, %32, %33, %34, %35, %36, %37, %38, %39, %40, %41, %42, %43, %44, %45, %46, %47, %48, %49, %50, %51, %52, %53, %54, %55, %56, %57, %58, %59, %60, %61, %62, %63, %64, %65, %66, %67, %68, %69, %70, %71}, {%72, %73, %74, %75}, db, 0, -1, 1, 1;\n}\n"
    : "=f"(d[0]), "=f"(d[1]), "=f"(d[2]), "=f"(d[3]), "=f"(d[4]), "=f"(d[5]), "=f"(d[6]), "=f"(d[7]), "=f"(d[8]),
      "=f"(d[9]), "=f"(d[10]), "=f"(d[11]), "=f"(d[12]), "=f"(d[13]), "=f"(d[14]), "=f"(d[15]), "=f"(d[16]), "=f"(d[17]),
      "=f"(d[18]), "=f"(d[19]), "=f"(d[20]), "=f"(d[21]), "=f"(d[22]), "=f"(d[23]), "=f"(d[24]), "=f"(d[25]), "=f"(d[26]),
      "=f"(d[27]), "=f"(d[28]), "=f"(d[29]), "=f"(d[30]), "=f"(d[31]), "=f"(d[32]), "=f"(d[33]), "=f"(d[34]), "=f"(d[35]),
      "=f"(d[36]), "=f"(d[37]), "=f"(d[38]), "=f"(d[39]), "=f"(d[40]), "=f"(d[41]), "=f"(d[42]), "=f"(d[43]), "=f"(d[44]),
      "=f"(d[45]), "=f"(d[46]), "=f"(d[47]), "=f"(d[48]), "=f"(d[49]), "=f"(d[50]), "=f"(d[51]), "=f"(d[52]), "=f"(d[53]),
      "=f"(d[54]), "=f"(d[55]), "=f"(d[56]), "=f"(d[57]), "=f"(d[58]), "=f"(d[59]), "=f"(d[60]), "=f"(d[61]), "=f"(d[62]),
      "=f"(d[63]), "=f"(d[64]), "=f"(d[65]), "=f"(d[66]), "=f"(d[67]), "=f"(d[68]), "=f"(d[69]), "=f"(d[70]), "=f"(d[71])
    : "r"(a[0]), "r"(a[1]), "r"(a[2]), "r"(a[3]), "r"(blo));
}
__device__ __forceinline__ void wgmma_n144_add(float* d, const uint32_t* a, uint32_t blo) {
  asm volatile("{\n.reg .b64 db;\nmov.b64 db, {%76, 2};\n"
    "wgmma.mma_async.sync.aligned.m64n144k16.f32.bf16.bf16 "
    "{%0, %1, %2, %3, %4, %5, %6, %7, %8, %9, %10, %11, %12, %13, %14, %15, %16, %17, %18, %19, %20, %21, %22, %23, %24, %25, %26, %27, %28, %29, %30, %31, %32, %33, %34, %35, %36, %37, %38, %39, %40, %41, %42, %43, %44, %45, %46, %47, %48, %49, %50, %51, %52, %53, %54, %55, %56, %57, %58, %59, %60, %61, %62, %63, %64, %65, %66, %67, %68, %69, %70, %71}, {%72, %73, %74, %75}, db, 1, -1, 1, 1;\n}\n"
    : "+f"(d[0]), "+f"(d[1]), "+f"(d[2]), "+f"(d[3]), "+f"(d[4]), "+f"(d[5]), "+f"(d[6]), "+f"(d[7]), "+f"(d[8]),
      "+f"(d[9]), "+f"(d[10]), "+f"(d[11]), "+f"(d[12]), "+f"(d[13]), "+f"(d[14]), "+f"(d[15]), "+f"(d[16]), "+f"(d[17]),
      "+f"(d[18]), "+f"(d[19]), "+f"(d[20]), "+f"(d[21]), "+f"(d[22]), "+f"(d[23]), "+f"(d[24]), "+f"(d[25]), "+f"(d[26]),
      "+f"(d[27]), "+f"(d[28]), "+f"(d[29]), "+f"(d[30]), "+f"(d[31]), "+f"(d[32]), "+f"(d[33]), "+f"(d[34]), "+f"(d[35]),
      "+f"(d[36]), "+f"(d[37]), "+f"(d[38]), "+f"(d[39]), "+f"(d[40]), "+f"(d[41]), "+f"(d[42]), "+f"(d[43]), "+f"(d[44]),
      "+f"(d[45]), "+f"(d[46]), "+f"(d[47]), "+f"(d[48]), "+f"(d[49]), "+f"(d[50]), "+f"(d[51]), "+f"(d[52]), "+f"(d[53]),
      "+f"(d[54]), "+f"(d[55]), "+f"(d[56]), "+f"(d[57]), "+f"(d[58]), "+f"(d[59]), "+f"(d[60]), "+f"(d[61]), "+f"(d[62]),
      "+f"(d[63]), "+f"(d[64]), "+f"(d[65]), "+f"(d[66]), "+f"(d[67]), "+f"(d[68]), "+f"(d[69]), "+f"(d[70]), "+f"(d[71])
    : "r"(a[0]), "r"(a[1]), "r"(a[2]), "r"(a[3]), "r"(blo));
}
__device__ __forceinline__ void wgmma_n72(float* d, uint32_t alo, uint32_t ahi, uint32_t blo) {
  asm volatile("{\n.reg .b64 da, db;\nmov.b64 da, {%36, %37};\nmov.b64 db, {%38, 8};\n"
    "wgmma.mma_async.sync.aligned.m64n72k16.f32.bf16.bf16 "
    "{%0, %1, %2, %3, %4, %5, %6, %7, %8, %9, %10, %11, %12, %13, %14, %15, %16, %17, %18, %19, %20, %21, %22, %23, %24, %25, %26, %27, %28, %29, %30, %31, %32, %33, %34, %35}, da, db, 1, 1, 1, 0, 1;\n}\n"
    : "+f"(d[0]), "+f"(d[1]), "+f"(d[2]), "+f"(d[3]), "+f"(d[4]), "+f"(d[5]), "+f"(d[6]), "+f"(d[7]), "+f"(d[8]),
      "+f"(d[9]), "+f"(d[10]), "+f"(d[11]), "+f"(d[12]), "+f"(d[13]), "+f"(d[14]), "+f"(d[15]), "+f"(d[16]), "+f"(d[17]),
      "+f"(d[18]), "+f"(d[19]), "+f"(d[20]), "+f"(d[21]), "+f"(d[22]), "+f"(d[23]), "+f"(d[24]), "+f"(d[25]), "+f"(d[26]),
      "+f"(d[27]), "+f"(d[28]), "+f"(d[29]), "+f"(d[30]), "+f"(d[31]), "+f"(d[32]), "+f"(d[33]), "+f"(d[34]), "+f"(d[35])
    : "r"(alo), "r"(ahi), "r"(blo));
}
__device__ __forceinline__ void wgmma_n72_set(float* d, const uint32_t* a, uint32_t blo) {
  asm volatile("{\n.reg .b64 db;\nmov.b64 db, {%40, 2};\n"
    "wgmma.mma_async.sync.aligned.m64n72k16.f32.bf16.bf16 "
    "{%0, %1, %2, %3, %4, %5, %6, %7, %8, %9, %10, %11, %12, %13, %14, %15, %16, %17, %18, %19, %20, %21, %22, %23, %24, %25, %26, %27, %28, %29, %30, %31, %32, %33, %34, %35}, {%36, %37, %38, %39}, db, 0, -1, 1, 1;\n}\n"
    : "=f"(d[0]), "=f"(d[1]), "=f"(d[2]), "=f"(d[3]), "=f"(d[4]), "=f"(d[5]), "=f"(d[6]), "=f"(d[7]), "=f"(d[8]),
      "=f"(d[9]), "=f"(d[10]), "=f"(d[11]), "=f"(d[12]), "=f"(d[13]), "=f"(d[14]), "=f"(d[15]), "=f"(d[16]), "=f"(d[17]),
      "=f"(d[18]), "=f"(d[19]), "=f"(d[20]), "=f"(d[21]), "=f"(d[22]), "=f"(d[23]), "=f"(d[24]), "=f"(d[25]), "=f"(d[26]),
      "=f"(d[27]), "=f"(d[28]), "=f"(d[29]), "=f"(d[30]), "=f"(d[31]), "=f"(d[32]), "=f"(d[33]), "=f"(d[34]), "=f"(d[35])
    : "r"(a[0]), "r"(a[1]), "r"(a[2]), "r"(a[3]), "r"(blo));
}
__device__ __forceinline__ void wgmma_n72_add(float* d, const uint32_t* a, uint32_t blo) {
  asm volatile("{\n.reg .b64 db;\nmov.b64 db, {%40, 2};\n"
    "wgmma.mma_async.sync.aligned.m64n72k16.f32.bf16.bf16 "
    "{%0, %1, %2, %3, %4, %5, %6, %7, %8, %9, %10, %11, %12, %13, %14, %15, %16, %17, %18, %19, %20, %21, %22, %23, %24, %25, %26, %27, %28, %29, %30, %31, %32, %33, %34, %35}, {%36, %37, %38, %39}, db, 1, -1, 1, 1;\n}\n"
    : "+f"(d[0]), "+f"(d[1]), "+f"(d[2]), "+f"(d[3]), "+f"(d[4]), "+f"(d[5]), "+f"(d[6]), "+f"(d[7]), "+f"(d[8]),
      "+f"(d[9]), "+f"(d[10]), "+f"(d[11]), "+f"(d[12]), "+f"(d[13]), "+f"(d[14]), "+f"(d[15]), "+f"(d[16]), "+f"(d[17]),
      "+f"(d[18]), "+f"(d[19]), "+f"(d[20]), "+f"(d[21]), "+f"(d[22]), "+f"(d[23]), "+f"(d[24]), "+f"(d[25]), "+f"(d[26]),
      "+f"(d[27]), "+f"(d[28]), "+f"(d[29]), "+f"(d[30]), "+f"(d[31]), "+f"(d[32]), "+f"(d[33]), "+f"(d[34]), "+f"(d[35])
    : "r"(a[0]), "r"(a[1]), "r"(a[2]), "r"(a[3]), "r"(blo));
}
__device__ __forceinline__ void q_tail(float* d, uint32_t* v, uint32_t ahi, const uint32_t* dsc, const uint32_t* bar, const uint32_t* adr) {
  asm volatile(
    "{\n.reg .pred p<2>, q;\n.reg .b64 da, db;\n.reg .u32 n;\n"
    "mbarrier.test_wait.parity.shared::cta.b64 p0, [%116], %117;\n"
    "mbarrier.test_wait.parity.shared::cta.b64 p1, [%118], %119;\n"
    "ld.volatile.shared.u32 %108, [%120];\n"
    "mov.b64 da, {%110, %109};\nmov.b64 db, {%111, 8};\n"
    "wgmma.mma_async.sync.aligned.m64n144k16.f32.bf16.bf16 {%36, %37, %38, %39, %40, %41, %42, %43, %44, %45, %46, %47, %48, %49, %50, %51, %52, %53, %54, %55, %56, %57, %58, %59, %60, %61, %62, %63, %64, %65, %66, %67, %68, %69, %70, %71, %72, %73, %74, %75, %76, %77, %78, %79, %80, %81, %82, %83, %84, %85, %86, %87, %88, %89, %90, %91, %92, %93, %94, %95, %96, %97, %98, %99, %100, %101, %102, %103, %104, %105, %106, %107}, da, db, 1, 1, 1, 0, 1;\n"
    "mov.b64 da, {%112, %109};\nmov.b64 db, {%113, 8};\n"
    "wgmma.mma_async.sync.aligned.m64n72k16.f32.bf16.bf16 {%0, %1, %2, %3, %4, %5, %6, %7, %8, %9, %10, %11, %12, %13, %14, %15, %16, %17, %18, %19, %20, %21, %22, %23, %24, %25, %26, %27, %28, %29, %30, %31, %32, %33, %34, %35}, da, db, 1, 1, 1, 0, 1;\n"
    "mov.b64 da, {%114, %109};\nmov.b64 db, {%115, 8};\n"
    "wgmma.mma_async.sync.aligned.m64n144k16.f32.bf16.bf16 {%36, %37, %38, %39, %40, %41, %42, %43, %44, %45, %46, %47, %48, %49, %50, %51, %52, %53, %54, %55, %56, %57, %58, %59, %60, %61, %62, %63, %64, %65, %66, %67, %68, %69, %70, %71, %72, %73, %74, %75, %76, %77, %78, %79, %80, %81, %82, %83, %84, %85, %86, %87, %88, %89, %90, %91, %92, %93, %94, %95, %96, %97, %98, %99, %100, %101, %102, %103, %104, %105, %106, %107}, da, db, 1, 1, 1, 0, 1;\n"
    "wgmma.commit_group.sync.aligned;\n"
    "@p0 bra.uni D0;\nmov.u32 n, 0;\nW0:\nmbarrier.try_wait.parity.shared::cta.b64 q, [%116], %117;\n@q bra.uni R0;\nadd.u32 n, n, 1;\nsetp.lt.u32 q, n, 8192;\n@q bra.uni W0;\nR0:\n"
    "D0:\n"
    "@p1 bra.uni D1;\nmov.u32 n, 0;\nW1:\nmbarrier.try_wait.parity.shared::cta.b64 q, [%118], %119;\n@q bra.uni R1;\nadd.u32 n, n, 1;\nsetp.lt.u32 q, n, 8192;\n@q bra.uni W1;\nR1:\n"
    "ld.volatile.shared.u32 %108, [%120];\n"
    "D1:\n"
    "}\n"
    : "+f"(d[0]), "+f"(d[1]), "+f"(d[2]), "+f"(d[3]), "+f"(d[4]), "+f"(d[5]), "+f"(d[6]), "+f"(d[7]), "+f"(d[8]),
      "+f"(d[9]), "+f"(d[10]), "+f"(d[11]), "+f"(d[12]), "+f"(d[13]), "+f"(d[14]), "+f"(d[15]), "+f"(d[16]), "+f"(d[17]),
      "+f"(d[18]), "+f"(d[19]), "+f"(d[20]), "+f"(d[21]), "+f"(d[22]), "+f"(d[23]), "+f"(d[24]), "+f"(d[25]), "+f"(d[26]),
      "+f"(d[27]), "+f"(d[28]), "+f"(d[29]), "+f"(d[30]), "+f"(d[31]), "+f"(d[32]), "+f"(d[33]), "+f"(d[34]), "+f"(d[35]),
      "+f"(d[36]), "+f"(d[37]), "+f"(d[38]), "+f"(d[39]), "+f"(d[40]), "+f"(d[41]), "+f"(d[42]), "+f"(d[43]), "+f"(d[44]),
      "+f"(d[45]), "+f"(d[46]), "+f"(d[47]), "+f"(d[48]), "+f"(d[49]), "+f"(d[50]), "+f"(d[51]), "+f"(d[52]), "+f"(d[53]),
      "+f"(d[54]), "+f"(d[55]), "+f"(d[56]), "+f"(d[57]), "+f"(d[58]), "+f"(d[59]), "+f"(d[60]), "+f"(d[61]), "+f"(d[62]),
      "+f"(d[63]), "+f"(d[64]), "+f"(d[65]), "+f"(d[66]), "+f"(d[67]), "+f"(d[68]), "+f"(d[69]), "+f"(d[70]), "+f"(d[71]),
      "+f"(d[72]), "+f"(d[73]), "+f"(d[74]), "+f"(d[75]), "+f"(d[76]), "+f"(d[77]), "+f"(d[78]), "+f"(d[79]), "+f"(d[80]),
      "+f"(d[81]), "+f"(d[82]), "+f"(d[83]), "+f"(d[84]), "+f"(d[85]), "+f"(d[86]), "+f"(d[87]), "+f"(d[88]), "+f"(d[89]),
      "+f"(d[90]), "+f"(d[91]), "+f"(d[92]), "+f"(d[93]), "+f"(d[94]), "+f"(d[95]), "+f"(d[96]), "+f"(d[97]), "+f"(d[98]),
      "+f"(d[99]), "+f"(d[100]), "+f"(d[101]), "+f"(d[102]), "+f"(d[103]), "+f"(d[104]), "+f"(d[105]), "+f"(d[106]), "+f"(d[107]),
      "=&r"(v[0])
    : "r"(ahi), "r"(dsc[0]), "r"(dsc[1]), "r"(dsc[2]), "r"(dsc[3]), "r"(dsc[4]), "r"(dsc[5]), "r"(bar[0]), "r"(bar[1]), "r"(bar[2]), "r"(bar[3]), "r"(adr[0]) : "memory");
}
__device__ __forceinline__ void kv_tail(float* d, uint32_t* v, uint32_t ahi, const uint32_t* dsc, const uint32_t* bar, const uint32_t* adr) {
  asm volatile(
    "{\n.reg .pred p<3>, q;\n.reg .b64 da, db;\n.reg .u32 n;\n"
    "mbarrier.test_wait.parity.shared::cta.b64 p0, [%79], %80;\n"
    "mbarrier.test_wait.parity.shared::cta.b64 p1, [%81], %82;\n"
    "mbarrier.test_wait.parity.shared::cta.b64 p2, [%83], %84;\n"
    "ld.volatile.shared.u32 %72, [%85];\n"
    "ld.volatile.shared.u32 %73, [%86];\n"
    "mov.b64 da, {%75, %74};\nmov.b64 db, {%76, 8};\n"
    "wgmma.mma_async.sync.aligned.m64n144k16.f32.bf16.bf16 {%0, %1, %2, %3, %4, %5, %6, %7, %8, %9, %10, %11, %12, %13, %14, %15, %16, %17, %18, %19, %20, %21, %22, %23, %24, %25, %26, %27, %28, %29, %30, %31, %32, %33, %34, %35, %36, %37, %38, %39, %40, %41, %42, %43, %44, %45, %46, %47, %48, %49, %50, %51, %52, %53, %54, %55, %56, %57, %58, %59, %60, %61, %62, %63, %64, %65, %66, %67, %68, %69, %70, %71}, da, db, 1, 1, 1, 0, 1;\n"
    "mov.b64 da, {%77, %74};\nmov.b64 db, {%78, 8};\n"
    "wgmma.mma_async.sync.aligned.m64n144k16.f32.bf16.bf16 {%0, %1, %2, %3, %4, %5, %6, %7, %8, %9, %10, %11, %12, %13, %14, %15, %16, %17, %18, %19, %20, %21, %22, %23, %24, %25, %26, %27, %28, %29, %30, %31, %32, %33, %34, %35, %36, %37, %38, %39, %40, %41, %42, %43, %44, %45, %46, %47, %48, %49, %50, %51, %52, %53, %54, %55, %56, %57, %58, %59, %60, %61, %62, %63, %64, %65, %66, %67, %68, %69, %70, %71}, da, db, 1, 1, 1, 0, 1;\n"
    "wgmma.commit_group.sync.aligned;\n"
    "@p0 bra.uni D0;\nmov.u32 n, 0;\nW0:\nmbarrier.try_wait.parity.shared::cta.b64 q, [%79], %80;\n@q bra.uni R0;\nadd.u32 n, n, 1;\nsetp.lt.u32 q, n, 8192;\n@q bra.uni W0;\nR0:\n"
    "D0:\n"
    "@p1 bra.uni D1;\nmov.u32 n, 0;\nW1:\nmbarrier.try_wait.parity.shared::cta.b64 q, [%81], %82;\n@q bra.uni R1;\nadd.u32 n, n, 1;\nsetp.lt.u32 q, n, 8192;\n@q bra.uni W1;\nR1:\n"
    "ld.volatile.shared.u32 %72, [%85];\n"
    "D1:\n"
    "@p2 bra.uni D2;\nmov.u32 n, 0;\nW2:\nmbarrier.try_wait.parity.shared::cta.b64 q, [%83], %84;\n@q bra.uni R2;\nadd.u32 n, n, 1;\nsetp.lt.u32 q, n, 8192;\n@q bra.uni W2;\nR2:\n"
    "ld.volatile.shared.u32 %73, [%86];\n"
    "D2:\n"
    "}\n"
    : "+f"(d[36]), "+f"(d[37]), "+f"(d[38]), "+f"(d[39]), "+f"(d[40]), "+f"(d[41]), "+f"(d[42]), "+f"(d[43]), "+f"(d[44]),
      "+f"(d[45]), "+f"(d[46]), "+f"(d[47]), "+f"(d[48]), "+f"(d[49]), "+f"(d[50]), "+f"(d[51]), "+f"(d[52]), "+f"(d[53]),
      "+f"(d[54]), "+f"(d[55]), "+f"(d[56]), "+f"(d[57]), "+f"(d[58]), "+f"(d[59]), "+f"(d[60]), "+f"(d[61]), "+f"(d[62]),
      "+f"(d[63]), "+f"(d[64]), "+f"(d[65]), "+f"(d[66]), "+f"(d[67]), "+f"(d[68]), "+f"(d[69]), "+f"(d[70]), "+f"(d[71]),
      "+f"(d[72]), "+f"(d[73]), "+f"(d[74]), "+f"(d[75]), "+f"(d[76]), "+f"(d[77]), "+f"(d[78]), "+f"(d[79]), "+f"(d[80]),
      "+f"(d[81]), "+f"(d[82]), "+f"(d[83]), "+f"(d[84]), "+f"(d[85]), "+f"(d[86]), "+f"(d[87]), "+f"(d[88]), "+f"(d[89]),
      "+f"(d[90]), "+f"(d[91]), "+f"(d[92]), "+f"(d[93]), "+f"(d[94]), "+f"(d[95]), "+f"(d[96]), "+f"(d[97]), "+f"(d[98]),
      "+f"(d[99]), "+f"(d[100]), "+f"(d[101]), "+f"(d[102]), "+f"(d[103]), "+f"(d[104]), "+f"(d[105]), "+f"(d[106]), "+f"(d[107]),
      "=&r"(v[0]), "=&r"(v[1])
    : "r"(ahi), "r"(dsc[0]), "r"(dsc[1]), "r"(dsc[2]), "r"(dsc[3]), "r"(bar[0]), "r"(bar[1]), "r"(bar[2]), "r"(bar[3]), "r"(bar[4]), "r"(bar[5]), "r"(adr[0]), "r"(adr[1]) : "memory");
}
__device__ __forceinline__ void kv_last(float* d, uint32_t* v, uint32_t ahi, const uint32_t* dsc, const uint32_t* bar, const uint32_t* adr) {
  asm volatile(
    "{\n.reg .pred p<1>, q;\n.reg .b64 da, db;\n.reg .u32 n;\n"
    "mbarrier.test_wait.parity.shared::cta.b64 p0, [%81], %82;\n"
    "mov.b64 da, {%73, %72};\nmov.b64 db, {%74, 8};\n"
    "wgmma.mma_async.sync.aligned.m64n144k16.f32.bf16.bf16 {%0, %1, %2, %3, %4, %5, %6, %7, %8, %9, %10, %11, %12, %13, %14, %15, %16, %17, %18, %19, %20, %21, %22, %23, %24, %25, %26, %27, %28, %29, %30, %31, %32, %33, %34, %35, %36, %37, %38, %39, %40, %41, %42, %43, %44, %45, %46, %47, %48, %49, %50, %51, %52, %53, %54, %55, %56, %57, %58, %59, %60, %61, %62, %63, %64, %65, %66, %67, %68, %69, %70, %71}, da, db, 1, 1, 1, 0, 1;\n"
    "mov.b64 da, {%75, %72};\nmov.b64 db, {%76, 8};\n"
    "wgmma.mma_async.sync.aligned.m64n144k16.f32.bf16.bf16 {%0, %1, %2, %3, %4, %5, %6, %7, %8, %9, %10, %11, %12, %13, %14, %15, %16, %17, %18, %19, %20, %21, %22, %23, %24, %25, %26, %27, %28, %29, %30, %31, %32, %33, %34, %35, %36, %37, %38, %39, %40, %41, %42, %43, %44, %45, %46, %47, %48, %49, %50, %51, %52, %53, %54, %55, %56, %57, %58, %59, %60, %61, %62, %63, %64, %65, %66, %67, %68, %69, %70, %71}, da, db, 1, 1, 1, 0, 1;\n"
    "mov.b64 da, {%77, %72};\nmov.b64 db, {%78, 8};\n"
    "wgmma.mma_async.sync.aligned.m64n144k16.f32.bf16.bf16 {%0, %1, %2, %3, %4, %5, %6, %7, %8, %9, %10, %11, %12, %13, %14, %15, %16, %17, %18, %19, %20, %21, %22, %23, %24, %25, %26, %27, %28, %29, %30, %31, %32, %33, %34, %35, %36, %37, %38, %39, %40, %41, %42, %43, %44, %45, %46, %47, %48, %49, %50, %51, %52, %53, %54, %55, %56, %57, %58, %59, %60, %61, %62, %63, %64, %65, %66, %67, %68, %69, %70, %71}, da, db, 1, 1, 1, 0, 1;\n"
    "mov.b64 da, {%79, %72};\nmov.b64 db, {%80, 8};\n"
    "wgmma.mma_async.sync.aligned.m64n144k16.f32.bf16.bf16 {%0, %1, %2, %3, %4, %5, %6, %7, %8, %9, %10, %11, %12, %13, %14, %15, %16, %17, %18, %19, %20, %21, %22, %23, %24, %25, %26, %27, %28, %29, %30, %31, %32, %33, %34, %35, %36, %37, %38, %39, %40, %41, %42, %43, %44, %45, %46, %47, %48, %49, %50, %51, %52, %53, %54, %55, %56, %57, %58, %59, %60, %61, %62, %63, %64, %65, %66, %67, %68, %69, %70, %71}, da, db, 1, 1, 1, 0, 1;\n"
    "wgmma.commit_group.sync.aligned;\n"
    "@p0 bra.uni D0;\nmov.u32 n, 0;\nW0:\nmbarrier.try_wait.parity.shared::cta.b64 q, [%81], %82;\n@q bra.uni R0;\nadd.u32 n, n, 1;\nsetp.lt.u32 q, n, 8192;\n@q bra.uni W0;\nR0:\n"
    "D0:\n"
    "}\n"
    : "+f"(d[36]), "+f"(d[37]), "+f"(d[38]), "+f"(d[39]), "+f"(d[40]), "+f"(d[41]), "+f"(d[42]), "+f"(d[43]), "+f"(d[44]),
      "+f"(d[45]), "+f"(d[46]), "+f"(d[47]), "+f"(d[48]), "+f"(d[49]), "+f"(d[50]), "+f"(d[51]), "+f"(d[52]), "+f"(d[53]),
      "+f"(d[54]), "+f"(d[55]), "+f"(d[56]), "+f"(d[57]), "+f"(d[58]), "+f"(d[59]), "+f"(d[60]), "+f"(d[61]), "+f"(d[62]),
      "+f"(d[63]), "+f"(d[64]), "+f"(d[65]), "+f"(d[66]), "+f"(d[67]), "+f"(d[68]), "+f"(d[69]), "+f"(d[70]), "+f"(d[71]),
      "+f"(d[72]), "+f"(d[73]), "+f"(d[74]), "+f"(d[75]), "+f"(d[76]), "+f"(d[77]), "+f"(d[78]), "+f"(d[79]), "+f"(d[80]),
      "+f"(d[81]), "+f"(d[82]), "+f"(d[83]), "+f"(d[84]), "+f"(d[85]), "+f"(d[86]), "+f"(d[87]), "+f"(d[88]), "+f"(d[89]),
      "+f"(d[90]), "+f"(d[91]), "+f"(d[92]), "+f"(d[93]), "+f"(d[94]), "+f"(d[95]), "+f"(d[96]), "+f"(d[97]), "+f"(d[98]),
      "+f"(d[99]), "+f"(d[100]), "+f"(d[101]), "+f"(d[102]), "+f"(d[103]), "+f"(d[104]), "+f"(d[105]), "+f"(d[106]), "+f"(d[107])
    : "r"(ahi), "r"(dsc[0]), "r"(dsc[1]), "r"(dsc[2]), "r"(dsc[3]), "r"(dsc[4]), "r"(dsc[5]), "r"(dsc[6]), "r"(dsc[7]), "r"(bar[0]), "r"(bar[1]) : "memory");
}
__device__ __forceinline__ void o_tail(float* d, uint32_t* v, uint32_t ahi, const uint32_t* dsc, const uint32_t* bar, const uint32_t* adr) {
  asm volatile(
    "{\n.reg .pred p<1>, q;\n.reg .b64 da, db;\n.reg .u32 n;\n"
    "mbarrier.test_wait.parity.shared::cta.b64 p0, [%42], %43;\n"
    "ld.volatile.shared.u32 %36, [%44];\n"
    "mov.b64 da, {%38, %37};\nmov.b64 db, {%39, 8};\n"
    "wgmma.mma_async.sync.aligned.m64n72k16.f32.bf16.bf16 {%0, %1, %2, %3, %4, %5, %6, %7, %8, %9, %10, %11, %12, %13, %14, %15, %16, %17, %18, %19, %20, %21, %22, %23, %24, %25, %26, %27, %28, %29, %30, %31, %32, %33, %34, %35}, da, db, 1, 1, 1, 0, 1;\n"
    "mov.b64 da, {%40, %37};\nmov.b64 db, {%41, 8};\n"
    "wgmma.mma_async.sync.aligned.m64n72k16.f32.bf16.bf16 {%0, %1, %2, %3, %4, %5, %6, %7, %8, %9, %10, %11, %12, %13, %14, %15, %16, %17, %18, %19, %20, %21, %22, %23, %24, %25, %26, %27, %28, %29, %30, %31, %32, %33, %34, %35}, da, db, 1, 1, 1, 0, 1;\n"
    "wgmma.commit_group.sync.aligned;\n"
    "@p0 bra.uni D0;\nmov.u32 n, 0;\nW0:\nmbarrier.try_wait.parity.shared::cta.b64 q, [%42], %43;\n@q bra.uni R0;\nadd.u32 n, n, 1;\nsetp.lt.u32 q, n, 8192;\n@q bra.uni W0;\nR0:\n"
    "ld.volatile.shared.u32 %36, [%44];\n"
    "D0:\n"
    "}\n"
    : "+f"(d[0]), "+f"(d[1]), "+f"(d[2]), "+f"(d[3]), "+f"(d[4]), "+f"(d[5]), "+f"(d[6]), "+f"(d[7]), "+f"(d[8]),
      "+f"(d[9]), "+f"(d[10]), "+f"(d[11]), "+f"(d[12]), "+f"(d[13]), "+f"(d[14]), "+f"(d[15]), "+f"(d[16]), "+f"(d[17]),
      "+f"(d[18]), "+f"(d[19]), "+f"(d[20]), "+f"(d[21]), "+f"(d[22]), "+f"(d[23]), "+f"(d[24]), "+f"(d[25]), "+f"(d[26]),
      "+f"(d[27]), "+f"(d[28]), "+f"(d[29]), "+f"(d[30]), "+f"(d[31]), "+f"(d[32]), "+f"(d[33]), "+f"(d[34]), "+f"(d[35]),
      "=&r"(v[0])
    : "r"(ahi), "r"(dsc[0]), "r"(dsc[1]), "r"(dsc[2]), "r"(dsc[3]), "r"(bar[0]), "r"(bar[1]), "r"(adr[0]) : "memory");
}
__device__ __forceinline__ void o_tail2(float* d, uint32_t* v, uint32_t ahi, const uint32_t* dsc, const uint32_t* bar, const uint32_t* adr) {
  asm volatile(
    "{\n.reg .pred p<2>, q;\n.reg .b64 da, db;\n.reg .u32 n;\n"
    "mbarrier.test_wait.parity.shared::cta.b64 p0, [%42], %43;\n"
    "mbarrier.test_wait.parity.shared::cta.b64 p1, [%44], %45;\n"
    "ld.volatile.shared.u32 %36, [%46];\n"
    "mov.b64 da, {%38, %37};\nmov.b64 db, {%39, 8};\n"
    "wgmma.mma_async.sync.aligned.m64n72k16.f32.bf16.bf16 {%0, %1, %2, %3, %4, %5, %6, %7, %8, %9, %10, %11, %12, %13, %14, %15, %16, %17, %18, %19, %20, %21, %22, %23, %24, %25, %26, %27, %28, %29, %30, %31, %32, %33, %34, %35}, da, db, 1, 1, 1, 0, 1;\n"
    "mov.b64 da, {%40, %37};\nmov.b64 db, {%41, 8};\n"
    "wgmma.mma_async.sync.aligned.m64n72k16.f32.bf16.bf16 {%0, %1, %2, %3, %4, %5, %6, %7, %8, %9, %10, %11, %12, %13, %14, %15, %16, %17, %18, %19, %20, %21, %22, %23, %24, %25, %26, %27, %28, %29, %30, %31, %32, %33, %34, %35}, da, db, 1, 1, 1, 0, 1;\n"
    "wgmma.commit_group.sync.aligned;\n"
    "@p0 bra.uni D0;\nmov.u32 n, 0;\nW0:\nmbarrier.try_wait.parity.shared::cta.b64 q, [%42], %43;\n@q bra.uni R0;\nadd.u32 n, n, 1;\nsetp.lt.u32 q, n, 8192;\n@q bra.uni W0;\nR0:\n"
    "D0:\n"
    "@p1 bra.uni D1;\nmov.u32 n, 0;\nW1:\nmbarrier.try_wait.parity.shared::cta.b64 q, [%44], %45;\n@q bra.uni R1;\nadd.u32 n, n, 1;\nsetp.lt.u32 q, n, 8192;\n@q bra.uni W1;\nR1:\n"
    "ld.volatile.shared.u32 %36, [%46];\n"
    "D1:\n"
    "}\n"
    : "+f"(d[0]), "+f"(d[1]), "+f"(d[2]), "+f"(d[3]), "+f"(d[4]), "+f"(d[5]), "+f"(d[6]), "+f"(d[7]), "+f"(d[8]),
      "+f"(d[9]), "+f"(d[10]), "+f"(d[11]), "+f"(d[12]), "+f"(d[13]), "+f"(d[14]), "+f"(d[15]), "+f"(d[16]), "+f"(d[17]),
      "+f"(d[18]), "+f"(d[19]), "+f"(d[20]), "+f"(d[21]), "+f"(d[22]), "+f"(d[23]), "+f"(d[24]), "+f"(d[25]), "+f"(d[26]),
      "+f"(d[27]), "+f"(d[28]), "+f"(d[29]), "+f"(d[30]), "+f"(d[31]), "+f"(d[32]), "+f"(d[33]), "+f"(d[34]), "+f"(d[35]),
      "=&r"(v[0])
    : "r"(ahi), "r"(dsc[0]), "r"(dsc[1]), "r"(dsc[2]), "r"(dsc[3]), "r"(bar[0]), "r"(bar[1]), "r"(bar[2]), "r"(bar[3]), "r"(adr[0]) : "memory");
}

DEVI void mbar_init(uint32_t b, int c) { asm volatile("mbarrier.init.shared::cta.b64 [%0], %1;" ::"r"(b), "r"(c)); }
DEVI void mbar_arrive(uint32_t b) { asm volatile("mbarrier.arrive.shared::cta.b64 _, [%0];" ::"r"(b) : "memory"); }
DEVI void mbar_expect(uint32_t b, uint32_t tx) {
  asm volatile("mbarrier.arrive.expect_tx.shared::cta.b64 _, [%0], %1;" ::"r"(b), "r"(tx) : "memory");
}
DEVI void mbar_wait(uint32_t b, uint32_t ph) {
  asm volatile(
      "{\n.reg .pred p;\n.reg .u32 n;\nmov.u32 n, 0;\n"
      "LW:\nmbarrier.try_wait.parity.shared::cta.b64 p, [%0], %1;\n"
      "@p bra LD;\nadd.u32 n, n, 1;\nsetp.lt.u32 p, n, 8192;\n@p bra LW;\nLD:\n}\n" ::"r"(b), "r"(ph)
      : "memory");
}
DEVI void mbar_wait2(uint32_t a, uint32_t pa, uint32_t b, uint32_t pb) {
  asm volatile(
      "{\n.reg .pred p, q;\n.reg .u32 n;\nmov.u32 n, 0;\n"
      "LW:\nmbarrier.try_wait.parity.shared::cta.b64 p, [%0], %1;\nmbarrier.try_wait.parity.shared::cta.b64 q, [%2], %3;\n"
      "and.pred p, p, q;\n@p bra LD;\nadd.u32 n, n, 1;\nsetp.lt.u32 p, n, 8192;\n@p bra LW;\nLD:\n}\n" ::"r"(a), "r"(pa), "r"(b), "r"(pb)
      : "memory");
}
DEVI bool elect() {
  uint32_t el;
  asm volatile("{\n.reg .pred p;\nelect.sync _|p, 0xffffffff;\nselp.u32 %0,1,0,p;\n}\n" : "=r"(el));
  return el;
}
DEVI void bulk_g2s(uint32_t dst, const void* src, uint32_t bytes, uint32_t bar) {
  asm volatile("cp.async.bulk.shared::cluster.global.mbarrier::complete_tx::bytes [%0], [%1], %2, [%3];" ::"r"(dst),
               "l"(src), "r"(bytes), "r"(bar)
               : "memory");
}
DEVI void bulk_g2s_pair(uint32_t dst, const void* src, uint32_t bytes, uint32_t bar) {
  asm volatile("cp.async.bulk.shared::cluster.global.mbarrier::complete_tx::bytes.multicast::cluster [%0], [%1], %2, [%3], %4;" ::"r"(dst),
               "l"(src), "r"(bytes), "r"(bar), "h"((uint16_t)3)
               : "memory");
}
DEVI void mbar_arrive_pair(uint32_t b) {
  asm volatile("mbarrier.arrive.shared::cta.b64 _, [%0];\nmbarrier.arrive.shared::cluster.b64 _, [%1];\n" ::"r"(b), "r"(b ^ 0x1000000u) : "memory");
}
DEVI void cluster_arrive() { asm volatile("barrier.cluster.arrive.relaxed.aligned;" ::: "memory"); }
DEVI void cluster_wait() { asm volatile("barrier.cluster.wait.aligned;" ::: "memory"); }
DEVI void tma3(uint32_t dst, const CUtensorMap* m, int c0, int c1, int c2, uint32_t bar) {
  asm volatile(
      "cp.async.bulk.tensor.3d.shared::cluster.global.mbarrier::complete_tx::bytes [%0], [%1, {%3,%4,%5}], [%2];" ::"r"(dst),
      "l"(m), "r"(bar), "r"(c0), "r"(c1), "r"(c2)
      : "memory");
}
DEVI constexpr uint32_t mkdesc(uint32_t addr, uint32_t lbo) { return ((addr & 0x3FFFF) >> 4) | ((lbo >> 4) << 16); }
DEVI void bar_sync(int id) { asm volatile("bar.sync %0, 128;" ::"r"(id) : "memory"); }
DEVI uint4 ld_msg(const void* p) {
  uint4 v;
  asm volatile("ld.relaxed.gpu.global.v4.u32 {%0,%1,%2,%3}, [%4];" : "=r"(v.x), "=r"(v.y), "=r"(v.z), "=r"(v.w) : "l"(p) : "memory");
  return v;
}
DEVI void st_msg(void* p, uint32_t a, uint32_t b, uint32_t c, uint32_t d) {
  asm volatile("st.relaxed.gpu.global.v4.u32 [%0], {%1,%2,%3,%4};" ::"l"(p), "r"(a), "r"(b), "r"(c), "r"(d) : "memory");
}
DEVI uint4 ld_gen(const void* p) {
  uint4 v;
  asm volatile("ld.relaxed.gpu.v4.u32 {%0,%1,%2,%3}, [%4];" : "=r"(v.x), "=r"(v.y), "=r"(v.z), "=r"(v.w) : "l"(p) : "memory");
  return v;
}
DEVI void st_gen(void* p, uint32_t a, uint32_t b, uint32_t c, uint32_t d) {
  asm volatile("st.relaxed.gpu.v4.u32 [%0], {%1,%2,%3,%4};" ::"l"(p), "r"(a), "r"(b), "r"(c), "r"(d) : "memory");
}
DEVI uint32_t ld_rlx(const void* p) {
  uint32_t v;
  asm volatile("ld.relaxed.gpu.global.u32 %0, [%1];" : "=r"(v) : "l"(p) : "memory");
  return v;
}
DEVI uint2 ld_rlx2(const void* p) {
  uint2 v;
  asm volatile("ld.relaxed.gpu.global.v2.u32 {%0,%1}, [%2];" : "=r"(v.x), "=r"(v.y) : "l"(p) : "memory");
  return v;
}
DEVI void st_rlx(void* p, uint32_t v) { asm volatile("st.relaxed.gpu.global.u32 [%0], %1;" ::"l"(p), "r"(v) : "memory"); }
#define spin_guard(n) if (++n > (1u << 16)) break
DEVI void wait_flags(const uint8_t* p, int word, uint32_t target) {
  uint32_t n = 0;
  p += 4 * word;
  _Pragma("unroll 1") while (__any_sync(0xffffffffu, (int)(ld_rlx(p) - target) < 0)) spin_guard(n);
  asm volatile("fence.acquire.gpu;" ::: "memory");
  asm volatile("fence.proxy.async.global;" ::: "memory");
}
DEVI void bulk_s2g(void* dst, uint32_t src, uint32_t bytes) {
  asm volatile("cp.async.bulk.global.shared::cta.bulk_group [%0], [%1], %2;" ::"l"(dst), "r"(src), "r"(bytes) : "memory");
}
#define ABL 0
DEVI void l2_prefetch(const void* p, uint32_t bytes) { if (!(ABL & 2)) asm volatile("cp.async.bulk.prefetch.L2.global [%0], %1;" ::"l"(p), "r"(bytes) : "memory"); }
DEVI void fence_async_smem() { asm volatile("fence.proxy.async.shared::cta;" ::: "memory"); }
DEVI void tma2(uint32_t dst, const CUtensorMap* m, int c0, int c1, uint32_t bar) {
  asm volatile("cp.async.bulk.tensor.2d.shared::cluster.global.mbarrier::complete_tx::bytes [%0], [%1, {%3,%4}], [%2];" ::"r"(dst),
               "l"(m), "r"(bar), "r"(c0), "r"(c1) : "memory");
}
DEVI void stsm4(uint32_t a, uint32_t r0, uint32_t r1, uint32_t r2, uint32_t r3) {
  asm volatile("stmatrix.sync.aligned.m8n8.x4.shared.b16 [%0], {%1,%2,%3,%4};" ::"r"(a), "r"(r0), "r"(r1), "r"(r2), "r"(r3) : "memory");
}
DEVI void stsm2(uint32_t a, uint32_t r0, uint32_t r1) {
  asm volatile("stmatrix.sync.aligned.m8n8.x2.shared.b16 [%0], {%1,%2};" ::"r"(a), "r"(r0), "r"(r1) : "memory");
}
DEVI uint32_t mbar_test(uint32_t b, uint32_t ph) {
  uint32_t ok;
  asm volatile("{\n.reg .pred p;\nmbarrier.test_wait.parity.shared::cta.b64 p, [%1], %2;\nselp.u32 %0,1,0,p;\n}\n"
               : "=r"(ok) : "r"(b), "r"(ph) : "memory");
  return ok;
}
DEVI void st_rlx2(void* p, uint32_t a, uint32_t b) {
  asm volatile("{\n.reg .b64 v;\nmov.b64 v, {%1,%2};\nst.relaxed.gpu.global.b64 [%0], v;\n}\n" ::"l"(p), "r"(a), "r"(b) : "memory");
}
DEVI float selp(int c, float a, float b) {
  float y;
  asm("{\n.reg .pred p;\nsetp.ne.s32 p, %3, 0;\nselp.f32 %0, %1, %2, p;\n}\n" : "=f"(y) : "f"(a), "f"(b), "r"(c));
  return y;
}
DEVI float ex2(float x) { float y; asm("ex2.approx.ftz.f32 %0, %1;" : "=f"(y) : "f"(x)); return y; }
DEVI float rcp(float x) { float y; asm("rcp.approx.ftz.f32 %0, %1;" : "=f"(y) : "f"(x)); return y; }
DEVI float sqrt_a(float x) { float y; asm("sqrt.approx.ftz.f32 %0, %1;" : "=f"(y) : "f"(x)); return y; }
DEVI void ldsm4t(uint32_t* r, uint32_t a) {
  asm volatile("ldmatrix.sync.aligned.m8n8.x4.trans.shared.b16 {%0,%1,%2,%3}, [%4];"
               : "=r"(r[0]), "=r"(r[1]), "=r"(r[2]), "=r"(r[3]) : "r"(a) : "memory");
}
DEVI void ldsm4(uint32_t* r, uint32_t a) {
  asm volatile("ldmatrix.sync.aligned.m8n8.x4.shared.b16 {%0,%1,%2,%3}, [%4];"
               : "=r"(r[0]), "=r"(r[1]), "=r"(r[2]), "=r"(r[3]) : "r"(a) : "memory");
}
DEVI uint32_t lds16(uint32_t a) {
  uint32_t v;
  asm volatile("ld.shared.u16 %0, [%1];" : "=r"(v) : "r"(a) : "memory");
  return v;
}
DEVI void sts16(uint32_t a, uint32_t x) { asm volatile("st.shared.u16 [%0], %1;" ::"r"(a), "r"(x) : "memory"); }
DEVI uint4 ldg128(const void* p) {
  uint4 v;
  asm volatile("ld.global.nc.v4.u32 {%0,%1,%2,%3}, [%4];" : "=r"(v.x), "=r"(v.y), "=r"(v.z), "=r"(v.w) : "l"(p));
  return v;
}
DEVI uint2 ldg64(const void* p) {
  uint2 v;
  asm volatile("ld.global.nc.v2.u32 {%0,%1}, [%2];" : "=r"(v.x), "=r"(v.y) : "l"(p));
  return v;
}
DEVI uint32_t ldg32(const void* p) {
  uint32_t v;
  asm volatile("ld.global.nc.u32 %0, [%1];" : "=r"(v) : "l"(p));
  return v;
}
DEVI uint4 ldcg128(const void* p) {
  uint4 v;
  asm volatile("ld.global.cg.v4.u32 {%0,%1,%2,%3}, [%4];" : "=r"(v.x), "=r"(v.y), "=r"(v.z), "=r"(v.w) : "l"(p) : "memory");
  return v;
}
DEVI uint2 ldcg64(const void* p) {
  uint2 v;
  asm volatile("ld.global.cg.v2.u32 {%0,%1}, [%2];" : "=r"(v.x), "=r"(v.y) : "l"(p) : "memory");
  return v;
}
DEVI uint32_t ldcg32(const void* p) {
  uint32_t v;
  asm volatile("ld.global.cg.u32 %0, [%1];" : "=r"(v) : "l"(p) : "memory");
  return v;
}
DEVI void stg128(void* p, uint32_t a, uint32_t b, uint32_t c, uint32_t d) {
  asm volatile("st.global.v4.u32 [%0], {%1,%2,%3,%4};" ::"l"(p), "r"(a), "r"(b), "r"(c), "r"(d) : "memory");
}
DEVI void stg32(void* p, uint32_t a) { asm volatile("st.global.u32 [%0], %1;" ::"l"(p), "r"(a) : "memory"); }
DEVI uint4 lds128(uint32_t a) {
  uint4 v;
  asm volatile("ld.shared.v4.u32 {%0,%1,%2,%3}, [%4];" : "=r"(v.x), "=r"(v.y), "=r"(v.z), "=r"(v.w) : "r"(a) : "memory");
  return v;
}
DEVI uint2 lds64(uint32_t a) {
  uint2 v;
  asm volatile("ld.shared.v2.u32 {%0,%1}, [%2];" : "=r"(v.x), "=r"(v.y) : "r"(a) : "memory");
  return v;
}
DEVI uint32_t lds32(uint32_t a) {
  uint32_t v;
  asm volatile("ld.shared.u32 %0, [%1];" : "=r"(v) : "r"(a) : "memory");
  return v;
}
DEVI void lds64f_if(bool p, float& a, float& b, uint32_t addr) {
  asm volatile("{\n.reg .pred p;\nsetp.ne.u32 p, %3, 0;\n@p ld.shared.v2.f32 {%0,%1}, [%2];\n}\n"
               : "+f"(a), "+f"(b) : "r"(addr), "r"((uint32_t)p) : "memory");
}
DEVI float ldsf(uint32_t a) { return __uint_as_float(lds32(a)); }
DEVI void sts128(uint32_t a, uint32_t x, uint32_t y, uint32_t z, uint32_t w) {
  asm volatile("st.shared.v4.u32 [%0], {%1,%2,%3,%4};" ::"r"(a), "r"(x), "r"(y), "r"(z), "r"(w) : "memory");
}
DEVI void sts64(uint32_t a, uint32_t x, uint32_t y) { asm volatile("st.shared.v2.u32 [%0], {%1,%2};" ::"r"(a), "r"(x), "r"(y) : "memory"); }
DEVI void sts32(uint32_t a, uint32_t x) { asm volatile("st.shared.u32 [%0], %1;" ::"r"(a), "r"(x) : "memory"); }
DEVI void stsf(uint32_t a, float x) { sts32(a, __float_as_uint(x)); }
DEVI uint32_t packbf(float lo, float hi) {
  uint32_t r;
  asm("cvt.rn.bf16x2.f32 %0, %1, %2;" : "=r"(r) : "f"(hi), "f"(lo));
  return r;
}
DEVI uint32_t nz(uint32_t w) { uint32_t y; asm("max.u32 %0, %1, 1;" : "=r"(y) : "r"(w)); return y; }
DEVI float blo(uint32_t w) { return __uint_as_float(w << 16); }
DEVI float bhi(uint32_t w) { return __uint_as_float(w & 0xffff0000u); }
DEVI float rbf(float x) { return __uint_as_float(packbf(0.f, x)); }
DEVI float shx(float v, int m) { return __shfl_xor_sync(0xffffffffu, v, m); }
DEVI float quad_sum(float v) { v += shx(v, 1); v += shx(v, 2); return v; }
DEVI uint32_t movm(uint32_t a) {
  uint32_t d;
  asm volatile("movmatrix.sync.aligned.m8n8.trans.b16 %0, %1;" : "=r"(d) : "r"(a));
  return d;
}
DEVI void mma16(float* d, uint32_t a0, uint32_t a1, uint32_t a2, uint32_t a3, uint32_t b0, uint32_t b1) {
  asm("mma.sync.aligned.m16n8k16.row.col.f32.bf16.bf16.f32 {%0,%1,%2,%3},{%4,%5,%6,%7},{%8,%9},{%0,%1,%2,%3};"
      : "+f"(d[0]), "+f"(d[1]), "+f"(d[2]), "+f"(d[3])
      : "r"(a0), "r"(a1), "r"(a2), "r"(a3), "r"(b0), "r"(b1));
}
DEVI void mma8z(float* d, uint32_t a0, uint32_t a1, uint32_t b0) {
  asm("mma.sync.aligned.m16n8k8.row.col.f32.bf16.bf16.f32 {%0,%1,%2,%3},{%4,%5},{%6},{%7,%7,%7,%7};"
      : "=f"(d[0]), "=f"(d[1]), "=f"(d[2]), "=f"(d[3])
      : "r"(a0), "r"(a1), "r"(b0), "f"(0.f));
}
DEVI void mma8(float* d, uint32_t a0, uint32_t a1, uint32_t b0) {
  asm("mma.sync.aligned.m16n8k8.row.col.f32.bf16.bf16.f32 {%0,%1,%2,%3},{%4,%5},{%6},{%0,%1,%2,%3};"
      : "+f"(d[0]), "+f"(d[1]), "+f"(d[2]), "+f"(d[3])
      : "r"(a0), "r"(a1), "r"(b0));
}
DEVI void mma16z(float* d, uint32_t a0, uint32_t a1, uint32_t a2, uint32_t a3, uint32_t b0, uint32_t b1) {
  asm("mma.sync.aligned.m16n8k16.row.col.f32.bf16.bf16.f32 {%0,%1,%2,%3},{%4,%5,%6,%7},{%8,%9},{%10,%10,%10,%10};"
      : "=f"(d[0]), "=f"(d[1]), "=f"(d[2]), "=f"(d[3])
      : "r"(a0), "r"(a1), "r"(a2), "r"(a3), "r"(b0), "r"(b1), "f"(0.f));
}
DEVI void mma16a(float* d, const uint32_t* a, uint32_t b0, uint32_t b1) { mma16(d, a[0], a[1], a[2], a[3], b0, b1); }
DEVI float ln_sd(float var) { return rbf(sqrt_a(rbf(rbf(var) + kEps))); }
DEVI int fkey(float f) { int i = __float_as_int(f); return i ^ ((i >> 31) & 0x7fffffff); }
DEVI float sigmoidf(float x) { return rcp(1.f + ex2(-1.4426950408889634f * x)); }

DEVI uint32_t probe_stage(uint32_t pa) { return lds32(pa); }
DEVI void check_stage(uint32_t pv, uint32_t fa, const uint8_t* src) {
  if (__any_sync(0xffffffffu, pv == 0)) {
    uint32_t n = 0, tid;
    asm volatile("mov.u32 %0, %%tid.x;" : "=r"(tid));
    const uint32_t fo = (tid & 96) * 8 + (tid & 16) * 64 + (tid & 15) * 16;
    fa += fo; src += fo;
#pragma unroll 1
    for (uint32_t o = 0; o < 8192;) {
      const uint4 v = ld_msg(src + o);
      sts128(fa + o, v.x, v.y, v.z, v.w);
      if (!__any_sync(0xffffffffu, min(min(v.x, v.y), min(v.z, v.w)) == 0) || ++n > (1u << 16)) o += 2048;
    }
    fence_async_smem();
    __syncwarp();
  }
}

struct Params {
  const uint8_t *x, *wqkv, *wo, *wr, *wg, *wu, *wd;
  uint8_t* out;
  Scratch* g;
};

struct Maps { CUtensorMap wq, x, wo, xr, wg, wu, out; };
#define QPRE 2
#define FDEPTH 2
#define PFSTART 700
#define PFPRE 0
#define PFPER 3
#define PFNS 200
#define XSTART 100
#define XSTEP 300
#define PKSTEP 350
#define WPOLL 300
#define CSROUND 0
#define XLROUND 0
#define CLNS 20
#define FSTART 4000
#define XLSTART 3000
#define WGAP0 0
#define XGAP 150
#define OGAP 100
#define WDGAP 60
#define WR0 5
#define WR1 3
#define WR2 6
#define WEARLY 1

__global__ void __cluster_dims__(2, 1, 1) __launch_bounds__(512, 1) fused_kernel(const Params p, const __grid_constant__ Maps tm) {
  extern __shared__ __align__(1024) uint8_t smem_raw[];
  constexpr uint32_t sbd = 1024;
  int cta;
  uint32_t rank;
  {
    asm volatile("mov.u32 %0, %%cluster_ctarank;" : "=r"(rank));
    const int c = blockIdx.x >> 1, t = c - 4, u = c - 36, uq = (u * 37) >> 8;
    const int gpc = c < 4 ? 0 : c < 36 ? t & 7 : 1 + u - 7 * uq, idx = c < 4 ? 4 + c : c < 36 ? t >> 3 : 4 + uq;
    cta = __shfl_sync(0xffffffffu, (2 * gpc + (int)rank) * 8 + idx, 0);
  }
  const uint32_t sb = sbd | (rank << 24);
  if ((uint32_t)__cvta_generic_to_shared(smem_raw) != sb) return;
  if (threadIdx.x < 27) asm volatile("prefetch.global.L2 [%0];" ::"l"(p.wqkv + blockIdx.x * 3456 + threadIdx.x * 128));
  const int m = cta >> 3, r = cta & 7;
  const int warp = __shfl_sync(0xffffffffu, (int)(threadIdx.x >> 5), 0);
  const int lane = threadIdx.x & 31;
  uint8_t* const gb = reinterpret_cast<uint8_t*>(p.g);
  auto pack = [&]() -> uint32_t {
    const uint32_t t0 = clock();
    const uint32_t tp = sb + SM_WD + warp * 2304, bar = sb + SM_PART + 8 * warp;
    uint8_t* flag = GA(flagP, (12 * r + warp) * 128 + 4 * m);
    if (warp > 1) {
      asm volatile("bar.sync 4, 512;" ::: "memory");
      cluster_arrive();
      while ((uint32_t)clock() - t0 < (warp - 1) * PKSTEP) {}
    }
    if (elect()) {
      mbar_init(bar, 1);
      asm volatile("fence.mbarrier_init.release.cluster;" ::: "memory");
      mbar_expect(bar, 2304);
      if (warp < 9) tma3(tp, &tm.wq, 72 * r, 64 * warp + 8 * (m >> 1), m & 1, bar);
      else tma2(tp, &tm.wo, 72 * r, 192 * (warp - 9) + 24 * (m >> 1) + 8 * (m & 1), bar);
    }
    __syncwarp();
    if (lane == 0) st_rlx(flag, 0);
    if (warp <= 1) { asm volatile("bar.sync 4, 512;" ::: "memory"); cluster_arrive(); }
    mbar_wait(sb + B_EP, 0);
    const uint32_t epoch = lds32(sb + SM_EP);
    uint8_t* dst = GC(wpack, (r * 12 + warp) * WSTAGE + (27 * (m >> 1) + 14 * (m & 1)) * 128 + lane * 16);
    mbar_wait(bar, 0);
#pragma unroll
    for (int i = 0; i < 4; i++) {
      const int u = 4 * i + (lane >> 3) + 5 * (m & 1);
      const uint4 x = lds128(tp + (lane & 7) * 144 + u * 16 + (u >= 9 ? 1008 : 0));
      if (u < 14 + 4 * (m & 1)) stg128(dst + 512 * i, nz(x.x), nz(x.y), nz(x.z), nz(x.w));
    }
    if (lane == 0) st_rlx(flag, epoch);
    fence_async_smem();
    __syncwarp();
    if (elect()) asm volatile("mbarrier.inval.shared::cta.b64 [%0];" ::"r"(bar) : "memory");
    cluster_wait();
    return epoch;
  };

  if (warp >= 12) {
    asm volatile("setmaxnreg.dec.sync.aligned.u32 24;");
    uint32_t e0 = 0;
    if (elect()) {
#pragma unroll
      for (int i = 0; i < NBAR; i++)
        if (warp - 12 == (i * 4) / NBAR)
          mbar_init(sb + SM_BAR + 8 * i, i < 4 ? 1 : i < 8 ? 16 : i < 16 ? 2 : i < NBAR4 ? 4 : 1);
      asm volatile("fence.mbarrier_init.release.cluster;" ::: "memory");
    }
    __syncwarp();
    if (warp == 15) asm volatile("bar.arrive 4, 512;" ::: "memory");
    else asm volatile("bar.sync 4, 512;" ::: "memory");
    cluster_arrive();
    if (warp == 15) e0 = ld_rlx(GA(epoch, 32 * cta));
    if (warp == 12) {
      mbar_wait(sb + B_EP, 0);
      cluster_wait();
      const uint32_t epoch = lds32(sb + SM_EP);
      const uint32_t half = (m & 1) * (WSTAGE / 2);
      const uint8_t* src = GC(wpack, r * 12 * WSTAGE + half);
      __nanosleep(WPOLL);
#pragma unroll 1
      for (int g = 0; g < 24; g++) {
        const uint32_t slot = g & 3;
        if (g < 12) wait_flags(GA(flagP, (12 * r + g) * 128), lane & 15, epoch);
        if (g == 0) TRL(3, 0);
        if (g >= 4) mbar_wait(sb + B_WEMPTY + 8 * slot, ((g >> 2) - 1) & 1);
        if (elect()) {
          const uint32_t bar = sb + (g < 12 ? B_WL : B_WFULL) + 8 * slot;
          mbar_expect(bar, WSTAGE);
          bulk_g2s_pair(sb + SM_W + slot * WSTAGE + half, src + (g >= 12 ? g - 12 : g) * WSTAGE, WSTAGE / 2, bar);
        }
      }
    } else if (warp <= 14) {
      const int w = warp - 13;
      const uint32_t full = sb + B_XFULL + 32 * w, empty = sb + B_XEMPTY + 32 * w, ring = sb + SM_X + w * 4 * XSTAGE;
      mbar_wait(sb + B_EP, 0);
      cluster_wait();
      const uint32_t epoch = lds32(sb + SM_EP);
      if (lane < 4) st_rlx(GA(flagX, 128 * (2 * m + w) + 16 * r + 4 * lane), epoch * 4);
#pragma unroll 1
      for (int gemm = 0; gemm < 4; gemm++) {
        const uint8_t* src = GC(act, (gemm - 1) * ACT + (2 * m + w) * 73728);
        if (gemm & 1) {
          mbar_wait(empty, 0);
          if (elect()) {
            mbar_expect(sb + B_RES + 8 * w, 9216);
            if (gemm == 1) tma3(ring, &tm.xr, 72 * r, w, m * 64, sb + B_RES + 8 * w);
            else bulk_g2s(ring, GC(act, ACT + (2 * m + w) * 73728 + r * 9216), 9216, sb + B_RES + 8 * w);
          }
        }
        if (gemm > 0) {
          mbar_wait(gemm & 1 ? sb + B_RC + 8 * w : empty, gemm & 1 ? gemm >> 1 : 1);
          TRL(3, 11 + w * 4 + gemm);
          wait_flags(GA(flagX, 128 * (2 * m + w)), lane, epoch * 4 + gemm);
          TRL(3, 1 + w * 4 + gemm);
        }
        if (gemm & 1) {
          if (elect()) {
#pragma unroll
            for (int s = 0; s < 9; s++) {
              if (s > 0 && s < 5) { const uint32_t t1 = clock(); while ((uint32_t)clock() - t1 < OGAP) {} }
              if (s == 4) {
                mbar_wait(sb + B_RC + 8 * (w ^ 1), gemm >> 1);
                mbar_expect(sb + B_XE + 8 * w, XSTAGE);
                bulk_g2s(sb + SM_W + w * XSTAGE, src + 4 * XSTAGE, XSTAGE, sb + B_XE + 8 * w);
                continue;
              }
              const int sl = s < 4 ? s : s - 5;
              if (s >= 5) mbar_wait(empty + 8 * sl, s == 5);
              mbar_expect(full + 8 * sl, XSTAGE);
              bulk_g2s(ring + sl * XSTAGE, src + s * XSTAGE, XSTAGE, full + 8 * sl);
              mbar_arrive(full + 8 * sl);
            }
            mbar_wait(empty, 0);
            mbar_arrive(full);
            mbar_arrive(full);
          }
          __syncwarp();
          continue;
        }
        bool gate = gemm == 2;
#pragma unroll 1
        for (int s = 0; s < (gemm == 2 ? 11 : 9); s++) {
          const uint32_t slot = s & 3;
          if (gemm == 0 && s < 4) __nanosleep(s ? XSTEP : XSTART);
          if (gemm == 2 && s > 0 && s < 4) __nanosleep(XGAP);
          if (s >= 4) mbar_wait(empty + 8 * slot, s >> 3);
          const bool hold = gate && s >= 4 && mbar_test(sb + B_WANT, 0);
          if (lane == 0 && !hold && (gemm != 2 || (s & ~1) != 2)) mbar_arrive(full + 8 * (gemm == 2 && s >= 4 ? (s - 2) & 3 : slot));
          if (s < 9 && elect()) {
            mbar_expect(full + 8 * slot, XSTAGE);
            if (gemm == 0) tma3(ring + slot * XSTAGE, &tm.x, s * 64, w, m * 64, full + 8 * slot);
            else bulk_g2s(ring + slot * XSTAGE, src + s * XSTAGE, XSTAGE, full + 8 * slot);
          }
          if (hold) {
            mbar_wait(sb + B_DONE, 0);
            gate = false;
            if (lane == 0) mbar_arrive(full + 8 * ((s - 2) & 3));
          }
        }
      }
    } else {
      const uint32_t epoch = e0 + 1;
      if (lane == 0) {
        sts32(sb + SM_EP, epoch);
        mbar_arrive(sb + B_EP);
      }
      __syncwarp();
      cluster_wait();
      int pi = lane;
      auto prefetch = [&]() {
        const uint8_t* pp = pi < 648 ? ((cta & 1) ? p.wu : p.wg) + (uint32_t)(((pi / 72) * 63 + (cta >> 1)) * 9216 + pi * 128)
                                     : p.wd + (uint32_t)((cta * 324 + pi - 648) * 128);
        if (pi < 972 && !(ABL & 2)) asm volatile("prefetch.global.L2 [%0];" ::"l"(pp));
        pi += 32;
      };
      __nanosleep(PFSTART);
#pragma unroll 1
      for (int i = 0; i < PFPRE; i++) { prefetch(); __nanosleep(PFNS); }
      uint32_t ph = 0;
#pragma unroll 1
      for (int g = 0; g < 12; g++) {
        const uint32_t slot = g & 3;
#pragma unroll 1
        for (int n = 0; n < 4096; n++) {
          mbar_wait(sb + B_WL + 8 * slot, (ph >> slot) & 1);
          ph ^= 1 << slot;
          const uint32_t a = sb + SM_W + slot * WSTAGE + lane * 128 + (lane & 3) * 32 + (lane >> 2) * 4;
          uint32_t mn = lds32(a + (lane < 24 ? 6 * 4096 : 0));
#pragma unroll
          for (int u = 0; u < 6; u++) mn = min(mn, lds32(a + u * 4096));
          if (!__any_sync(0xffffffffu, mn == 0) || (ABL & 32)) break;
          fence_async_smem();
          __syncwarp();
          if (elect()) {
            mbar_expect(sb + B_WL + 8 * slot, WSTAGE);
            bulk_g2s(sb + SM_W + slot * WSTAGE, GC(wpack, (r * 12 + g) * WSTAGE), WSTAGE, sb + B_WL + 8 * slot);
          }
        }
        if (lane == 0) mbar_arrive(sb + B_WFULL + 8 * slot);
#pragma unroll 1
        for (int i = 0; i < PFPER; i++) prefetch();
      }
      TRL(3, 22);
      mbar_wait(sb + B_FD, 0);
      TRL(3, 20);
      if (elect()) {
        mbar_expect(sb + B_WD, (ABL & 64) ? 0 : 41472);
#pragma unroll 4
        for (int i = 0; i < 36; i++) {
          { const uint32_t t1 = clock(); while ((uint32_t)clock() - t1 < WDGAP) {} }
          if (!(ABL & 64)) bulk_g2s(sb + SM_WD + i * WDP, p.wd + (uint32_t)(cta * 36 + i) * 1152u, 1152, sb + B_WD);
        }
      }
      __syncwarp();
      TRL(3, 21);
      {
        const uint32_t epoch = e0, h = (lane >> 1) * 128 + (lane & 1) * 16;
        mbar_wait(sb + B_IDX, 0);
#pragma unroll 1
        for (int i = cta; i < 1296; i += 128) { stg128(GC(wpack, i * 2048 + (lane & 6) * 16 + h), 0, 0, 0, 0); __nanosleep(CLNS); }
#pragma unroll 1
        for (int i = 0; i < 5; i++) {
          stg128(GC(halo, (cta * 5 + i) * 2048 + h), 0, 0, 0, 0);
          if (i < 4 || lane < 16) stg128(GC(candrow, cta * 2304 + i * 512 + lane * 16), 0, 0, 0, 0);
          stg128(GC(act, (cta * 27 + i) * 2048 + 96 + h), 0, 0, 0, 0);
          __nanosleep(CLNS);
        }
        mbar_wait(sb + B_EPI, 1);
#pragma unroll 1
        for (int i = 5; i < 27; i++) { stg128(GC(act, (cta * 27 + i) * 2048 + 96 + h), 0, 0, 0, 0); __nanosleep(CLNS); }
      }
      TRL(3, 23);
    }
  } else if (warp >= 8) {
    asm volatile("setmaxnreg.inc.sync.aligned.u32 200;");
    const int sw = warp - 8, s = threadIdx.x - 256;
    const uint32_t t0 = clock();
    const uint32_t epoch = pack();
    TR(2, 0);
    auto ffn_round = [&](int u) {
      const uint32_t bar = sb + B_FF + 8 * (u % FDEPTH), dst = sb + SM_WD + (u % FDEPTH) * FSLOT;
      if (ABL & 4) { mbar_arrive(bar); return; }
      mbar_expect(bar, 12288);
      tma2(dst, &tm.wg, ((cta * 72) >> 5) << 4, 64 * u, bar);
      tma2(dst + FSLOT / 2, &tm.wu, ((cta * 72) >> 5) << 4, 64 * u, bar);
    };
    const int xi = 8 * r + 4 * (sw >> 1) + (lane >> 3);
    uint4 xv[9];
    uint32_t wr[9];
        {
          const uint8_t* xsrc = p.x + (uint32_t)((128 * m + 2 * xi + (sw & 1)) * 1152 + (lane & 7) * 16);
#pragma unroll
          for (int u = 0; u < 9; u++) xv[u] = ldg128(xsrc + u * 128);
#pragma unroll
          for (int u = 0; u < 9; u++) wr[u] = sw == 0 ? ldg32(p.wr + 128 * u + 4 * lane) : 0u;
        }
    {
      asm volatile("bar.sync 15, 384;" ::: "memory");
      const int u = (s >> 3) + 5 * (m & 1);
      uint4 v[9];
#pragma unroll
      for (int g = 0; g < 9; g++) v[g] = lds128(sb + SM_WD + g * 2304 + u * 16 + (u >= 9 ? 1008 : 0) + (s & 7) * 144);
      fence_async_smem();
      bar_sync(3);
      float a[8] = {};
#pragma unroll
      for (int g = 0; g < 9; g++) {
        a[0] += blo(v[g].x); a[1] += bhi(v[g].x); a[2] += blo(v[g].y); a[3] += bhi(v[g].y);
        a[4] += blo(v[g].z); a[5] += bhi(v[g].z); a[6] += blo(v[g].w); a[7] += bhi(v[g].w);
      }
      const bool b4 = s & 4, b2 = s & 2;
      float b[4];
#pragma unroll
      for (int e = 0; e < 4; e++) b[e] = (b4 ? a[4 + e] : a[e]) + shx(b4 ? a[e] : a[4 + e], 4);
      float c0 = (b2 ? b[2] : b[0]) + shx(b2 ? b[0] : b[2], 2), c1 = (b2 ? b[3] : b[1]) + shx(b2 ? b[1] : b[3], 2);
      c0 += shx(c0, 1); c1 += shx(c1, 1);
      if (!(s & 1) && (s >> 3) < 14 - (m & 1))
        st_rlx2(GA(colpart, (8 * r + (m >> 1)) * 864 + 14 * (m & 1) * 32 + 4 * s), __float_as_uint(c0), (__float_as_uint(c1) & ~15u) | (epoch & 15));
      TR(2, 1);
    }
    if (sw == 0) {
      while ((uint32_t)clock() - t0 < FSTART) {}
      if (elect()) {
#pragma unroll
        for (int u = 0; u < FDEPTH; u++) ffn_round(u);
      }
      __syncwarp();
    }
        {
          float sum = 0.f;
#pragma unroll
          for (int u = 0; u < 9; u++)
            sum += (blo(xv[u].x) + bhi(xv[u].x)) + (blo(xv[u].y) + bhi(xv[u].y)) + (blo(xv[u].z) + bhi(xv[u].z)) + (blo(xv[u].w) + bhi(xv[u].w));
          sum += shx(sum, 1); sum += shx(sum, 2); sum += shx(sum, 4);
          const float mu = sum * (1.f / kD);
          float q = 0.f;
#pragma unroll
          for (int u = 0; u < 9; u++) {
            const uint32_t ww[4] = {xv[u].x, xv[u].y, xv[u].z, xv[u].w};
#pragma unroll
            for (int e = 0; e < 4; e++) {
              const float d0 = blo(ww[e]) - mu, d1 = bhi(ww[e]) - mu;
              q = fmaf(d0, d0, q); q = fmaf(d1, d1, q);
            }
          }
          q += shx(q, 1); q += shx(q, 2); q += shx(q, 4);
          const float rho = rcp(ln_sd(q * (1.f / kD)));
          if ((lane & 7) == 0) st_msg(GA(stats0, 16 * (128 * m + 64 * (sw & 1) + xi)), __float_as_uint(rho), __float_as_uint(mu), 0, epoch);
          if (sw == 0) {
            float wsum = 0.f;
#pragma unroll
            for (int u = 0; u < 9; u++) wsum += blo(wr[u]) + bhi(wr[u]);
#pragma unroll
            for (int o = 1; o < 32; o <<= 1) wsum += shx(wsum, o);
            if (lane == 0) stsf(sb + SM_WSUM, wsum);
          }
          TR(2, 3);
        }
    uint32_t WF[9][4][4];
    {
      const int g = lane >> 2, t = lane & 3;
      const uint32_t c0 = (cta * 72) & 31, ra = 2 * (lane & 6) + (lane & 1) + 2 * ((lane >> 4) ^ ((lane >> 2) & 1));
      const uint32_t fa = sb + SM_WD + (16 * sw + ra) * 128 + ((((c0 + 8) >> 4) + ((lane >> 3) & 1)) << 4);
      const uint32_t fa0 = fa ^ ((ra & 7) << 4), fa1 = (fa + 32) ^ ((ra & 7) << 4);
      const uint32_t rl = 2 * (g & 6) + (g & 1) + 2 * (g >> 2);
      const uint32_t fl = sb + SM_WD + 16 * sw * 128 + (t >> 1) * (FSLOT / 2) + c0 + 64 * (~cta & 1) + 4 * (t & 1);
      const uint32_t fl0 = (fl + rl * 128) ^ ((rl & 7) << 4), fl1 = (fl + (rl ^ 2) * 128) ^ (((rl ^ 2) & 7) << 4);
#pragma unroll
      for (int i = 0; i < 9; i++) {
        mbar_wait(sb + B_FF + 8 * (i % FDEPTH), (i / FDEPTH) & 1);
#pragma unroll
        for (int e = 0; e < 4; e++) ldsm4t(WF[i][e], ((e & 1) ? fa1 : fa0) + (e >> 1) * (FSLOT / 2) + (i % FDEPTH) * FSLOT);
        const uint32_t v0 = lds32(fl0 + (i % FDEPTH) * FSLOT), v1 = lds32(fl1 + (i % FDEPTH) * FSLOT);
        if (i + FDEPTH < 9 || i == 8) {
          fence_async_smem();
          bar_sync(3);
          if (sw == 0 && elect()) {
            if (i < 8) ffn_round(i + FDEPTH);
            else mbar_arrive(sb + B_FD);
          }
        }
        sts64(sb + SM_LEFT + i * 1024 + s * 8, movm(v0), movm(v1));
        if (i == CSROUND) {
          TR(2, 21);
          float c0, c1;
          uint4 s0;
          uint32_t nc = 0;
          _Pragma("unroll 1") while (true) {
            s0 = ld_msg(GA(stats0, 16 * (128 * m + s)));
            uint32_t bad = s0.w != epoch;
            c0 = 0.f; c1 = 0.f;
#pragma unroll
            for (int mm = 0; mm < 8; mm++) {
              const uint2 v = ld_rlx2(GA(colpart, 8 * 864 * r + 8 * min(s, 107)) + mm * 864);
              c0 += __uint_as_float(v.x); c1 += __uint_as_float(v.y & ~15u);
              bad |= v.y ^ epoch;
            }
            if (!__any_sync(0xffffffffu, bad & 15)) break;
            spin_guard(nc);
          }
          if (s < 108) {
            const uint32_t hi = packbf(c0, c1);
            sts32(sb + SM_COLSUM + 32 * (s >> 2) + 4 * (s & 3), hi);
            sts32(sb + SM_COLSUM + 32 * (s >> 2) + 4 * (s & 3) + 16, packbf(c0 - blo(hi), c1 - bhi(hi)));
          }
          sts32(sb + SM_ROWC + 4 * s, s0.x);
          sts64(sb + SM_ROWM + 8 * s, s0.y, __float_as_uint(1.f));
          fence_async_smem();
          __syncwarp();
          if (lane == 0) mbar_arrive(sb + B_COLSUM);
          TR(2, 13);
        }
      }
      TR(2, 4);
    }
    {
      mbar_wait(sb + B_OS, 0);
      const uint32_t y = epoch * 2 - 1;
      st_msg(GA(ypart, (s >> 1) * 4096 + cta * 32 + (s & 1) * 16), y, y, y, y);
      if (s < 16) {
        st_msg(GA(ypart, (64 + (s >> 1)) * 4096 + cta * 32 + (s & 1) * 16), y, y, y, y);
        st_rlx(GA(fixmsg, 1024 * r + 64 * m + 4 * s), epoch - 1);
      }
      if (s < 64 && cta < 72) st_rlx(GA(x2msg, (s >> 3) * 2304 + 32 * cta + 4 * (s & 7)), epoch - 1);
    }
#pragma unroll 1
    for (int L = 0; L < 2; L++) {
      const uint32_t tag = epoch * 2 + L;
      int s0 = __shfl_sync(0xffffffffu, (int)threadIdx.x + L, threadIdx.x & 31) - L - 256;
#define RELANE asm volatile("" : "+r"(s0)); const int s = s0, lane = s & 31, g = lane >> 2, t = lane & 3; (void)g; (void)t
      RELANE;
      const uint8_t* crow = GC(candrow, L * 128 * 1152);
      const uint8_t* cptr = GA(cand, (8 * L + r) * 2048 + 16 * s);
      asm volatile("" : "+l"(crow), "+l"(cptr));
      mbar_wait2(sb + B_WD, 0, sb + B_EPI, L);
      uint32_t win;
      {
        uint32_t c, n = 0;
        _Pragma("unroll 1") while (true) {
          c = ld_rlx(cptr) ^ (epoch & 0x7f);
          if (!__any_sync(0xffffffffu, c & 0x7f)) break;
          spin_guard(n);
        }
        const int wm = __reduce_max_sync(0xffffffffu, (int)(c | s));
        if (lane == 0) sts32(sb + SM_RED + 4 * sw, wm);
        bar_sync(3);
        const uint4 v = lds128(sb + SM_RED);
        win = max(max((int)v.x, (int)v.y), max((int)v.z, (int)v.w));
      }
      crow += (win & 127) * 1152;
      if (s == 0) {
        if (L == 0 && WEARLY) mbar_arrive(sb + B_WANT);
        sts32(sb + SM_SEL + 4 * L, win & 0x7ff);
        mbar_arrive(sb + B_IDX + 8 * L);
      }
      TR(2, 5 + 10 * L);
      uint2 xw[9];
      {
        if (sw < 3) {
          uint4 v;
          uint32_t n = 0;
          _Pragma("unroll 1") while (true) {
            v = ld_msg(crow + 16 * min(s, 71));
            if (!__any_sync(0xffffffffu, min(min(v.x, v.y), min(v.z, v.w)) == 0)) break;
            spin_guard(n);
          }
          if (s < 72) sts128(sb + SM_PART + 16 * s, v.x, v.y, v.z, v.w);
        }
        bar_sync(3);
#pragma unroll
        for (int i = 0; i < 9; i++) xw[i] = lds64(sb + SM_PART + 128 * i + 32 * sw + 8 * t);
      }
      if (L == 0 && !WEARLY && s == 0) mbar_arrive(sb + B_WANT);
      TR(2, 6 + 10 * L);
      {
        float a[4][4] = {}, al[4] = {};
#pragma unroll
        for (int i = 0; i < 9; i++) {
          const uint2 wl = lds64(sb + SM_LEFT + s * 8 + i * 1024);
#pragma unroll
          for (int e = 0; e < 4; e++) mma16a(a[e], WF[i][e], xw[i].x, xw[i].y);
          mma8(al, wl.x, wl.y, (g & 1) ? xw[i].y : xw[i].x);
        }
        bar_sync(3);
        const uint32_t pp = sb + SM_PART + ((t >> 1) * 36 + 16 * (t & 1) + g + 4 * (cta & 1)) * 16 + 4 * sw;
        stsf(pp, selp(t & 2, selp(t & 1, a[3][0], a[2][0]), selp(t & 1, a[1][0], a[0][0])));
        stsf(pp + 128, selp(t & 2, selp(t & 1, a[3][2], a[2][2]), selp(t & 1, a[1][2], a[0][2])));
        stsf(sb + SM_PART + ((g >> 2) * 36 + 32 * (~cta & 1) + (g & 3)) * 16 + 4 * sw, al[0] + al[3]);
      }
      {
        RELANE;
        const uint32_t wa = sb + SM_WD + 288 * sw + ((lane >> 3) & 1) * 16 + ((lane & 7) + 8 * (lane >> 4)) * WDP;
        const uint32_t wb = sb + SM_WD + 288 * sw + ((lane >> 3) & 1) * 16 + (32 + (lane & 3)) * WDP;
        uint32_t f[4][4];
#pragma unroll
        for (int u = 0; u < 4; u++) ldsm4t(f[u], wa + 32 * (u & 1) + (u >> 1) * 16 * WDP);
        bar_sync(3);
        {
          float hv[2];
#pragma unroll
          for (int e = 0; e < 2; e++) {
            const uint32_t pp = sb + SM_PART + 16 * (e ? 32 + t : lane);
            const uint4 pg = lds128(pp), pu = lds128(pp + 576);
            const float gp = rbf((__uint_as_float(pg.x) + __uint_as_float(pg.y)) + (__uint_as_float(pg.z) + __uint_as_float(pg.w)));
            const float u = rbf((__uint_as_float(pu.x) + __uint_as_float(pu.y)) + (__uint_as_float(pu.z) + __uint_as_float(pu.w)));
            hv[e] = rbf(gp * sigmoidf(gp)) * u;
          }
          const uint32_t hh = packbf(hv[0], hv[1]);
          sts16(sb + SM_H + 80 * sw + 2 * lane, hh);
          sts16(sb + SM_H + 80 * sw + 64 + 2 * t, hh >> 16);
          __syncwarp();
        }
        TR(2, 7 + 10 * L);
        uint32_t hp[5];
#pragma unroll
        for (int i = 0; i < 4; i++) hp[i] = lds32(sb + SM_H + 80 * sw + 16 * i + 4 * t);
        hp[4] = lds32(sb + SM_H + 80 * sw + 64 + 4 * (t & 1));
        float Y[4] = {}, Z[4] = {}, C[4] = {};
        {
          uint32_t e0[4], e1[4], e2[4];
          const uint32_t wq = wb + 32 * (((lane >> 2) & 1) + 2 * (lane >> 4));
          ldsm4t(e0, wq); ldsm4t(e1, wq + 128); ldsm4t(e2, wb + 256);
          mma16a(Y, e0, g == (t >> 1) ? hp[4] : 0u, g == 2 + (t >> 1) ? hp[4] : 0u);
          mma16a(Z, e1, g == 4 + (t >> 1) ? hp[4] : 0u, g == 6 + (t >> 1) ? hp[4] : 0u);
          mma8(C, e2[0], e2[1], t < 2 ? hp[4] : 0u);
        }
#pragma unroll
        for (int u = 0; u < 4; u++) {
          const uint32_t wn = wa + 64 * (u + 1);
          const bool p0 = g == 2 * u, p1 = g == 2 * u + 1;
          mma16a(Y, f[0], p0 ? hp[0] : 0u, p0 ? hp[1] : 0u);
          mma16a(Z, f[1], p1 ? hp[0] : 0u, p1 ? hp[1] : 0u);
          ldsm4t(f[0], wn);
          if (u < 3) ldsm4t(f[1], wn + 32);
          mma16a(Y, f[2], p0 ? hp[2] : 0u, p0 ? hp[3] : 0u);
          mma16a(Z, f[3], p1 ? hp[2] : 0u, p1 ? hp[3] : 0u);
          ldsm4t(f[2], wn + 16 * WDP);
          if (u < 3) ldsm4t(f[3], wn + 32 + 16 * WDP);
        }
        mma16a(C, f[0], hp[0], hp[1]);
        mma16a(C, f[2], hp[2], hp[3]);
#pragma unroll
        for (int e = 0; e < 4; e++) Y[e] += Z[e];
        const uint32_t t4 = tag & 15;
        {
          uint8_t* yo = GA(ypart, (18 * sw + 4 * t) * 4096 + cta * 32 + 4 * g);
#pragma unroll
          for (int e = 0; e < 4; e++) st_rlx(yo + (2 * (e & 1) + (e >> 1)) * 4096, (__float_as_uint(Y[e]) & ~15u) | t4);
          if (t < 2) st_rlx(yo + (16 - 3 * t) * 4096, (__float_as_uint(t ? C[2] : C[0]) & ~15u) | t4);
          if (L == 0 && lane == 0) mbar_arrive(sb + B_DONE);
        }
      }
      TR(2, 8 + 10 * L);
      if (cta < 72) {
        RELANE;
        const uint32_t xn = ld_rlx(GC(candrow, (L * 128 + (win & 127)) * 1152 + 16 * cta + 2 * ((s & 6) ^ (2 * (cta & 1)))));
        const uint4 cm = ld_msg(GA(cand, (8 * L + r) * 2048 + 16 * (win & 127)));
        const uint8_t* yp = GA(ypart, cta * 4096 + s * 16);
        uint4 u0, u1;
        uint32_t n = 0;
        _Pragma("unroll 1") while (true) {
          u0 = ld_msg(yp);
          u1 = ld_msg(yp + 2048);
          const uint32_t t4 = tag & 15;
          u0.x ^= t4; u0.y ^= t4; u0.z ^= t4; u0.w ^= t4; u1.x ^= t4; u1.y ^= t4; u1.z ^= t4; u1.w ^= t4;
          if (!__any_sync(0xffffffffu, (u0.x | u0.y | u0.z | u0.w | u1.x | u1.y | u1.z | u1.w) & 15)) break;
          spin_guard(n);
        }
        const float a0 = __uint_as_float(u0.x) + __uint_as_float(u1.x), a1 = __uint_as_float(u0.y) + __uint_as_float(u1.y);
        const float a2 = __uint_as_float(u0.z) + __uint_as_float(u1.z), a3 = __uint_as_float(u0.w) + __uint_as_float(u1.w);
        const bool b4 = lane & 4, b2 = lane & 2;
        const float c0 = (b4 ? a2 : a0) + shx(b4 ? a0 : a2, 4), c1 = (b4 ? a3 : a1) + shx(b4 ? a1 : a3, 4);
        float d = (b2 ? c1 : c0) + shx(b2 ? c0 : c1, 2);
        d += shx(d, 8);
        if (!(lane & 8)) stsf(sb + SM_RED + 32 * (4 * (lane & 1) + ((lane >> 1) & 3)) + 8 * sw + 4 * (lane >> 4), d);
        bar_sync(3);
        if (s < 64) {
          const uint4 p0 = lds128(sb + SM_RED + 32 * (s & 7)), p1 = lds128(sb + SM_RED + 32 * (s & 7) + 16);
          const float y = rbf(((__uint_as_float(p0.x) + __uint_as_float(p0.y)) + (__uint_as_float(p0.z) + __uint_as_float(p0.w))) +
                              ((__uint_as_float(p1.x) + __uint_as_float(p1.y)) + (__uint_as_float(p1.z) + __uint_as_float(p1.w))));
          const uint32_t v = packbf(0.f, fmaf((s & 1) ? bhi(xn) : blo(xn), __uint_as_float(cm.z), __uint_as_float(cm.w)) + rbf(y * __uint_as_float(cm.y)));
          if (L == 0) st_rlx(GA(x2msg, (s >> 3) * 2304 + 32 * cta + 4 * (s & 7)), v | (epoch & 0xffff));
          const int tok = 128 * ((win >> 3) & 15) + 2 * (16 * (win & 3) + ((win >> 7) & 15)) + ((win >> 2) & 1);
          if (L == 1 && s < 8) *reinterpret_cast<uint16_t*>(p.out + (uint32_t)(tok * 1152 + 16 * cta + 2 * s)) = (uint16_t)(v >> 16);
        }
      }
      TR(2, 9 + 10 * L);
      if (L == 0 && m < 14) {
        RELANE;
        const int c = min(2 * m + ((s >> 3) & 1), 26);
        const uint8_t* wsrc = GC(wpack, r * 12 * WSTAGE + (s >> 4) * 3456 + c * 128 + (s & 7) * 16);
        const int k0 = 8 * (s >> 4) + (s & 7);
        uint4 wv[5];
#pragma unroll
        for (int i = 0; i < 5; i++) wv[i] = ldcg128(wsrc + i * WSTAGE);
        uint32_t xv[9];
        {
          uint32_t n = 0;
          _Pragma("unroll 1") while (true) {
            uint32_t bad = 0;
#pragma unroll
            for (int i = 0; i < 9; i++) { xv[i] = ld_rlx(GA(x2msg, r * 2304 + 4 * k0) + 256 * i); bad |= xv[i] ^ epoch; }
            if (!__any_sync(0xffffffffu, bad & 0xffff)) break;
            spin_guard(n);
          }
        }
        TR(2, 10);
        float a[8], z = 0.f;
#pragma unroll
        for (int e = 0; e < 8; e++) a[e] = 0.f;
#pragma unroll
        for (int i = 0; i < 9; i++) {
          const float xx = bhi(xv[i]);
          const uint4 w4 = wv[i % 5];
          if (i < 4) wv[i] = ldcg128(wsrc + (i + 5) * WSTAGE);
          z = fmaf(xx, (lane & 8) ? xx : 1.f, z);
          a[0] = fmaf(xx, blo(w4.x), a[0]); a[1] = fmaf(xx, bhi(w4.x), a[1]);
          a[2] = fmaf(xx, blo(w4.y), a[2]); a[3] = fmaf(xx, bhi(w4.y), a[3]);
          a[4] = fmaf(xx, blo(w4.z), a[4]); a[5] = fmaf(xx, bhi(w4.z), a[5]);
          a[6] = fmaf(xx, blo(w4.w), a[6]); a[7] = fmaf(xx, bhi(w4.w), a[7]);
        }
        const bool b4 = lane & 4, b2 = lane & 2, b1 = lane & 1;
        float b[4];
#pragma unroll
        for (int e = 0; e < 4; e++) b[e] = (b4 ? a[4 + e] : a[e]) + shx(b4 ? a[e] : a[4 + e], 4);
        z += shx(z, 4);
        const float c0 = (b2 ? b[2] : b[0]) + shx(b2 ? b[0] : b[2], 2);
        const float c1 = (b2 ? b[3] : b[1]) + shx(b2 ? b[1] : b[3], 2);
        z += shx(z, 2);
        float d = (b1 ? c1 : c0) + shx(b1 ? c0 : c1, 1);
        z += shx(z, 1);
        d += shx(d, 16);
        z += shx(z, 16);
        if (lane < 16) stsf(sb + SM_GEMV + 16 * lane + 4 * sw, d);
        if ((lane & 23) == 0) stsf(sb + SM_GEMV + 256 + 2 * lane + 4 * sw, z);
        bar_sync(3);
        if (s < 16) {
          const uint4 pd = lds128(sb + SM_GEMV + 16 * s), p1 = lds128(sb + SM_GEMV + 256), p2 = lds128(sb + SM_GEMV + 272);
          const float acc = (__uint_as_float(pd.x) + __uint_as_float(pd.y)) + (__uint_as_float(pd.z) + __uint_as_float(pd.w));
          const float m1 = ((__uint_as_float(p1.x) + __uint_as_float(p1.y)) + (__uint_as_float(p1.z) + __uint_as_float(p1.w))) * (1.f / kD);
          const float m2 = ((__uint_as_float(p2.x) + __uint_as_float(p2.y)) + (__uint_as_float(p2.z) + __uint_as_float(p2.w))) * (1.f / kD);
          const float cs = blo(lds16(sb + SM_COLSUM + 32 * c + 2 * (s & 7))) + blo(lds16(sb + SM_COLSUM + 32 * c + 2 * (s & 7) + 16));
          const float v = (acc - m1 * cs) * rcp(ln_sd(fmaxf(m2 - m1 * m1, 0.f)));
          st_rlx(GA(fixmsg, 1024 * r + 64 * m + 4 * s), __float_as_uint(rbf(v)) | (epoch & 0xffff));
        }
        TR(2, 11);
      }
      {
        if (L == 0 && (int)((win >> 3) & 15) == m) {
          RELANE;
          if (s < 72) {
            const uint8_t* fp = s < 54 ? GA(fixmsg, 1024 * r + 16 * s) : GA(x2msg, r * (2304 + 288) + 16 * (s - 54));
            uint4 v;
            uint32_t n = 0;
            _Pragma("unroll 1") while (true) {
              v = ld_msg(fp);
              if ((((v.x ^ epoch) | (v.y ^ epoch) | (v.z ^ epoch) | (v.w ^ epoch)) & 0xffff) == 0) break;
              spin_guard(n);
            }
            sts128(sb + SM_FIXQ + 16 * s, v.x & 0xffff0000u, v.y & 0xffff0000u, v.z & 0xffff0000u, v.w & 0xffff0000u);
          }
          __syncwarp();
          if (lane == 0) mbar_arrive(sb + B_FIX);
          TR(2, 12);
        }
      }
    }
    if (s == 0) st_rlx(GA(epoch, 32 * cta), epoch);
  } else {
    asm volatile("setmaxnreg.inc.sync.aligned.u32 144;");
    const int w = warp >> 2, j = warp & 3;
    const uint32_t xfull = sb + B_XFULL + 32 * w, xempty = sb + B_XEMPTY + 32 * w, xring = sb + SM_X + w * 4 * XSTAGE;
    if (threadIdx.x >= 128 && threadIdx.x < 188) { sts128(sb + SM_COLSUM + 16 * (threadIdx.x - 128), 0, 0, 0, 0); fence_async_smem(); }
    {
      const uint32_t epoch = pack();
      asm volatile("bar.arrive 15, 384;" ::: "memory");
      TRW(24);
      if (!(ABL & 8)) {
        if (lane < 16) st_msg(GA(statsP, (2 * m + w) * 8192 + r * 1024 + (16 * j + lane) * 16), 0, 0, 0, 0);
        if (lane < 2) st_msg(GA(cand, (8 * lane + r) * 2048 + 16 * (8 * m + warp)), ~epoch, 0, 0, 0);
        __syncwarp();
      }
      TRW(11);
    }
    const uint32_t mw = 2 * m + w, cid = 8 * m + warp;
    const uint32_t rowc = sb + SM_ROWC + 64 * warp, rowm = sb + SM_ROWM + 128 * warp;
#pragma unroll 1
    for (int L = 0; L < 2; L++) {
      int ln0 = __shfl_sync(0xffffffffu, lane + L, lane) - L;
#define RELANE2 asm volatile("" : "+r"(ln0)); const int ln = ln0, g = ln >> 2, t = ln & 3; \
      const uint32_t pa = xring + j * 256 + (ln & 7) * 1028 + ((ln >> 3) & 1) * 128 + 96; (void)pa
      uint32_t P[27][2], H[20];
      const uint8_t* hl;
      auto halo = [&]() {
#pragma unroll
        for (int u = 0; u < 5; u++) {
          const uint4 v = ld_gen(hl + u * 512);
          H[4 * u] = v.x; H[4 * u + 1] = v.y; H[4 * u + 2] = v.z; H[4 * u + 3] = v.w;
        }
      };
      {
        RELANE2;
        const uint32_t epoch = __shfl_sync(0xffffffffu, lds32(sb + SM_EP), 0);
        int selrow = -1;
        bool tgtwg = false;
        float d[108];
        uint32_t am[4];
        auto split_mean = [&](float m0, float m1) {
          const uint32_t h0 = packbf(m0, m0), h1 = packbf(m1, m1);
          const float l0 = m0 - bhi(h0), l1 = m1 - bhi(h1);
          am[0] = t ? 0u : h0; am[1] = t ? 0u : h1; am[2] = t ? 0u : packbf(l0, l0); am[3] = t ? 0u : packbf(l1, l1);
        };
        const uint32_t cdesc = mkdesc(sbd + SM_COLSUM, 0);
        am[0] = am[1] = am[2] = am[3] = 0;
        if (L == 1) split_mean(ldsf(rowm + 8 * g), ldsf(rowm + 8 * g + 64));
        asm volatile("wgmma.fence.sync.aligned;" ::: "memory");
        wgmma_n144_set(d + 36, am, cdesc + 18);
        wgmma_n72_set(d, am, cdesc);
        asm volatile("wgmma.commit_group.sync.aligned;" ::: "memory");
        const uint32_t adesc = mkdesc(sbd + SM_X + w * 4 * XSTAGE, 1024), ahi = L == 0 ? 0x40000040u : 8u, astep = L == 0 ? 2 : 128;
        const uint32_t bdesc = mkdesc(sbd + SM_W, 3456);
        const uint8_t* xsrc = GC(act, ACT + mw * 73728);
        mbar_wait2(sb + B_WFULL, L, xfull, 0);
        if (L == 1) check_stage(probe_stage(pa), xring, xsrc);
        TRW(0 + 12 * L);
#pragma unroll 1
        for (int s = 0; s < 7; s++) {
          TRQ(s + 9 * L);
          const uint32_t da = adesc + (s & 3) * (XSTAGE >> 4), db = bdesc + (s & 3) * (WSTAGE >> 4);
          const uint32_t nx = (s + 1) & 3, px = ((s + 1) >> 2) & 1;
          asm volatile("wgmma.fence.sync.aligned;" ::: "memory");
          wgmma_n72(d, da, ahi, db);
          wgmma_n144(d + 36, da, ahi, db + (1152 >> 4));
          wgmma_n72(d, da + astep, ahi, db + (6912 >> 4));
          asm volatile("wgmma.commit_group.sync.aligned;" ::: "memory");
          asm volatile("wgmma.wait_group.sync.aligned 1;" ::: "memory");
          if (s > 0 && ln == 0) {
            mbar_arrive_pair(sb + B_WEMPTY + 8 * ((s - 1) & 3));
            mbar_arrive(xempty + 8 * ((s - 1) & 3));
          }
          wgmma_n144(d + 36, da + astep, ahi, db + ((6912 + 1152) >> 4));
          wgmma_n72(d, da + 2 * astep, ahi, db + 2 * (6912 >> 4));
          uint32_t pv;
          const uint32_t dsc[6] = {da + 2 * astep, db + ((2 * 6912 + 1152) >> 4), da + 3 * astep, db + 3 * (6912 >> 4),
                                   da + 3 * astep, db + ((3 * 6912 + 1152) >> 4)};
          const uint32_t bar[4] = {sb + B_WFULL + 8 * nx, px ^ L, xfull + 8 * nx, px}, adr = pa + nx * XSTAGE;
          q_tail(d, &pv, ahi, dsc, bar, &adr);
          if (L == 1) check_stage(pv, xring + nx * XSTAGE, xsrc + (s + 1) * XSTAGE);
          if (s == 1 && j == 3) {
            uint8_t* hp = GC(halo, (4 * cta + 2 * L + w) * 2560 + ln * 16);
#pragma unroll
            for (int u = 0; u < 5; u++) st_msg(hp + u * 512, 0, 0, 0, 0);
          }
        }
        TRQ(7 + 9 * L);
        const uint32_t da7 = adesc + 3 * (XSTAGE >> 4), db7 = bdesc + 3 * (WSTAGE >> 4);
        asm volatile("wgmma.fence.sync.aligned;" ::: "memory");
        wgmma_n144(d + 36, da7, ahi, db7 + (1152 >> 4));
        wgmma_n144(d + 36, da7 + astep, ahi, db7 + ((6912 + 1152) >> 4));
        asm volatile("wgmma.commit_group.sync.aligned;" ::: "memory");
        asm volatile("wgmma.wait_group.sync.aligned 1;" ::: "memory");
        if (ln == 0) { mbar_arrive_pair(sb + B_WEMPTY + 16); mbar_arrive(xempty + 16); }
        {
          uint32_t v[2];
          const uint32_t dsc[4] = {da7 + 2 * astep, db7 + ((2 * 6912 + 1152) >> 4), da7 + 3 * astep, db7 + ((3 * 6912 + 1152) >> 4)};
          const uint32_t bar[6] = {sb + B_WFULL, (uint32_t)L, xfull, 0, sb + (L ? B_IDX : B_COLSUM), 0}, adr[2] = {pa, sb + SM_SEL + (ln >> 5)};
          kv_tail(d, v, ahi, dsc, bar, adr);
          if (L == 1) {
            if ((v[1] & 127) == cid) selrow = v[1] >> 7;
            tgtwg = ((v[1] & 127) >> 2) == (cid >> 2);
            check_stage(v[0], xring, xsrc + 8 * XSTAGE);
          }
        }
        TRQ(8 + 9 * L);
        const float m0 = ldsf(rowm + 8 * g), m1 = ldsf(rowm + 8 * g + 64);
        {
          uint32_t dsc[8];
#pragma unroll
          for (int kk = 0; kk < 4; kk++) { dsc[2 * kk] = adesc + kk * astep; dsc[2 * kk + 1] = bdesc + ((kk * 6912 + 1152) >> 4); }
          const uint32_t bar[2] = {xempty + 16, 1};
          asm volatile("wgmma.fence.sync.aligned;" ::: "memory");
          kv_last(d, nullptr, ahi, dsc, bar, nullptr);
        }
        if (L == 0) {
          split_mean(m0, m1);
          asm volatile("wgmma.fence.sync.aligned;" ::: "memory");
          wgmma_n144_add(d + 36, am, cdesc + 18);
          wgmma_n72_add(d, am, cdesc);
          asm volatile("wgmma.commit_group.sync.aligned;" ::: "memory");
        }
        auto qstep = [&](int k) {
          wgmma_n72(d, (k < 4 ? da7 : adesc) + (k & 3) * astep, ahi, (k < 4 ? db7 : bdesc) + (k & 3) * (6912 >> 4));
        };
#pragma unroll
        for (int k = 0; k < QPRE; k++) qstep(k);
        asm volatile("wgmma.commit_group.sync.aligned;" ::: "memory");
        if (tgtwg) {
          asm volatile("wgmma.fence.sync.aligned;" ::: "memory");
#pragma unroll
          for (int k = QPRE; k < 8; k++) qstep(k);
          asm volatile("wgmma.commit_group.sync.aligned;" ::: "memory");
        }
        asm volatile("wgmma.wait_group.sync.aligned 1;" ::: "memory");
#pragma unroll
        for (int i = 36; i < 108; i++) asm volatile("" : "+f"(d[i])::"memory");
        if (selrow >= 0) {
          mbar_wait(sb + B_FIX, 0);
          stsf(rowc + 4 * selrow, 1.f);
#pragma unroll
          for (int q = 18; q < 54; q++) lds64f_if(selrow == g + 8 * (q & 1), d[2 * q], d[2 * q + 1], sb + SM_FIXQ + 32 * (q >> 1) + 8 * t);
          __syncwarp();
        }
#pragma unroll
        for (int q = 26; q >= 9; q--) { P[q][1] = packbf(d[4 * q + 2], d[4 * q + 3]); P[q][0] = packbf(d[4 * q], d[4 * q + 1]); }
#pragma unroll
        for (int q = 26; q >= 18; q--) P[q][1] = movm(P[q][1]);
        const uint2 ck1 = lds64(rowc + 32 + 8 * t);
        uint8_t* ha = (j < 3 ? smem_raw + (SM_X + (4 * w + 2) * XSTAGE + j * 2560) : GC(halo, (4 * cta + 2 * L + w) * 2560)) + ln * 16;
        P[9][1] = nz(P[9][1]); P[13][1] = nz(P[13][1]); P[17][1] = nz(P[17][1]);
        st_gen(ha, P[9][1], P[10][1], P[11][1], P[12][1]);
        st_gen(ha + 512, P[13][1], P[14][1], P[15][1], P[16][1]);
        st_gen(ha + 2048, nz(ck1.y), P[24][1], P[25][1], P[26][1]);
        st_gen(ha + 1536, nz(ck1.x), P[21][1], P[22][1], P[23][1]);
        st_gen(ha + 1024, P[17][1], P[18][1], P[19][1], P[20][1]);
#pragma unroll
        for (int q = 9; q < 27; q++) asm volatile("" : "+r"(P[q][0]));
        if (j < 3) asm volatile("bar.arrive %0, 64;" ::"r"(5 + warp) : "memory");
        mbar_wait(sb + B_EP, 0);
#pragma unroll
        for (int q = 26; q >= 18; q--) P[q][0] = movm(P[q][0]);
        if (!tgtwg)
        {
          asm volatile("wgmma.fence.sync.aligned;" ::: "memory");
#pragma unroll
          for (int k = QPRE; k < 8; k++) qstep(k);
          asm volatile("wgmma.commit_group.sync.aligned;" ::: "memory");
        }
        hl = (j > 0 || m == 0 ? smem_raw + (SM_X + (4 * w + 2) * XSTAGE + max(j - 1, 0) * 2560)
                              : GC(halo, (4 * (cta - 8) + 2 * L + w) * 2560)) + ln * 16;
        if (j > 0) asm volatile("bar.sync %0, 64;" ::"r"(4 + warp) : "memory");
        asm volatile("wgmma.wait_group.sync.aligned 0;" ::: "memory");
#pragma unroll
        for (int i = 0; i < 36; i++) asm volatile("" : "+f"(d[i])::"memory");
        TRW(1 + 12 * L);
        if (selrow >= 0) {
#pragma unroll
          for (int q = 0; q < 18; q++) lds64f_if(selrow == g + 8 * (q & 1), d[2 * q], d[2 * q + 1], sb + SM_FIXQ + 32 * (q >> 1) + 8 * t);
        }
#pragma unroll
        for (int q = 0; q < 9; q++) { P[q][0] = packbf(d[4 * q], d[4 * q + 1]); P[q][1] = packbf(d[4 * q + 2], d[4 * q + 3]); }
      }
      TRW(2 + 12 * L);
      const uint32_t epoch = lds32(sb + SM_EP);
      uint8_t* fptr = GA(flagX, 128 * mw + 16 * r + 4 * j + ln0);
      {
        RELANE2;
        halo();
        if (ln == 0) { mbar_arrive(xempty + 24); mbar_arrive(xempty); }
        const bool le0 = 2 * t <= g, le1 = 2 * t + 1 <= g;
        uint32_t A0[4][2], A2[4][2];
        float s0[4][4], s1[4][4];
#pragma unroll
        for (int h = 0; h < 4; h++) {
          const int T = 2 * h;
          A0[h][0] = t >= h ? P[T][0] : 0u; A0[h][1] = t >= h ? P[T][1] : 0u;
          A2[h][0] = t <= h ? P[T + 2][0] : 0u; A2[h][1] = t <= h ? P[T + 2][1] : 0u;
          mma8z(s0[h], A2[h][0], A2[h][1], P[9 + T + 2][0]);
          mma8z(s1[h], A2[h][0], A2[h][1], P[9 + T + 2][1]);
        }
#pragma unroll
        for (int h = 0; h < 4; h++) {
          const int T = 2 * h;
          mma16(s0[h], A0[h][0], A0[h][1], P[T + 1][0], P[T + 1][1], P[9 + T][0], P[9 + T + 1][0]);
          mma16(s1[h], A0[h][0], A0[h][1], P[T + 1][0], P[T + 1][1], P[9 + T][1], P[9 + T + 1][1]);
        }
        const uint2 ck0 = lds64(rowc + 8 * t), ck1 = lds64(rowc + 32 + 8 * t);
        const float sc = 0.23570226039551584f * 1.4426950408889634f;
        const float cq0 = ldsf(rowc + 4 * g) * sc, cq1 = ldsf(rowc + 32 + 4 * g) * sc;
        uint8_t* ob = GC(act, 2 * L * ACT + mw * 73728 + r * 9216 + j * 256 + ln * 4);
        float l[2][4][2], ks[2][2], mx[2][4];
        ks[1][0] = __uint_as_float(le0 ? ck1.x : ck0.x); ks[1][1] = __uint_as_float(le1 ? ck1.y : ck0.y);
#pragma unroll
        for (int h = 0; h < 4; h++) {
          l[1][h][0] = (le0 ? s1[h][2] : s0[h][2]) * (cq1 * ks[1][0]); l[1][h][1] = (le1 ? s1[h][3] : s0[h][3]) * (cq1 * ks[1][1]);
          asm volatile("" : "+f"(l[1][h][0]), "+f"(l[1][h][1]));
        }
        asm volatile("" : "+l"(fptr), "+l"(ob));
        {
          uint32_t n = 0;
          _Pragma("unroll 1") while (__any_sync(0xffffffffu, min(min(min(H[0], H[4]), min(H[8], H[12])), H[16]) == 0)) {
            halo();
            spin_guard(n);
          }
        }
        if (ln == 0) mbar_arrive_pair(sb + B_WEMPTY + 24);
        TRW(3 + 12 * L);
        {
          float sm[4][4];
#pragma unroll
          for (int h = 0; h < 4; h++) mma8z(sm[h], A2[h][0], A2[h][1], H[2 * h + 2]);
#pragma unroll
          for (int h = 0; h < 4; h++) mma16(sm[h], A0[h][0], A0[h][1], P[2 * h + 1][0], P[2 * h + 1][1], H[2 * h], H[2 * h + 1]);
          ks[0][0] = __uint_as_float(le0 ? ck0.x : H[12]); ks[0][1] = __uint_as_float(le1 ? ck0.y : H[16]);
          const bool nohalo = (m == 0 && j == 0);
          const float b0 = (nohalo && !le0) ? -INFINITY : 0.f, b1 = (nohalo && !le1) ? -INFINITY : 0.f;
#pragma unroll
          for (int h = 0; h < 4; h++) {
            l[0][h][0] = fmaf(le0 ? s0[h][0] : sm[h][0], cq0 * ks[0][0], b0);
            l[0][h][1] = fmaf(le1 ? s0[h][1] : sm[h][1], cq0 * ks[0][1], b1);
          }
        }
#pragma unroll
        for (int i = 7; i >= 0; i--) mx[i >> 2][i & 3] = fmaxf(l[i >> 2][i & 3][0], l[i >> 2][i & 3][1]);
#pragma unroll
        for (int x = 1; x <= 2; x <<= 1) {
#pragma unroll
          for (int i = 7; i >= 0; i--) mx[i >> 2][i & 3] = fmaxf(mx[i >> 2][i & 3], shx(mx[i >> 2][i & 3], x));
        }
        const uint32_t mle = (le0 ? 0xffffu : 0u) | (le1 ? 0xffff0000u : 0u);
        uint32_t pp[2][4], pc[2][4];
#pragma unroll
        for (int i = 3; i >= 0; i--) {
          const int e = i >> 1, h = 2 * (i & 1);
          const float p0 = ex2(l[e][h][0] - mx[e][h]), p1 = ex2(l[e][h][1] - mx[e][h]);
          const float p2 = ex2(l[e][h + 1][0] - mx[e][h + 1]), p3 = ex2(l[e][h + 1][1] - mx[e][h + 1]);
          float sum[4];
          mma8z(sum, packbf(p0, p1), packbf(p2, p3), 0x3f803f80u);
          const float inv = rcp(sum[0] * sum[2]);
          const float ia = inv * sum[2], ib = inv * sum[0];
          const uint32_t u0 = packbf(p0 * ks[e][0] * ia, p1 * ks[e][1] * ia), u1 = packbf(p2 * ks[e][0] * ib, p3 * ks[e][1] * ib);
          pp[e][h] = u0 & ~mle; pc[e][h] = u0 & mle; pp[e][h + 1] = u1 & ~mle; pc[e][h + 1] = u1 & mle;
        }
#pragma unroll
        for (int e = 1; e >= 0; e--) {
#pragma unroll
          for (int q = 8; q >= 0; q--) {
            const int h = q < 4 ? 0 : q == 4 ? 1 : 2;
            float a[4];
            mma16z(a, pp[e][h], pp[e][h + 1], pc[e][h], pc[e][h + 1], e ? P[18 + q][0] : H[9 + q + q / 3], P[18 + q][e]);
            const bool second = q == 2 * h + 2 ? t > h : q > 2 * h + 2;
            st_rlx(ob + q * 1024 + e * 128, nz(packbf(second ? a[2] : a[0], second ? a[3] : a[1])));
          }
        }
        if (ln == 0) st_rlx(fptr, epoch * 4 + 1 + 2 * L);
        TRW(4 + 12 * L);
      }
      RELANE2;
      float d[36];
      uint32_t WB[9];
      {
        uint32_t R[10][2];
        const uint32_t qs = L == 0 ? 16 : 1024, ra = xring + (16 * j + (ln & 15)) * (L == 0 ? 144 : 16) + (ln >> 4) * qs;
        mbar_wait(sb + B_RES + 8 * w, L);
#pragma unroll
        for (int q = 0; q < 10; q += 2) ldsm4(&R[q][0], ra + q * qs);
        fence_async_smem();
        __syncwarp();
        if (ln == 0) mbar_arrive(sb + B_RC + 8 * w);
#pragma unroll
        for (int q = 0; q < 9; q++) WB[q] = ldg32(p.wr + (uint32_t)(r * 144 + 4 * t) + 16 * q);
#pragma unroll
        for (int h = 0; h < 2; h++) {
          const uint2 mf = lds64(rowm + 8 * g + 64 * h);
          const float f = __uint_as_float(mf.y), k = -__uint_as_float(mf.x) * f;
#pragma unroll
          for (int q = 0; q < 9; q++) { d[4 * q + 2 * h] = fmaf(blo(R[q][h]), f, k); d[4 * q + 2 * h + 1] = fmaf(bhi(R[q][h]), f, k); }
        }
        const uint32_t sel = lds32(sb + SM_SEL);
        if (L == 1 && (sel & 127) == cid) {
          const int selrow = sel >> 7;
#pragma unroll
          for (int q = 0; q < 18; q++) lds64f_if(selrow == g + 8 * (q & 1), d[2 * q], d[2 * q + 1], sb + SM_X2R + 32 * (q >> 1) + 8 * t);
        }
#pragma unroll
        for (int q = 0; q < 9; q++) WB[q] = (g & 1) ? WB[q] : 0x3f803f80u;
        __syncwarp();
      }
      uint8_t* xb = GC(act, ACT + mw * 73728 + r * 9216 + j * 256 + ln * 4);
      uint8_t* sst = GA(statsP, mw * 8192 + r * 1024 + (16 * j + g + 8 * t) * 16);
      const uint8_t* sld = GA(statsP, mw * 8192 + (ln >> 4) * 4096 + (16 * j + (ln & 15)) * 16);
      uint8_t* cptr = GA(cand, (8 * L + r) * 2048 + 16 * cid);
      uint8_t* crow = GC(candrow, (128 * L + cid) * 1152 + 144 * r + 4 * t);
      uint32_t tag = epoch * 2 + L, ktag = ((ln & 15) << 7) | (epoch & 0x7f);
      float wsum = ldsf(sb + SM_WSUM);
      float pivot = __uint_as_float(ld_rlx(GA(stats0, 16 * (16 * cid + (ln & 15)) + 4))) + (L ? ldsf(rowm + 8 * (ln & 15)) : 0.f);
      asm volatile("" : "+l"(xb), "+l"(sst), "+l"(sld), "+l"(cptr), "+l"(crow), "+r"(tag), "+r"(ktag), "+f"(wsum), "+f"(pivot));
      TRW(5 + 12 * L);
      {
        constexpr uint32_t bdesc = mkdesc(sbd + SM_W + WSTAGE, 1152);
        uint32_t adesc[3];
#pragma unroll
        for (int i = 0; i < 3; i++) adesc[i] = __shfl_sync(0xffffffffu, mkdesc(sbd + SM_X + w * 4 * XSTAGE, 1024) + (ln >> 2), i);
#pragma unroll
        for (int i = 0; i < 36; i++) asm volatile("" : "+f"(d[i])::"memory");
        const bool lead = warp == 0 && ln == 0;
        const uint8_t* osrc = GC(act, 2 * L * ACT + mw * 73728);
        mbar_wait2(sb + B_WFULL + 8, L, xfull, 1);
        check_stage(probe_stage(pa), xring, osrc);
        TRW(6 + 12 * L);
#pragma unroll
        for (int s = 0; s < 9; s++) {
          TRQ(18 + s);
          const uint32_t da = s == 4 ? adesc[1] - ((SM_X - SM_W) >> 4) - w * 3 * (XSTAGE >> 4) : adesc[s >> 2] + (s < 4 ? s : s - 5) * (XSTAGE >> 4);
          const uint32_t db = bdesc + s * (9216 >> 4);
          const int n1 = s + 1, nx = n1 < 4 ? n1 : n1 - 5;
          const uint32_t xoff = n1 == 4 ? SM_W - SM_X - w * 3 * XSTAGE : nx * XSTAGE;
          asm volatile("wgmma.fence.sync.aligned;" ::: "memory");
          wgmma_n72(d, da, 8u, db);
          wgmma_n72(d, da + 128, 8u, db + (2304 >> 4));
          asm volatile("wgmma.commit_group.sync.aligned;" ::: "memory");
          if (s > 0) {
            asm volatile("wgmma.wait_group.sync.aligned 1;" ::: "memory");
            if (ln == 0) {
              if (s != 5) mbar_arrive(xempty + 8 * (s < 5 ? s - 1 : s - 6));
              if (L == 0) {
                if (s == WR0) mbar_arrive_pair(sb + B_WEMPTY);
                if (s == WR1) mbar_arrive_pair(sb + B_WEMPTY + 8);
                if (s == WR2) mbar_arrive_pair(sb + B_WEMPTY + 16);
              }
            }
          }
          const uint32_t xbar = n1 == 4 ? sb + B_XE + 8 * w : xfull + 8 * nx, px = n1 == 4 ? L : n1 >= 6;
          if ((s == 0 || s == 8) && lead) mbar_arrive(sb + (s ? B_EPI : B_OS));
          if (s < 8) {
            uint32_t pv;
            const uint32_t dsc[4] = {da + 256, db + (4608 >> 4), da + 384, db + (6912 >> 4)};
            const uint32_t bar[4] = {sb + B_WFULL + 8 + 8 * ((s + 1) / 3), (uint32_t)L, xbar, px}, adr = pa + xoff;
            o_tail2(d, &pv, 8u, dsc, bar, &adr);
            check_stage(pv, xring + xoff, osrc + (s + 1) * XSTAGE);
          } else {
            wgmma_n72(d, da + 256, 8u, db + (4608 >> 4));
            wgmma_n72(d, da + 384, 8u, db + (6912 >> 4));
            asm volatile("wgmma.commit_group.sync.aligned;" ::: "memory");
          }
        }
        asm volatile("wgmma.wait_group.sync.aligned 0;" ::: "memory");
#pragma unroll
        for (int i = 0; i < 36; i++) asm volatile("" : "+f"(d[i])::"memory");
        mbar_wait(xfull, 1);
        if (ln == 0) { if (L == 0) mbar_arrive_pair(sb + B_WEMPTY + 24); mbar_arrive(xempty + 24); mbar_arrive(xempty); }
      }
      TRW(7 + 12 * L);
      uint32_t R[9][2];
#pragma unroll
      for (int q = 0; q < 9; q++) { R[q][0] = packbf(d[4 * q], d[4 * q + 1]); R[q][1] = packbf(d[4 * q + 2], d[4 * q + 3]); }
      {
        float sa[4], sc[4];
        mma16z(sa, R[0][0], R[0][1], R[1][0], R[1][1], WB[0], WB[1]);
        mma16z(sc, R[2][0], R[2][1], R[3][0], R[3][1], WB[2], WB[3]);
        mma16(sa, R[4][0], R[4][1], R[5][0], R[5][1], WB[4], WB[5]);
        mma16(sc, R[6][0], R[6][1], R[7][0], R[7][1], WB[6], WB[7]);
        mma8(sa, R[8][0], R[8][1], WB[8]);
        float qq[4] = {0.f, 0.f, 0.f, 0.f};
#pragma unroll
        for (int q = 0; q < 36; q++) qq[q & 3] = fmaf(d[q], d[q], qq[q & 3]);
        const float qa = qq[0] + qq[1], qc = qq[2] + qq[3];
        const bool odd = t & 1;
        float q2 = (odd ? qc : qa) + shx(odd ? qa : qc, 1);
        q2 += shx(q2, 2);
        if (t < 2)
          st_msg(sst, __float_as_uint(odd ? sa[2] + sc[2] : sa[0] + sc[0]), __float_as_uint(q2),
                 __float_as_uint(odd ? sa[3] + sc[3] : sa[1] + sc[1]), tag);
      }
      if (L == 0) {
#pragma unroll
        for (int q = 0; q < 9; q++) { st_rlx(xb + q * 1024, nz(R[q][0])); st_rlx(xb + q * 1024 + 128, nz(R[q][1])); }
        if (ln == 0) st_rlx(fptr, epoch * 4 + 2);
      }
      TRW(8 + 12 * L);
      {
        uint4 u[4];
        uint32_t n = 0;
        _Pragma("unroll 1") while (true) {
#pragma unroll
          for (int i = 0; i < 4; i++) u[i] = ld_msg(sld + 1024 * i);
          if (!__any_sync(0xffffffffu, (u[0].w ^ tag) | (u[1].w ^ tag) | (u[2].w ^ tag) | (u[3].w ^ tag))) break;
          spin_guard(n);
        }
        TRW(9 + 12 * L);
        float s1 = (__uint_as_float(u[0].x) + __uint_as_float(u[1].x)) + (__uint_as_float(u[2].x) + __uint_as_float(u[3].x));
        float s2 = (__uint_as_float(u[0].y) + __uint_as_float(u[1].y)) + (__uint_as_float(u[2].y) + __uint_as_float(u[3].y));
        float s3 = (__uint_as_float(u[0].z) + __uint_as_float(u[1].z)) + (__uint_as_float(u[2].z) + __uint_as_float(u[3].z));
        s1 += shx(s1, 16); s2 += shx(s2, 16); s3 += shx(s3, 16);
        const float mu = s1 * (1.f / kD);
        const float var = fmaxf(fmaf(s2, 1.f / kD, -mu * mu), 0.f);
        const float sd = ln_sd(var), rho = rcp(sd);
        const float rr = (s3 - mu * wsum) * rho;
        const int key = __reduce_max_sync(0xffffffffu, (int)((fkey(rr) & ~0x7ff) | ktag));
        const int best = (key >> 7) & 15;
        if (ln == best) st_msg(cptr, key, __float_as_uint(rbf(sigmoidf(rbf(rr)))), __float_as_uint(1.f + sd), __float_as_uint(L ? pivot + mu : 0.f));
        const float rb = __shfl_sync(0xffffffffu, rho, best), nb = __shfl_sync(0xffffffffu, -mu * rho, best);
        if ((best & 7) == g) {
          const bool hi = best >= 8;
#pragma unroll
          for (int q = 0; q < 9; q++)
            st_rlx(crow + (((q ^ r) & 1) * (4 - 8 * (t & 1))) + 16 * q, nz(packbf(fmaf(hi ? d[4 * q + 2] : d[4 * q], rb, nb), fmaf(hi ? d[4 * q + 3] : d[4 * q + 1], rb, nb))));
        }
        const float f = 1.f + rho, k = pivot - mu * rho;
        sts32(rowc + 4 * (ln & 15), __float_as_uint(f * rcp(ln_sd(var * f * f))));
        sts64(rowm + 8 * (ln & 15), __float_as_uint(L == 0 ? mu : k), __float_as_uint(f));
        __syncwarp();
      }
      TRW(10 + 12 * L);
      if (L == 1) {
#pragma unroll
        for (int h = 0; h < 2; h++) {
          const uint2 kf = lds64(rowm + 8 * g + 64 * h);
          const float k = __uint_as_float(kf.x), f = __uint_as_float(kf.y);
#pragma unroll
          for (int q = 0; q < 9; q++) R[q][h] = packbf(fmaf(d[4 * q + 2 * h], f, k), fmaf(d[4 * q + 2 * h + 1], f, k));
        }
        mbar_wait(xempty + 16, 1);
        const uint32_t st = xring + XSTAGE + (16 * j + (ln & 15)) * 144;
#pragma unroll
        for (int q = 0; q < 8; q += 2) stsm4(st + (ln >> 4) * 16 + q * 16, R[q][0], R[q][1], R[q + 1][0], R[q + 1][1]);
        stsm2(st + 128, R[8][0], R[8][1]);
        fence_async_smem();
        __syncwarp();
        mbar_wait(sb + B_IDX + 8, 0);
        const uint32_t sel = lds32(sb + SM_SEL + 4);
        if ((sel & 127) != cid) {
          if (elect())
            asm volatile("cp.async.bulk.tensor.3d.global.shared::cta.bulk_group [%0, {%2,%3,%4}], [%1];" ::"l"(&tm.out),
                         "r"(xring + XSTAGE + 16 * j * 144), "r"(72 * r), "r"(w), "r"(64 * m + 16 * j) : "memory");
        } else if (ln < 16 && ln != (sel >> 7)) {
          bulk_s2g(p.out + (uint32_t)((128 * m + 2 * (16 * j + ln) + w) * 1152 + r * 144), st, 144);
        }
        asm volatile("cp.async.bulk.commit_group;" ::: "memory");
        asm volatile("cp.async.bulk.wait_group.read 0;" ::: "memory");
        TRW(11 + 12 * L);
        TRDUMP(w);
      }
    }
  }
}

typedef CUresult (*EncodeFn)(CUtensorMap*, CUtensorMapDataType, cuuint32_t, void*, const cuuint64_t*, const cuuint64_t*,
                             const cuuint32_t*, const cuuint32_t*, CUtensorMapInterleave, CUtensorMapSwizzle,
                             CUtensorMapL2promotion, CUtensorMapFloatOOBfill);

}

extern "C" void kernel_launch(void* const* d_in, const int* in_sizes, int n_in, void* d_out, int out_size) {
  static EncodeFn enc = nullptr;
  static Scratch* scratch = nullptr;
  if (!enc) {
    cudaDriverEntryPointQueryResult q;
    cudaGetDriverEntryPoint("cuTensorMapEncodeTiled", (void**)&enc, cudaEnableDefault, &q);
    cudaGetSymbolAddress((void**)&scratch, g_s);
    cudaFuncSetAttribute(fused_kernel, cudaFuncAttributeMaxDynamicSharedMemorySize, 232448);
  }
  Maps tm;
  auto mk = [&](CUtensorMap* t, void* ptr, int rank, const cuuint64_t* dims, const cuuint64_t* strides, const cuuint32_t* box,
                CUtensorMapSwizzle sw, CUtensorMapL2promotion pr) {
    const cuuint32_t es[4] = {1, 1, 1, 1};
    enc(t, CU_TENSOR_MAP_DATA_TYPE_BFLOAT16, rank, ptr, dims, strides, box, es, CU_TENSOR_MAP_INTERLEAVE_NONE, sw, pr,
        CU_TENSOR_MAP_FLOAT_OOB_FILL_NONE);
  };
  { const cuuint64_t d[3] = {576, 2, 1024}, st[2] = {1152, 2304}; const cuuint32_t bx[3] = {64, 1, 64};
    mk(&tm.x, d_in[0], 3, d, st, bx, CU_TENSOR_MAP_SWIZZLE_128B, CU_TENSOR_MAP_L2_PROMOTION_NONE);
    const cuuint32_t br[3] = {72, 1, 64};
    mk(&tm.xr, d_in[0], 3, d, st, br, CU_TENSOR_MAP_SWIZZLE_NONE, CU_TENSOR_MAP_L2_PROMOTION_NONE);
    const cuuint32_t bo[3] = {72, 1, 16};
    mk(&tm.out, d_out, 3, d, st, bo, CU_TENSOR_MAP_SWIZZLE_NONE, CU_TENSOR_MAP_L2_PROMOTION_NONE); }
  { const cuuint64_t d[3] = {576, 576, 3}, st[2] = {3456, 1152}; const cuuint32_t bx[3] = {72, 8, 2};
    mk(&tm.wq, d_in[1], 3, d, st, bx, CU_TENSOR_MAP_SWIZZLE_NONE, CU_TENSOR_MAP_L2_PROMOTION_NONE); }
  { const cuuint64_t d[2] = {576, 576}, st[1] = {1152}; const cuuint32_t bx[2] = {72, 16};
    mk(&tm.wo, d_in[2], 2, d, st, bx, CU_TENSOR_MAP_SWIZZLE_NONE, CU_TENSOR_MAP_L2_PROMOTION_NONE); }
  { const cuuint64_t d[2] = {4608, 576}, st[1] = {9216}; const cuuint32_t bx[2] = {48, 64};
    mk(&tm.wg, d_in[5], 2, d, st, bx, CU_TENSOR_MAP_SWIZZLE_128B, CU_TENSOR_MAP_L2_PROMOTION_L2_128B);
    mk(&tm.wu, d_in[6], 2, d, st, bx, CU_TENSOR_MAP_SWIZZLE_128B, CU_TENSOR_MAP_L2_PROMOTION_L2_128B); }
  Params p;
  p.x = (const uint8_t*)d_in[0]; p.wqkv = (const uint8_t*)d_in[1]; p.wo = (const uint8_t*)d_in[2];
  p.wr = (const uint8_t*)d_in[4]; p.wg = (const uint8_t*)d_in[5]; p.wu = (const uint8_t*)d_in[6]; p.wd = (const uint8_t*)d_in[7];
  p.out = (uint8_t*)d_out;
  p.g = scratch;
  fused_kernel<<<128, 512, 232448>>>(p, tm);
}
```

```cpp
#include <cuda_runtime.h>
#include <cuda_bf16.h>
#include <cuda.h>
#include <stdint.h>
#include <stddef.h>

#define DEVI __device__ __forceinline__

namespace {

constexpr int kD = 576, kF = 4608;
constexpr uint32_t WSTAGE = 27648, XSTAGE = 8192;
constexpr float kEps = 1e-5f;

constexpr uint32_t WDP = 1168;
constexpr uint32_t SM_W = 0;
constexpr uint32_t SM_X = 110592;
constexpr uint32_t SM_WD = 176128;
constexpr uint32_t SM_LEFT = SM_WD + 36 * WDP;
constexpr uint32_t SM_COLSUM = SM_LEFT + 9216;
constexpr uint32_t SM_ROWC = SM_COLSUM + 960;
constexpr uint32_t SM_ROWM = SM_ROWC + 512;
constexpr uint32_t SM_PART = SM_ROWM + 1024;
constexpr uint32_t SM_FIXQ = SM_PART;
constexpr uint32_t SM_X2R = SM_PART + 864;
constexpr uint32_t SM_H = SM_PART + 1152;
constexpr uint32_t SM_GEMV = SM_H;
constexpr uint32_t SM_RED = SM_H + 320;
constexpr uint32_t SM_SEL = SM_RED + 256;
constexpr uint32_t SM_EP = SM_SEL + 8, SM_WSUM = SM_SEL + 12;
constexpr uint32_t SM_BAR = SM_SEL + 16;
constexpr uint32_t B_WFULL = SM_BAR, B_WEMPTY = B_WFULL + 32, B_XFULL = B_WEMPTY + 32, B_XEMPTY = B_XFULL + 64;
constexpr uint32_t B_RC = B_XEMPTY + 64;
constexpr uint32_t B_COLSUM = B_RC + 16, B_PKF = B_COLSUM + 8, B_FIX = B_PKF + 8, B_DONE = B_FIX + 8;
constexpr uint32_t B_FF = B_DONE + 8;
constexpr uint32_t B_IDX = B_FF + 24;
constexpr uint32_t B_WD = B_IDX + 16, B_WANT = B_WD + 8, B_EPI = B_WANT + 8, B_EP = B_EPI + 8, B_OS = B_EP + 8, B_FD = B_OS + 8;
constexpr uint32_t B_WL = B_FD + 8;
constexpr uint32_t B_RES = B_WL + 32;
constexpr uint32_t B_XE = B_RES + 16;
constexpr uint32_t SM_TOTAL = B_XE + 16;
constexpr int NBAR = (SM_TOTAL - SM_BAR) / 8, NBAR4 = (B_FF - SM_BAR) / 8;
static_assert(((B_EP - SM_BAR) / 8 * 4) / NBAR == 3, "warp 15 initialises B_EP");
constexpr uint32_t FSLOT = 16384;
static_assert(SM_TOTAL + 256 <= 232448, "smem");

struct __align__(1024) Checked {
  uint32_t candrow[2][128][288];
  uint4 halo[128][2][2][5][32];
  uint8_t wpack[8][12 * WSTAGE];
  uint8_t act[3][16][2][73728];
};
struct __align__(1024) Scratch {
  uint4 cand[2][8][128];
  uint4 ypart[72][128][2];
  uint32_t x2msg[8][576];
  uint32_t fixmsg[8][256];
  uint32_t flagP[8][12][32];
  uint32_t flagX[16][2][32];
  uint32_t epoch[128][8];
  uint4 stats0[16][2][64];
  uint4 statsP[16][2][8][64];
  float colpart[8][8][216];
  Checked chk[2];
};
__device__ Scratch g_s;
#define GA(member, off) (gb + offsetof(Scratch, member) + (uint32_t)(off))
#define GC(member, off) (gb + offsetof(Scratch, chk) + offsetof(Checked, member) + (uint32_t)((off) + (epoch & 1) * (uint32_t)sizeof(Checked)))
constexpr uint32_t ACT = 16 * 2 * 73728;

#define TR(role, i)
#define TRL(role, i)
#define TRDUMP(role)
#define TRW(i)
#define TRZ(i)
#define TRQ(i)

__device__ __forceinline__ void wgmma_n144(float* d, uint32_t alo, uint32_t ahi, uint32_t blo) {
  asm volatile("{\n.reg .b64 da, db;\nmov.b64 da, {%72, %73};\nmov.b64 db, {%74, 8};\n"
    "wgmma.mma_async.sync.aligned.m64n144k16.f32.bf16.bf16 "
    "{%0, %1, %2, %3, %4, %5, %6, %7, %8, %9, %10, %11, %12, %13, %14, %15, %16, %17, %18, %19, %20, %21, %22, %23, %24, %25, %26, %27, %28, %29, %30, %31, %32, %33, %34, %35, %36, %37, %38, %39, %40, %41, %42, %43, %44, %45, %46, %47, %48, %49, %50, %51, %52, %53, %54, %55, %56, %57, %58, %59, %60, %61, %62, %63, %64, %65, %66, %67, %68, %69, %70, %71}, da, db, 1, 1, 1, 0, 1;\n}\n"
    : "+f"(d[0]), "+f"(d[1]), "+f"(d[2]), "+f"(d[3]), "+f"(d[4]), "+f"(d[5]), "+f"(d[6]), "+f"(d[7]), "+f"(d[8]),
      "+f"(d[9]), "+f"(d[10]), "+f"(d[11]), "+f"(d[12]), "+f"(d[13]), "+f"(d[14]), "+f"(d[15]), "+f"(d[16]), "+f"(d[17]),
      "+f"(d[18]), "+f"(d[19]), "+f"(d[20]), "+f"(d[21]), "+f"(d[22]), "+f"(d[23]), "+f"(d[24]), "+f"(d[25]), "+f"(d[26]),
      "+f"(d[27]), "+f"(d[28]), "+f"(d[29]), "+f"(d[30]), "+f"(d[31]), "+f"(d[32]), "+f"(d[33]), "+f"(d[34]), "+f"(d[35]),
      "+f"(d[36]), "+f"(d[37]), "+f"(d[38]), "+f"(d[39]), "+f"(d[40]), "+f"(d[41]), "+f"(d[42]), "+f"(d[43]), "+f"(d[44]),
      "+f"(d[45]), "+f"(d[46]), "+f"(d[47]), "+f"(d[48]), "+f"(d[49]), "+f"(d[50]), "+f"(d[51]), "+f"(d[52]), "+f"(d[53]),
      "+f"(d[54]), "+f"(d[55]), "+f"(d[56]), "+f"(d[57]), "+f"(d[58]), "+f"(d[59]), "+f"(d[60]), "+f"(d[61]), "+f"(d[62]),
      "+f"(d[63]), "+f"(d[64]), "+f"(d[65]), "+f"(d[66]), "+f"(d[67]), "+f"(d[68]), "+f"(d[69]), "+f"(d[70]), "+f"(d[71])
    : "r"(alo), "r"(ahi), "r"(blo));
}
__device__ __forceinline__ void wgmma_n144_set(float* d, const uint32_t* a, uint32_t blo) {
  asm volatile("{\n.reg .b64 db;\nmov.b64 db, {%76, 2};\n"
    "wgmma.mma_async.sync.aligned.m64n144k16.f32.bf16.bf16 "
    "{%0, %1, %2, %3, %4, %5, %6, %7, %8, %9, %10, %11, %12, %13, %14, %15, %16, %17, %18, %19, %20, %21, %22, %23, %24, %25, %26, %27, %28, %29, %30, %31, %32, %33, %34, %35, %36, %37, %38, %39, %40, %41, %42, %43, %44, %45, %46, %47, %48, %49, %50, %51, %52, %53, %54, %55, %56, %57, %58, %59, %60, %61, %62, %63, %64, %65, %66, %67, %68, %69, %70, %71}, {%72, %73, %74, %75}, db, 0, -1, 1, 1;\n}\n"
    : "=f"(d[0]), "=f"(d[1]), "=f"(d[2]), "=f"(d[3]), "=f"(d[4]), "=f"(d[5]), "=f"(d[6]), "=f"(d[7]), "=f"(d[8]),
      "=f"(d[9]), "=f"(d[10]), "=f"(d[11]), "=f"(d[12]), "=f"(d[13]), "=f"(d[14]), "=f"(d[15]), "=f"(d[16]), "=f"(d[17]),
      "=f"(d[18]), "=f"(d[19]), "=f"(d[20]), "=f"(d[21]), "=f"(d[22]), "=f"(d[23]), "=f"(d[24]), "=f"(d[25]), "=f"(d[26]),
      "=f"(d[27]), "=f"(d[28]), "=f"(d[29]), "=f"(d[30]), "=f"(d[31]), "=f"(d[32]), "=f"(d[33]), "=f"(d[34]), "=f"(d[35]),
      "=f"(d[36]), "=f"(d[37]), "=f"(d[38]), "=f"(d[39]), "=f"(d[40]), "=f"(d[41]), "=f"(d[42]), "=f"(d[43]), "=f"(d[44]),
      "=f"(d[45]), "=f"(d[46]), "=f"(d[47]), "=f"(d[48]), "=f"(d[49]), "=f"(d[50]), "=f"(d[51]), "=f"(d[52]), "=f"(d[53]),
      "=f"(d[54]), "=f"(d[55]), "=f"(d[56]), "=f"(d[57]), "=f"(d[58]), "=f"(d[59]), "=f"(d[60]), "=f"(d[61]), "=f"(d[62]),
      "=f"(d[63]), "=f"(d[64]), "=f"(d[65]), "=f"(d[66]), "=f"(d[67]), "=f"(d[68]), "=f"(d[69]), "=f"(d[70]), "=f"(d[71])
    : "r"(a[0]), "r"(a[1]), "r"(a[2]), "r"(a[3]), "r"(blo));
}
__device__ __forceinline__ void wgmma_n144_add(float* d, const uint32_t* a, uint32_t blo) {
  asm volatile("{\n.reg .b64 db;\nmov.b64 db, {%76, 2};\n"
    "wgmma.mma_async.sync.aligned.m64n144k16.f32.bf16.bf16 "
    "{%0, %1, %2, %3, %4, %5, %6, %7, %8, %9, %10, %11, %12, %13, %14, %15, %16, %17, %18, %19, %20, %21, %22, %23, %24, %25, %26, %27, %28, %29, %30, %31, %32, %33, %34, %35, %36, %37, %38, %39, %40, %41, %42, %43, %44, %45, %46, %47, %48, %49, %50, %51, %52, %53, %54, %55, %56, %57, %58, %59, %60, %61, %62, %63, %64, %65, %66, %67, %68, %69, %70, %71}, {%72, %73, %74, %75}, db, 1, -1, 1, 1;\n}\n"
    : "+f"(d[0]), "+f"(d[1]), "+f"(d[2]), "+f"(d[3]), "+f"(d[4]), "+f"(d[5]), "+f"(d[6]), "+f"(d[7]), "+f"(d[8]),
      "+f"(d[9]), "+f"(d[10]), "+f"(d[11]), "+f"(d[12]), "+f"(d[13]), "+f"(d[14]), "+f"(d[15]), "+f"(d[16]), "+f"(d[17]),
      "+f"(d[18]), "+f"(d[19]), "+f"(d[20]), "+f"(d[21]), "+f"(d[22]), "+f"(d[23]), "+f"(d[24]), "+f"(d[25]), "+f"(d[26]),
      "+f"(d[27]), "+f"(d[28]), "+f"(d[29]), "+f"(d[30]), "+f"(d[31]), "+f"(d[32]), "+f"(d[33]), "+f"(d[34]), "+f"(d[35]),
      "+f"(d[36]), "+f"(d[37]), "+f"(d[38]), "+f"(d[39]), "+f"(d[40]), "+f"(d[41]), "+f"(d[42]), "+f"(d[43]), "+f"(d[44]),
      "+f"(d[45]), "+f"(d[46]), "+f"(d[47]), "+f"(d[48]), "+f"(d[49]), "+f"(d[50]), "+f"(d[51]), "+f"(d[52]), "+f"(d[53]),
      "+f"(d[54]), "+f"(d[55]), "+f"(d[56]), "+f"(d[57]), "+f"(d[58]), "+f"(d[59]), "+f"(d[60]), "+f"(d[61]), "+f"(d[62]),
      "+f"(d[63]), "+f"(d[64]), "+f"(d[65]), "+f"(d[66]), "+f"(d[67]), "+f"(d[68]), "+f"(d[69]), "+f"(d[70]), "+f"(d[71])
    : "r"(a[0]), "r"(a[1]), "r"(a[2]), "r"(a[3]), "r"(blo));
}
__device__ __forceinline__ void wgmma_n72(float* d, uint32_t alo, uint32_t ahi, uint32_t blo) {
  asm volatile("{\n.reg .b64 da, db;\nmov.b64 da, {%36, %37};\nmov.b64 db, {%38, 8};\n"
    "wgmma.mma_async.sync.aligned.m64n72k16.f32.bf16.bf16 "
    "{%0, %1, %2, %3, %4, %5, %6, %7, %8, %9, %10, %11, %12, %13, %14, %15, %16, %17, %18, %19, %20, %21, %22, %23, %24, %25, %26, %27, %28, %29, %30, %31, %32, %33, %34, %35}, da, db, 1, 1, 1, 0, 1;\n}\n"
    : "+f"(d[0]), "+f"(d[1]), "+f"(d[2]), "+f"(d[3]), "+f"(d[4]), "+f"(d[5]), "+f"(d[6]), "+f"(d[7]), "+f"(d[8]),
      "+f"(d[9]), "+f"(d[10]), "+f"(d[11]), "+f"(d[12]), "+f"(d[13]), "+f"(d[14]), "+f"(d[15]), "+f"(d[16]), "+f"(d[17]),
      "+f"(d[18]), "+f"(d[19]), "+f"(d[20]), "+f"(d[21]), "+f"(d[22]), "+f"(d[23]), "+f"(d[24]), "+f"(d[25]), "+f"(d[26]),
      "+f"(d[27]), "+f"(d[28]), "+f"(d[29]), "+f"(d[30]), "+f"(d[31]), "+f"(d[32]), "+f"(d[33]), "+f"(d[34]), "+f"(d[35])
    : "r"(alo), "r"(ahi), "r"(blo));
}
__device__ __forceinline__ void wgmma_n72_set(float* d, const uint32_t* a, uint32_t blo) {
  asm volatile("{\n.reg .b64 db;\nmov.b64 db, {%40, 2};\n"
    "wgmma.mma_async.sync.aligned.m64n72k16.f32.bf16.bf16 "
    "{%0, %1, %2, %3, %4, %5, %6, %7, %8, %9, %10, %11, %12, %13, %14, %15, %16, %17, %18, %19, %20, %21, %22, %23, %24, %25, %26, %27, %28, %29, %30, %31, %32, %33, %34, %35}, {%36, %37, %38, %39}, db, 0, -1, 1, 1;\n}\n"
    : "=f"(d[0]), "=f"(d[1]), "=f"(d[2]), "=f"(d[3]), "=f"(d[4]), "=f"(d[5]), "=f"(d[6]), "=f"(d[7]), "=f"(d[8]),
      "=f"(d[9]), "=f"(d[10]), "=f"(d[11]), "=f"(d[12]), "=f"(d[13]), "=f"(d[14]), "=f"(d[15]), "=f"(d[16]), "=f"(d[17]),
      "=f"(d[18]), "=f"(d[19]), "=f"(d[20]), "=f"(d[21]), "=f"(d[22]), "=f"(d[23]), "=f"(d[24]), "=f"(d[25]), "=f"(d[26]),
      "=f"(d[27]), "=f"(d[28]), "=f"(d[29]), "=f"(d[30]), "=f"(d[31]), "=f"(d[32]), "=f"(d[33]), "=f"(d[34]), "=f"(d[35])
    : "r"(a[0]), "r"(a[1]), "r"(a[2]), "r"(a[3]), "r"(blo));
}
__device__ __forceinline__ void wgmma_n72_add(float* d, const uint32_t* a, uint32_t blo) {
  asm volatile("{\n.reg .b64 db;\nmov.b64 db, {%40, 2};\n"
    "wgmma.mma_async.sync.aligned.m64n72k16.f32.bf16.bf16 "
    "{%0, %1, %2, %3, %4, %5, %6, %7, %8, %9, %10, %11, %12, %13, %14, %15, %16, %17, %18, %19, %20, %21, %22, %23, %24, %25, %26, %27, %28, %29, %30, %31, %32, %33, %34, %35}, {%36, %37, %38, %39}, db, 1, -1, 1, 1;\n}\n"
    : "+f"(d[0]), "+f"(d[1]), "+f"(d[2]), "+f"(d[3]), "+f"(d[4]), "+f"(d[5]), "+f"(d[6]), "+f"(d[7]), "+f"(d[8]),
      "+f"(d[9]), "+f"(d[10]), "+f"(d[11]), "+f"(d[12]), "+f"(d[13]), "+f"(d[14]), "+f"(d[15]), "+f"(d[16]), "+f"(d[17]),
      "+f"(d[18]), "+f"(d[19]), "+f"(d[20]), "+f"(d[21]), "+f"(d[22]), "+f"(d[23]), "+f"(d[24]), "+f"(d[25]), "+f"(d[26]),
      "+f"(d[27]), "+f"(d[28]), "+f"(d[29]), "+f"(d[30]), "+f"(d[31]), "+f"(d[32]), "+f"(d[33]), "+f"(d[34]), "+f"(d[35])
    : "r"(a[0]), "r"(a[1]), "r"(a[2]), "r"(a[3]), "r"(blo));
}
__device__ __forceinline__ void q_tail(float* d, uint32_t* v, uint32_t ahi, const uint32_t* dsc, const uint32_t* bar, const uint32_t* adr) {
  asm volatile(
    "{\n.reg .pred p<2>, q;\n.reg .b64 da, db;\n.reg .u32 n;\n"
    "mbarrier.test_wait.parity.shared::cta.b64 p0, [%116], %117;\n"
    "mbarrier.test_wait.parity.shared::cta.b64 p1, [%118], %119;\n"
    "ld.volatile.shared.u32 %108, [%120];\n"
    "mov.b64 da, {%110, %109};\nmov.b64 db, {%111, 8};\n"
    "wgmma.mma_async.sync.aligned.m64n144k16.f32.bf16.bf16 {%36, %37, %38, %39, %40, %41, %42, %43, %44, %45, %46, %47, %48, %49, %50, %51, %52, %53, %54, %55, %56, %57, %58, %59, %60, %61, %62, %63, %64, %65, %66, %67, %68, %69, %70, %71, %72, %73, %74, %75, %76, %77, %78, %79, %80, %81, %82, %83, %84, %85, %86, %87, %88, %89, %90, %91, %92, %93, %94, %95, %96, %97, %98, %99, %100, %101, %102, %103, %104, %105, %106, %107}, da, db, 1, 1, 1, 0, 1;\n"
    "mov.b64 da, {%112, %109};\nmov.b64 db, {%113, 8};\n"
    "wgmma.mma_async.sync.aligned.m64n72k16.f32.bf16.bf16 {%0, %1, %2, %3, %4, %5, %6, %7, %8, %9, %10, %11, %12, %13, %14, %15, %16, %17, %18, %19, %20, %21, %22, %23, %24, %25, %26, %27, %28, %29, %30, %31, %32, %33, %34, %35}, da, db, 1, 1, 1, 0, 1;\n"
    "mov.b64 da, {%114, %109};\nmov.b64 db, {%115, 8};\n"
    "wgmma.mma_async.sync.aligned.m64n144k16.f32.bf16.bf16 {%36, %37, %38, %39, %40, %41, %42, %43, %44, %45, %46, %47, %48, %49, %50, %51, %52, %53, %54, %55, %56, %57, %58, %59, %60, %61, %62, %63, %64, %65, %66, %67, %68, %69, %70, %71, %72, %73, %74, %75, %76, %77, %78, %79, %80, %81, %82, %83, %84, %85, %86, %87, %88, %89, %90, %91, %92, %93, %94, %95, %96, %97, %98, %99, %100, %101, %102, %103, %104, %105, %106, %107}, da, db, 1, 1, 1, 0, 1;\n"
    "wgmma.commit_group.sync.aligned;\n"
    "@p0 bra.uni D0;\nmov.u32 n, 0;\nW0:\nmbarrier.try_wait.parity.shared::cta.b64 q, [%116], %117;\n@q bra.uni R0;\nadd.u32 n, n, 1;\nsetp.lt.u32 q, n, 8192;\n@q bra.uni W0;\nR0:\n"
    "D0:\n"
    "@p1 bra.uni D1;\nmov.u32 n, 0;\nW1:\nmbarrier.try_wait.parity.shared::cta.b64 q, [%118], %119;\n@q bra.uni R1;\nadd.u32 n, n, 1;\nsetp.lt.u32 q, n, 8192;\n@q bra.uni W1;\nR1:\n"
    "ld.volatile.shared.u32 %108, [%120];\n"
    "D1:\n"
    "}\n"
    : "+f"(d[0]), "+f"(d[1]), "+f"(d[2]), "+f"(d[3]), "+f"(d[4]), "+f"(d[5]), "+f"(d[6]), "+f"(d[7]), "+f"(d[8]),
      "+f"(d[9]), "+f"(d[10]), "+f"(d[11]), "+f"(d[12]), "+f"(d[13]), "+f"(d[14]), "+f"(d[15]), "+f"(d[16]), "+f"(d[17]),
      "+f"(d[18]), "+f"(d[19]), "+f"(d[20]), "+f"(d[21]), "+f"(d[22]), "+f"(d[23]), "+f"(d[24]), "+f"(d[25]), "+f"(d[26]),
      "+f"(d[27]), "+f"(d[28]), "+f"(d[29]), "+f"(d[30]), "+f"(d[31]), "+f"(d[32]), "+f"(d[33]), "+f"(d[34]), "+f"(d[35]),
      "+f"(d[36]), "+f"(d[37]), "+f"(d[38]), "+f"(d[39]), "+f"(d[40]), "+f"(d[41]), "+f"(d[42]), "+f"(d[43]), "+f"(d[44]),
      "+f"(d[45]), "+f"(d[46]), "+f"(d[47]), "+f"(d[48]), "+f"(d[49]), "+f"(d[50]), "+f"(d[51]), "+f"(d[52]), "+f"(d[53]),
      "+f"(d[54]), "+f"(d[55]), "+f"(d[56]), "+f"(d[57]), "+f"(d[58]), "+f"(d[59]), "+f"(d[60]), "+f"(d[61]), "+f"(d[62]),
      "+f"(d[63]), "+f"(d[64]), "+f"(d[65]), "+f"(d[66]), "+f"(d[67]), "+f"(d[68]), "+f"(d[69]), "+f"(d[70]), "+f"(d[71]),
      "+f"(d[72]), "+f"(d[73]), "+f"(d[74]), "+f"(d[75]), "+f"(d[76]), "+f"(d[77]), "+f"(d[78]), "+f"(d[79]), "+f"(d[80]),
      "+f"(d[81]), "+f"(d[82]), "+f"(d[83]), "+f"(d[84]), "+f"(d[85]), "+f"(d[86]), "+f"(d[87]), "+f"(d[88]), "+f"(d[89]),
      "+f"(d[90]), "+f"(d[91]), "+f"(d[92]), "+f"(d[93]), "+f"(d[94]), "+f"(d[95]), "+f"(d[96]), "+f"(d[97]), "+f"(d[98]),
      "+f"(d[99]), "+f"(d[100]), "+f"(d[101]), "+f"(d[102]), "+f"(d[103]), "+f"(d[104]), "+f"(d[105]), "+f"(d[106]), "+f"(d[107]),
      "=&r"(v[0])
    : "r"(ahi), "r"(dsc[0]), "r"(dsc[1]), "r"(dsc[2]), "r"(dsc[3]), "r"(dsc[4]), "r"(dsc[5]), "r"(bar[0]), "r"(bar[1]), "r"(bar[2]), "r"(bar[3]), "r"(adr[0]) : "memory");
}
__device__ __forceinline__ void kv_tail(float* d, uint32_t* v, uint32_t ahi, const uint32_t* dsc, const uint32_t* bar, const uint32_t* adr) {
  asm volatile(
    "{\n.reg .pred p<3>, q;\n.reg .b64 da, db;\n.reg .u32 n;\n"
    "mbarrier.test_wait.parity.shared::cta.b64 p0, [%79], %80;\n"
    "mbarrier.test_wait.parity.shared::cta.b64 p1, [%81], %82;\n"
    "mbarrier.test_wait.parity.shared::cta.b64 p2, [%83], %84;\n"
    "ld.volatile.shared.u32 %72, [%85];\n"
    "ld.volatile.shared.u32 %73, [%86];\n"
    "mov.b64 da, {%75, %74};\nmov.b64 db, {%76, 8};\n"
    "wgmma.mma_async.sync.aligned.m64n144k16.f32.bf16.bf16 {%0, %1, %2, %3, %4, %5, %6, %7, %8, %9, %10, %11, %12, %13, %14, %15, %16, %17, %18, %19, %20, %21, %22, %23, %24, %25, %26, %27, %28, %29, %30, %31, %32, %33, %34, %35, %36, %37, %38, %39, %40, %41, %42, %43, %44, %45, %46, %47, %48, %49, %50, %51, %52, %53, %54, %55, %56, %57, %58, %59, %60, %61, %62, %63, %64, %65, %66, %67, %68, %69, %70, %71}, da, db, 1, 1, 1, 0, 1;\n"
    "mov.b64 da, {%77, %74};\nmov.b64 db, {%78, 8};\n"
    "wgmma.mma_async.sync.aligned.m64n144k16.f32.bf16.bf16 {%0, %1, %2, %3, %4, %5, %6, %7, %8, %9, %10, %11, %12, %13, %14, %15, %16, %17, %18, %19, %20, %21, %22, %23, %24, %25, %26, %27, %28, %29, %30, %31, %32, %33, %34, %35, %36, %37, %38, %39, %40, %41, %42, %43, %44, %45, %46, %47, %48, %49, %50, %51, %52, %53, %54, %55, %56, %57, %58, %59, %60, %61, %62, %63, %64, %65, %66, %67, %68, %69, %70, %71}, da, db, 1, 1, 1, 0, 1;\n"
    "wgmma.commit_group.sync.aligned;\n"
    "@p0 bra.uni D0;\nmov.u32 n, 0;\nW0:\nmbarrier.try_wait.parity.shared::cta.b64 q, [%79], %80;\n@q bra.uni R0;\nadd.u32 n, n, 1;\nsetp.lt.u32 q, n, 8192;\n@q bra.uni W0;\nR0:\n"
    "D0:\n"
    "@p1 bra.uni D1;\nmov.u32 n, 0;\nW1:\nmbarrier.try_wait.parity.shared::cta.b64 q, [%81], %82;\n@q bra.uni R1;\nadd.u32 n, n, 1;\nsetp.lt.u32 q, n, 8192;\n@q bra.uni W1;\nR1:\n"
    "ld.volatile.shared.u32 %72, [%85];\n"
    "D1:\n"
    "@p2 bra.uni D2;\nmov.u32 n, 0;\nW2:\nmbarrier.try_wait.parity.shared::cta.b64 q, [%83], %84;\n@q bra.uni R2;\nadd.u32 n, n, 1;\nsetp.lt.u32 q, n, 8192;\n@q bra.uni W2;\nR2:\n"
    "ld.volatile.shared.u32 %73, [%86];\n"
    "D2:\n"
    "}\n"
    : "+f"(d[36]), "+f"(d[37]), "+f"(d[38]), "+f"(d[39]), "+f"(d[40]), "+f"(d[41]), "+f"(d[42]), "+f"(d[43]), "+f"(d[44]),
      "+f"(d[45]), "+f"(d[46]), "+f"(d[47]), "+f"(d[48]), "+f"(d[49]), "+f"(d[50]), "+f"(d[51]), "+f"(d[52]), "+f"(d[53]),
      "+f"(d[54]), "+f"(d[55]), "+f"(d[56]), "+f"(d[57]), "+f"(d[58]), "+f"(d[59]), "+f"(d[60]), "+f"(d[61]), "+f"(d[62]),
      "+f"(d[63]), "+f"(d[64]), "+f"(d[65]), "+f"(d[66]), "+f"(d[67]), "+f"(d[68]), "+f"(d[69]), "+f"(d[70]), "+f"(d[71]),
      "+f"(d[72]), "+f"(d[73]), "+f"(d[74]), "+f"(d[75]), "+f"(d[76]), "+f"(d[77]), "+f"(d[78]), "+f"(d[79]), "+f"(d[80]),
      "+f"(d[81]), "+f"(d[82]), "+f"(d[83]), "+f"(d[84]), "+f"(d[85]), "+f"(d[86]), "+f"(d[87]), "+f"(d[88]), "+f"(d[89]),
      "+f"(d[90]), "+f"(d[91]), "+f"(d[92]), "+f"(d[93]), "+f"(d[94]), "+f"(d[95]), "+f"(d[96]), "+f"(d[97]), "+f"(d[98]),
      "+f"(d[99]), "+f"(d[100]), "+f"(d[101]), "+f"(d[102]), "+f"(d[103]), "+f"(d[104]), "+f"(d[105]), "+f"(d[106]), "+f"(d[107]),
      "=&r"(v[0]), "=&r"(v[1])
    : "r"(ahi), "r"(dsc[0]), "r"(dsc[1]), "r"(dsc[2]), "r"(dsc[3]), "r"(bar[0]), "r"(bar[1]), "r"(bar[2]), "r"(bar[3]), "r"(bar[4]), "r"(bar[5]), "r"(adr[0]), "r"(adr[1]) : "memory");
}
__device__ __forceinline__ void kv_last(float* d, uint32_t* v, uint32_t ahi, const uint32_t* dsc, const uint32_t* bar, const uint32_t* adr) {
  asm volatile(
    "{\n.reg .pred p<1>, q;\n.reg .b64 da, db;\n.reg .u32 n;\n"
    "mbarrier.test_wait.parity.shared::cta.b64 p0, [%81], %82;\n"
    "mov.b64 da, {%73, %72};\nmov.b64 db, {%74, 8};\n"
    "wgmma.mma_async.sync.aligned.m64n144k16.f32.bf16.bf16 {%0, %1, %2, %3, %4, %5, %6, %7, %8, %9, %10, %11, %12, %13, %14, %15, %16, %17, %18, %19, %20, %21, %22, %23, %24, %25, %26, %27, %28, %29, %30, %31, %32, %33, %34, %35, %36, %37, %38, %39, %40, %41, %42, %43, %44, %45, %46, %47, %48, %49, %50, %51, %52, %53, %54, %55, %56, %57, %58, %59, %60, %61, %62, %63, %64, %65, %66, %67, %68, %69, %70, %71}, da, db, 1, 1, 1, 0, 1;\n"
    "mov.b64 da, {%75, %72};\nmov.b64 db, {%76, 8};\n"
    "wgmma.mma_async.sync.aligned.m64n144k16.f32.bf16.bf16 {%0, %1, %2, %3, %4, %5, %6, %7, %8, %9, %10, %11, %12, %13, %14, %15, %16, %17, %18, %19, %20, %21, %22, %23, %24, %25, %26, %27, %28, %29, %30, %31, %32, %33, %34, %35, %36, %37, %38, %39, %40, %41, %42, %43, %44, %45, %46, %47, %48, %49, %50, %51, %52, %53, %54, %55, %56, %57, %58, %59, %60, %61, %62, %63, %64, %65, %66, %67, %68, %69, %70, %71}, da, db, 1, 1, 1, 0, 1;\n"
    "mov.b64 da, {%77, %72};\nmov.b64 db, {%78, 8};\n"
    "wgmma.mma_async.sync.aligned.m64n144k16.f32.bf16.bf16 {%0, %1, %2, %3, %4, %5, %6, %7, %8, %9, %10, %11, %12, %13, %14, %15, %16, %17, %18, %19, %20, %21, %22, %23, %24, %25, %26, %27, %28, %29, %30, %31, %32, %33, %34, %35, %36, %37, %38, %39, %40, %41, %42, %43, %44, %45, %46, %47, %48, %49, %50, %51, %52, %53, %54, %55, %56, %57, %58, %59, %60, %61, %62, %63, %64, %65, %66, %67, %68, %69, %70, %71}, da, db, 1, 1, 1, 0, 1;\n"
    "mov.b64 da, {%79, %72};\nmov.b64 db, {%80, 8};\n"
    "wgmma.mma_async.sync.aligned.m64n144k16.f32.bf16.bf16 {%0, %1, %2, %3, %4, %5, %6, %7, %8, %9, %10, %11, %12, %13, %14, %15, %16, %17, %18, %19, %20, %21, %22, %23, %24, %25, %26, %27, %28, %29, %30, %31, %32, %33, %34, %35, %36, %37, %38, %39, %40, %41, %42, %43, %44, %45, %46, %47, %48, %49, %50, %51, %52, %53, %54, %55, %56, %57, %58, %59, %60, %61, %62, %63, %64, %65, %66, %67, %68, %69, %70, %71}, da, db, 1, 1, 1, 0, 1;\n"
    "wgmma.commit_group.sync.aligned;\n"
    "@p0 bra.uni D0;\nmov.u32 n, 0;\nW0:\nmbarrier.try_wait.parity.shared::cta.b64 q, [%81], %82;\n@q bra.uni R0;\nadd.u32 n, n, 1;\nsetp.lt.u32 q, n, 8192;\n@q bra.uni W0;\nR0:\n"
    "D0:\n"
    "}\n"
    : "+f"(d[36]), "+f"(d[37]), "+f"(d[38]), "+f"(d[39]), "+f"(d[40]), "+f"(d[41]), "+f"(d[42]), "+f"(d[43]), "+f"(d[44]),
      "+f"(d[45]), "+f"(d[46]), "+f"(d[47]), "+f"(d[48]), "+f"(d[49]), "+f"(d[50]), "+f"(d[51]), "+f"(d[52]), "+f"(d[53]),
      "+f"(d[54]), "+f"(d[55]), "+f"(d[56]), "+f"(d[57]), "+f"(d[58]), "+f"(d[59]), "+f"(d[60]), "+f"(d[61]), "+f"(d[62]),
      "+f"(d[63]), "+f"(d[64]), "+f"(d[65]), "+f"(d[66]), "+f"(d[67]), "+f"(d[68]), "+f"(d[69]), "+f"(d[70]), "+f"(d[71]),
      "+f"(d[72]), "+f"(d[73]), "+f"(d[74]), "+f"(d[75]), "+f"(d[76]), "+f"(d[77]), "+f"(d[78]), "+f"(d[79]), "+f"(d[80]),
      "+f"(d[81]), "+f"(d[82]), "+f"(d[83]), "+f"(d[84]), "+f"(d[85]), "+f"(d[86]), "+f"(d[87]), "+f"(d[88]), "+f"(d[89]),
      "+f"(d[90]), "+f"(d[91]), "+f"(d[92]), "+f"(d[93]), "+f"(d[94]), "+f"(d[95]), "+f"(d[96]), "+f"(d[97]), "+f"(d[98]),
      "+f"(d[99]), "+f"(d[100]), "+f"(d[101]), "+f"(d[102]), "+f"(d[103]), "+f"(d[104]), "+f"(d[105]), "+f"(d[106]), "+f"(d[107])
    : "r"(ahi), "r"(dsc[0]), "r"(dsc[1]), "r"(dsc[2]), "r"(dsc[3]), "r"(dsc[4]), "r"(dsc[5]), "r"(dsc[6]), "r"(dsc[7]), "r"(bar[0]), "r"(bar[1]) : "memory");
}
__device__ __forceinline__ void o_tail(float* d, uint32_t* v, uint32_t ahi, const uint32_t* dsc, const uint32_t* bar, const uint32_t* adr) {
  asm volatile(
    "{\n.reg .pred p<1>, q;\n.reg .b64 da, db;\n.reg .u32 n;\n"
    "mbarrier.test_wait.parity.shared::cta.b64 p0, [%42], %43;\n"
    "ld.volatile.shared.u32 %36, [%44];\n"
    "mov.b64 da, {%38, %37};\nmov.b64 db, {%39, 8};\n"
    "wgmma.mma_async.sync.aligned.m64n72k16.f32.bf16.bf16 {%0, %1, %2, %3, %4, %5, %6, %7, %8, %9, %10, %11, %12, %13, %14, %15, %16, %17, %18, %19, %20, %21, %22, %23, %24, %25, %26, %27, %28, %29, %30, %31, %32, %33, %34, %35}, da, db, 1, 1, 1, 0, 1;\n"
    "mov.b64 da, {%40, %37};\nmov.b64 db, {%41, 8};\n"
    "wgmma.mma_async.sync.aligned.m64n72k16.f32.bf16.bf16 {%0, %1, %2, %3, %4, %5, %6, %7, %8, %9, %10, %11, %12, %13, %14, %15, %16, %17, %18, %19, %20, %21, %22, %23, %24, %25, %26, %27, %28, %29, %30, %31, %32, %33, %34, %35}, da, db, 1, 1, 1, 0, 1;\n"
    "wgmma.commit_group.sync.aligned;\n"
    "@p0 bra.uni D0;\nmov.u32 n, 0;\nW0:\nmbarrier.try_wait.parity.shared::cta.b64 q, [%42], %43;\n@q bra.uni R0;\nadd.u32 n, n, 1;\nsetp.lt.u32 q, n, 8192;\n@q bra.uni W0;\nR0:\n"
    "ld.volatile.shared.u32 %36, [%44];\n"
    "D0:\n"
    "}\n"
    : "+f"(d[0]), "+f"(d[1]), "+f"(d[2]), "+f"(d[3]), "+f"(d[4]), "+f"(d[5]), "+f"(d[6]), "+f"(d[7]), "+f"(d[8]),
      "+f"(d[9]), "+f"(d[10]), "+f"(d[11]), "+f"(d[12]), "+f"(d[13]), "+f"(d[14]), "+f"(d[15]), "+f"(d[16]), "+f"(d[17]),
      "+f"(d[18]), "+f"(d[19]), "+f"(d[20]), "+f"(d[21]), "+f"(d[22]), "+f"(d[23]), "+f"(d[24]), "+f"(d[25]), "+f"(d[26]),
      "+f"(d[27]), "+f"(d[28]), "+f"(d[29]), "+f"(d[30]), "+f"(d[31]), "+f"(d[32]), "+f"(d[33]), "+f"(d[34]), "+f"(d[35]),
      "=&r"(v[0])
    : "r"(ahi), "r"(dsc[0]), "r"(dsc[1]), "r"(dsc[2]), "r"(dsc[3]), "r"(bar[0]), "r"(bar[1]), "r"(adr[0]) : "memory");
}
__device__ __forceinline__ void o_tail2(float* d, uint32_t* v, uint32_t ahi, const uint32_t* dsc, const uint32_t* bar, const uint32_t* adr) {
  asm volatile(
    "{\n.reg .pred p<2>, q;\n.reg .b64 da, db;\n.reg .u32 n;\n"
    "mbarrier.test_wait.parity.shared::cta.b64 p0, [%42], %43;\n"
    "mbarrier.test_wait.parity.shared::cta.b64 p1, [%44], %45;\n"
    "ld.volatile.shared.u32 %36, [%46];\n"
    "mov.b64 da, {%38, %37};\nmov.b64 db, {%39, 8};\n"
    "wgmma.mma_async.sync.aligned.m64n72k16.f32.bf16.bf16 {%0, %1, %2, %3, %4, %5, %6, %7, %8, %9, %10, %11, %12, %13, %14, %15, %16, %17, %18, %19, %20, %21, %22, %23, %24, %25, %26, %27, %28, %29, %30, %31, %32, %33, %34, %35}, da, db, 1, 1, 1, 0, 1;\n"
    "mov.b64 da, {%40, %37};\nmov.b64 db, {%41, 8};\n"
    "wgmma.mma_async.sync.aligned.m64n72k16.f32.bf16.bf16 {%0, %1, %2, %3, %4, %5, %6, %7, %8, %9, %10, %11, %12, %13, %14, %15, %16, %17, %18, %19, %20, %21, %22, %23, %24, %25, %26, %27, %28, %29, %30, %31, %32, %33, %34, %35}, da, db, 1, 1, 1, 0, 1;\n"
    "wgmma.commit_group.sync.aligned;\n"
    "@p0 bra.uni D0;\nmov.u32 n, 0;\nW0:\nmbarrier.try_wait.parity.shared::cta.b64 q, [%42], %43;\n@q bra.uni R0;\nadd.u32 n, n, 1;\nsetp.lt.u32 q, n, 8192;\n@q bra.uni W0;\nR0:\n"
    "D0:\n"
    "@p1 bra.uni D1;\nmov.u32 n, 0;\nW1:\nmbarrier.try_wait.parity.shared::cta.b64 q, [%44], %45;\n@q bra.uni R1;\nadd.u32 n, n, 1;\nsetp.lt.u32 q, n, 8192;\n@q bra.uni W1;\nR1:\n"
    "ld.volatile.shared.u32 %36, [%46];\n"
    "D1:\n"
    "}\n"
    : "+f"(d[0]), "+f"(d[1]), "+f"(d[2]), "+f"(d[3]), "+f"(d[4]), "+f"(d[5]), "+f"(d[6]), "+f"(d[7]), "+f"(d[8]),
      "+f"(d[9]), "+f"(d[10]), "+f"(d[11]), "+f"(d[12]), "+f"(d[13]), "+f"(d[14]), "+f"(d[15]), "+f"(d[16]), "+f"(d[17]),
      "+f"(d[18]), "+f"(d[19]), "+f"(d[20]), "+f"(d[21]), "+f"(d[22]), "+f"(d[23]), "+f"(d[24]), "+f"(d[25]), "+f"(d[26]),
      "+f"(d[27]), "+f"(d[28]), "+f"(d[29]), "+f"(d[30]), "+f"(d[31]), "+f"(d[32]), "+f"(d[33]), "+f"(d[34]), "+f"(d[35]),
      "=&r"(v[0])
    : "r"(ahi), "r"(dsc[0]), "r"(dsc[1]), "r"(dsc[2]), "r"(dsc[3]), "r"(bar[0]), "r"(bar[1]), "r"(bar[2]), "r"(bar[3]), "r"(adr[0]) : "memory");
}

DEVI void mbar_init(uint32_t b, int c) { asm volatile("mbarrier.init.shared::cta.b64 [%0], %1;" ::"r"(b), "r"(c)); }
DEVI void mbar_arrive(uint32_t b) { asm volatile("mbarrier.arrive.shared::cta.b64 _, [%0];" ::"r"(b) : "memory"); }
DEVI void mbar_expect(uint32_t b, uint32_t tx) {
  asm volatile("mbarrier.arrive.expect_tx.shared::cta.b64 _, [%0], %1;" ::"r"(b), "r"(tx) : "memory");
}
DEVI void mbar_wait(uint32_t b, uint32_t ph) {
  asm volatile(
      "{\n.reg .pred p;\n.reg .u32 n;\nmov.u32 n, 0;\n"
      "LW:\nmbarrier.try_wait.parity.shared::cta.b64 p, [%0], %1;\n"
      "@p bra LD;\nadd.u32 n, n, 1;\nsetp.lt.u32 p, n, 8192;\n@p bra LW;\nLD:\n}\n" ::"r"(b), "r"(ph)
      : "memory");
}
DEVI void mbar_wait2(uint32_t a, uint32_t pa, uint32_t b, uint32_t pb) {
  asm volatile(
      "{\n.reg .pred p, q;\n.reg .u32 n;\nmov.u32 n, 0;\n"
      "LW:\nmbarrier.try_wait.parity.shared::cta.b64 p, [%0], %1;\nmbarrier.try_wait.parity.shared::cta.b64 q, [%2], %3;\n"
      "and.pred p, p, q;\n@p bra LD;\nadd.u32 n, n, 1;\nsetp.lt.u32 p, n, 8192;\n@p bra LW;\nLD:\n}\n" ::"r"(a), "r"(pa), "r"(b), "r"(pb)
      : "memory");
}
DEVI bool elect() {
  uint32_t el;
  asm volatile("{\n.reg .pred p;\nelect.sync _|p, 0xffffffff;\nselp.u32 %0,1,0,p;\n}\n" : "=r"(el));
  return el;
}
DEVI void bulk_g2s(uint32_t dst, const void* src, uint32_t bytes, uint32_t bar) {
  asm volatile("cp.async.bulk.shared::cluster.global.mbarrier::complete_tx::bytes [%0], [%1], %2, [%3];" ::"r"(dst),
               "l"(src), "r"(bytes), "r"(bar)
               : "memory");
}
DEVI void bulk_g2s_pair(uint32_t dst, const void* src, uint32_t bytes, uint32_t bar) {
  asm volatile("cp.async.bulk.shared::cluster.global.mbarrier::complete_tx::bytes.multicast::cluster [%0], [%1], %2, [%3], %4;" ::"r"(dst),
               "l"(src), "r"(bytes), "r"(bar), "h"((uint16_t)3)
               : "memory");
}
DEVI void mbar_arrive_pair(uint32_t b) {
  asm volatile("mbarrier.arrive.shared::cta.b64 _, [%0];\nmbarrier.arrive.shared::cluster.b64 _, [%1];\n" ::"r"(b), "r"(b ^ 0x1000000u) : "memory");
}
DEVI void cluster_arrive() { asm volatile("barrier.cluster.arrive.relaxed.aligned;" ::: "memory"); }
DEVI void cluster_wait() { asm volatile("barrier.cluster.wait.aligned;" ::: "memory"); }
DEVI void tma3(uint32_t dst, const CUtensorMap* m, int c0, int c1, int c2, uint32_t bar) {
  asm volatile(
      "cp.async.bulk.tensor.3d.shared::cluster.global.mbarrier::complete_tx::bytes [%0], [%1, {%3,%4,%5}], [%2];" ::"r"(dst),
      "l"(m), "r"(bar), "r"(c0), "r"(c1), "r"(c2)
      : "memory");
}
DEVI constexpr uint32_t mkdesc(uint32_t addr, uint32_t lbo) { return ((addr & 0x3FFFF) >> 4) | ((lbo >> 4) << 16); }
DEVI void bar_sync(int id) { asm volatile("bar.sync %0, 128;" ::"r"(id) : "memory"); }
DEVI uint4 ld_msg(const void* p) {
  uint4 v;
  asm volatile("ld.relaxed.gpu.global.v4.u32 {%0,%1,%2,%3}, [%4];" : "=r"(v.x), "=r"(v.y), "=r"(v.z), "=r"(v.w) : "l"(p) : "memory");
  return v;
}
DEVI void st_msg(void* p, uint32_t a, uint32_t b, uint32_t c, uint32_t d) {
  asm volatile("st.relaxed.gpu.global.v4.u32 [%0], {%1,%2,%3,%4};" ::"l"(p), "r"(a), "r"(b), "r"(c), "r"(d) : "memory");
}
DEVI uint4 ld_gen(const void* p) {
  uint4 v;
  asm volatile("ld.relaxed.gpu.v4.u32 {%0,%1,%2,%3}, [%4];" : "=r"(v.x), "=r"(v.y), "=r"(v.z), "=r"(v.w) : "l"(p) : "memory");
  return v;
}
DEVI void st_gen(void* p, uint32_t a, uint32_t b, uint32_t c, uint32_t d) {
  asm volatile("st.relaxed.gpu.v4.u32 [%0], {%1,%2,%3,%4};" ::"l"(p), "r"(a), "r"(b), "r"(c), "r"(d) : "memory");
}
DEVI uint32_t ld_rlx(const void* p) {
  uint32_t v;
  asm volatile("ld.relaxed.gpu.global.u32 %0, [%1];" : "=r"(v) : "l"(p) : "memory");
  return v;
}
DEVI uint2 ld_rlx2(const void* p) {
  uint2 v;
  asm volatile("ld.relaxed.gpu.global.v2.u32 {%0,%1}, [%2];" : "=r"(v.x), "=r"(v.y) : "l"(p) : "memory");
  return v;
}
DEVI void st_rlx(void* p, uint32_t v) { asm volatile("st.relaxed.gpu.global.u32 [%0], %1;" ::"l"(p), "r"(v) : "memory"); }
#define spin_guard(n) if (++n > (1u << 16)) break
DEVI void wait_flags(const uint8_t* p, int word, uint32_t target) {
  uint32_t n = 0;
  p += 4 * word;
  _Pragma("unroll 1") while (__any_sync(0xffffffffu, (int)(ld_rlx(p) - target) < 0)) spin_guard(n);
  asm volatile("fence.acquire.gpu;" ::: "memory");
  asm volatile("fence.proxy.async.global;" ::: "memory");
}
DEVI void bulk_s2g(void* dst, uint32_t src, uint32_t bytes) {
  asm volatile("cp.async.bulk.global.shared::cta.bulk_group [%0], [%1], %2;" ::"l"(dst), "r"(src), "r"(bytes) : "memory");
}
#define ABL 0
DEVI void l2_prefetch(const void* p, uint32_t bytes) { if (!(ABL & 2)) asm volatile("cp.async.bulk.prefetch.L2.global [%0], %1;" ::"l"(p), "r"(bytes) : "memory"); }
DEVI void fence_async_smem() { asm volatile("fence.proxy.async.shared::cta;" ::: "memory"); }
DEVI void tma2(uint32_t dst, const CUtensorMap* m, int c0, int c1, uint32_t bar) {
  asm volatile("cp.async.bulk.tensor.2d.shared::cluster.global.mbarrier::complete_tx::bytes [%0], [%1, {%3,%4}], [%2];" ::"r"(dst),
               "l"(m), "r"(bar), "r"(c0), "r"(c1) : "memory");
}
DEVI void stsm4(uint32_t a, uint32_t r0, uint32_t r1, uint32_t r2, uint32_t r3) {
  asm volatile("stmatrix.sync.aligned.m8n8.x4.shared.b16 [%0], {%1,%2,%3,%4};" ::"r"(a), "r"(r0), "r"(r1), "r"(r2), "r"(r3) : "memory");
}
DEVI void stsm2(uint32_t a, uint32_t r0, uint32_t r1) {
  asm volatile("stmatrix.sync.aligned.m8n8.x2.shared.b16 [%0], {%1,%2};" ::"r"(a), "r"(r0), "r"(r1) : "memory");
}
DEVI uint32_t mbar_test(uint32_t b, uint32_t ph) {
  uint32_t ok;
  asm volatile("{\n.reg .pred p;\nmbarrier.test_wait.parity.shared::cta.b64 p, [%1], %2;\nselp.u32 %0,1,0,p;\n}\n"
               : "=r"(ok) : "r"(b), "r"(ph) : "memory");
  return ok;
}
DEVI void st_rlx2(void* p, uint32_t a, uint32_t b) {
  asm volatile("{\n.reg .b64 v;\nmov.b64 v, {%1,%2};\nst.relaxed.gpu.global.b64 [%0], v;\n}\n" ::"l"(p), "r"(a), "r"(b) : "memory");
}
DEVI float selp(int c, float a, float b) {
  float y;
  asm("{\n.reg .pred p;\nsetp.ne.s32 p, %3, 0;\nselp.f32 %0, %1, %2, p;\n}\n" : "=f"(y) : "f"(a), "f"(b), "r"(c));
  return y;
}
DEVI float ex2(float x) { float y; asm("ex2.approx.ftz.f32 %0, %1;" : "=f"(y) : "f"(x)); return y; }
DEVI float rcp(float x) { float y; asm("rcp.approx.ftz.f32 %0, %1;" : "=f"(y) : "f"(x)); return y; }
DEVI float sqrt_a(float x) { float y; asm("sqrt.approx.ftz.f32 %0, %1;" : "=f"(y) : "f"(x)); return y; }
DEVI void ldsm4t(uint32_t* r, uint32_t a) {
  asm volatile("ldmatrix.sync.aligned.m8n8.x4.trans.shared.b16 {%0,%1,%2,%3}, [%4];"
               : "=r"(r[0]), "=r"(r[1]), "=r"(r[2]), "=r"(r[3]) : "r"(a) : "memory");
}
DEVI void ldsm4(uint32_t* r, uint32_t a) {
  asm volatile("ldmatrix.sync.aligned.m8n8.x4.shared.b16 {%0,%1,%2,%3}, [%4];"
               : "=r"(r[0]), "=r"(r[1]), "=r"(r[2]), "=r"(r[3]) : "r"(a) : "memory");
}
DEVI uint32_t lds16(uint32_t a) {
  uint32_t v;
  asm volatile("ld.shared.u16 %0, [%1];" : "=r"(v) : "r"(a) : "memory");
  return v;
}
DEVI void sts16(uint32_t a, uint32_t x) { asm volatile("st.shared.u16 [%0], %1;" ::"r"(a), "r"(x) : "memory"); }
DEVI uint4 ldg128(const void* p) {
  uint4 v;
  asm volatile("ld.global.nc.v4.u32 {%0,%1,%2,%3}, [%4];" : "=r"(v.x), "=r"(v.y), "=r"(v.z), "=r"(v.w) : "l"(p));
  return v;
}
DEVI uint2 ldg64(const void* p) {
  uint2 v;
  asm volatile("ld.global.nc.v2.u32 {%0,%1}, [%2];" : "=r"(v.x), "=r"(v.y) : "l"(p));
  return v;
}
DEVI uint32_t ldg32(const void* p) {
  uint32_t v;
  asm volatile("ld.global.nc.u32 %0, [%1];" : "=r"(v) : "l"(p));
  return v;
}
DEVI uint4 ldcg128(const void* p) {
  uint4 v;
  asm volatile("ld.global.cg.v4.u32 {%0,%1,%2,%3}, [%4];" : "=r"(v.x), "=r"(v.y), "=r"(v.z), "=r"(v.w) : "l"(p) : "memory");
  return v;
}
DEVI uint2 ldcg64(const void* p) {
  uint2 v;
  asm volatile("ld.global.cg.v2.u32 {%0,%1}, [%2];" : "=r"(v.x), "=r"(v.y) : "l"(p) : "memory");
  return v;
}
DEVI uint32_t ldcg32(const void* p) {
  uint32_t v;
  asm volatile("ld.global.cg.u32 %0, [%1];" : "=r"(v) : "l"(p) : "memory");
  return v;
}
DEVI void stg128(void* p, uint32_t a, uint32_t b, uint32_t c, uint32_t d) {
  asm volatile("st.global.v4.u32 [%0], {%1,%2,%3,%4};" ::"l"(p), "r"(a), "r"(b), "r"(c), "r"(d) : "memory");
}
DEVI void stg32(void* p, uint32_t a) { asm volatile("st.global.u32 [%0], %1;" ::"l"(p), "r"(a) : "memory"); }
DEVI uint4 lds128(uint32_t a) {
  uint4 v;
  asm volatile("ld.shared.v4.u32 {%0,%1,%2,%3}, [%4];" : "=r"(v.x), "=r"(v.y), "=r"(v.z), "=r"(v.w) : "r"(a) : "memory");
  return v;
}
DEVI uint2 lds64(uint32_t a) {
  uint2 v;
  asm volatile("ld.shared.v2.u32 {%0,%1}, [%2];" : "=r"(v.x), "=r"(v.y) : "r"(a) : "memory");
  return v;
}
DEVI uint32_t lds32(uint32_t a) {
  uint32_t v;
  asm volatile("ld.shared.u32 %0, [%1];" : "=r"(v) : "r"(a) : "memory");
  return v;
}
DEVI void lds64f_if(bool p, float& a, float& b, uint32_t addr) {
  asm volatile("{\n.reg .pred p;\nsetp.ne.u32 p, %3, 0;\n@p ld.shared.v2.f32 {%0,%1}, [%2];\n}\n"
               : "+f"(a), "+f"(b) : "r"(addr), "r"((uint32_t)p) : "memory");
}
DEVI float ldsf(uint32_t a) { return __uint_as_float(lds32(a)); }
DEVI void sts128(uint32_t a, uint32_t x, uint32_t y, uint32_t z, uint32_t w) {
  asm volatile("st.shared.v4.u32 [%0], {%1,%2,%3,%4};" ::"r"(a), "r"(x), "r"(y), "r"(z), "r"(w) : "memory");
}
DEVI void sts64(uint32_t a, uint32_t x, uint32_t y) { asm volatile("st.shared.v2.u32 [%0], {%1,%2};" ::"r"(a), "r"(x), "r"(y) : "memory"); }
DEVI void sts32(uint32_t a, uint32_t x) { asm volatile("st.shared.u32 [%0], %1;" ::"r"(a), "r"(x) : "memory"); }
DEVI void stsf(uint32_t a, float x) { sts32(a, __float_as_uint(x)); }
DEVI uint32_t packbf(float lo, float hi) {
  uint32_t r;
  asm("cvt.rn.bf16x2.f32 %0, %1, %2;" : "=r"(r) : "f"(hi), "f"(lo));
  return r;
}
DEVI uint32_t nz(uint32_t w) { uint32_t y; asm("max.u32 %0, %1, 1;" : "=r"(y) : "r"(w)); return y; }
DEVI float blo(uint32_t w) { return __uint_as_float(w << 16); }
DEVI float bhi(uint32_t w) { return __uint_as_float(w & 0xffff0000u); }
DEVI float rbf(float x) { return __uint_as_float(packbf(0.f, x)); }
DEVI float shx(float v, int m) { return __shfl_xor_sync(0xffffffffu, v, m); }
DEVI float quad_sum(float v) { v += shx(v, 1); v += shx(v, 2); return v; }
DEVI uint32_t movm(uint32_t a) {
  uint32_t d;
  asm volatile("movmatrix.sync.aligned.m8n8.trans.b16 %0, %1;" : "=r"(d) : "r"(a));
  return d;
}
DEVI void mma16(float* d, uint32_t a0, uint32_t a1, uint32_t a2, uint32_t a3, uint32_t b0, uint32_t b1) {
  asm("mma.sync.aligned.m16n8k16.row.col.f32.bf16.bf16.f32 {%0,%1,%2,%3},{%4,%5,%6,%7},{%8,%9},{%0,%1,%2,%3};"
      : "+f"(d[0]), "+f"(d[1]), "+f"(d[2]), "+f"(d[3])
      : "r"(a0), "r"(a1), "r"(a2), "r"(a3), "r"(b0), "r"(b1));
}
DEVI void mma8z(float* d, uint32_t a0, uint32_t a1, uint32_t b0) {
  asm("mma.sync.aligned.m16n8k8.row.col.f32.bf16.bf16.f32 {%0,%1,%2,%3},{%4,%5},{%6},{%7,%7,%7,%7};"
      : "=f"(d[0]), "=f"(d[1]), "=f"(d[2]), "=f"(d[3])
      : "r"(a0), "r"(a1), "r"(b0), "f"(0.f));
}
DEVI void mma8(float* d, uint32_t a0, uint32_t a1, uint32_t b0) {
  asm("mma.sync.aligned.m16n8k8.row.col.f32.bf16.bf16.f32 {%0,%1,%2,%3},{%4,%5},{%6},{%0,%1,%2,%3};"
      : "+f"(d[0]), "+f"(d[1]), "+f"(d[2]), "+f"(d[3])
      : "r"(a0), "r"(a1), "r"(b0));
}
DEVI void mma16z(float* d, uint32_t a0, uint32_t a1, uint32_t a2, uint32_t a3, uint32_t b0, uint32_t b1) {
  asm("mma.sync.aligned.m16n8k16.row.col.f32.bf16.bf16.f32 {%0,%1,%2,%3},{%4,%5,%6,%7},{%8,%9},{%10,%10,%10,%10};"
      : "=f"(d[0]), "=f"(d[1]), "=f"(d[2]), "=f"(d[3])
      : "r"(a0), "r"(a1), "r"(a2), "r"(a3), "r"(b0), "r"(b1), "f"(0.f));
}
DEVI void mma16a(float* d, const uint32_t* a, uint32_t b0, uint32_t b1) { mma16(d, a[0], a[1], a[2], a[3], b0, b1); }
DEVI float ln_sd(float var) { return rbf(sqrt_a(rbf(rbf(var) + kEps))); }
DEVI int fkey(float f) { int i = __float_as_int(f); return i ^ ((i >> 31) & 0x7fffffff); }
DEVI float sigmoidf(float x) { return rcp(1.f + ex2(-1.4426950408889634f * x)); }

DEVI uint32_t probe_stage(uint32_t pa) { return lds32(pa); }
DEVI void check_stage(uint32_t pv, uint32_t fa, const uint8_t* src) {
  if (__any_sync(0xffffffffu, pv == 0)) {
    uint32_t n = 0, tid;
    asm volatile("mov.u32 %0, %%tid.x;" : "=r"(tid));
    const uint32_t fo = (tid & 96) * 8 + (tid & 16) * 64 + (tid & 15) * 16;
    fa += fo; src += fo;
#pragma unroll 1
    for (uint32_t o = 0; o < 8192;) {
      const uint4 v = ld_msg(src + o);
      sts128(fa + o, v.x, v.y, v.z, v.w);
      if (!__any_sync(0xffffffffu, min(min(v.x, v.y), min(v.z, v.w)) == 0) || ++n > (1u << 16)) o += 2048;
    }
    fence_async_smem();
    __syncwarp();
  }
}

struct Params {
  const uint8_t *x, *wqkv, *wo, *wr, *wg, *wu, *wd;
  uint8_t* out;
  Scratch* g;
};

struct Maps { CUtensorMap wq, x, wo, xr, wg, wu, out; };
#define QPRE 2
#define FDEPTH 2
#define PFSTART 700
#define PFPRE 0
#define PFPER 3
#define PFNS 200
#define XSTART 100
#define XSTEP 300
#define PKSTEP 350
#define WPOLL 300
#define CSROUND 0
#define XLROUND 0
#define CLNS 20
#define FSTART 4000
#define XLSTART 3000
#define WGAP0 0
#define XGAP 150
#define OGAP 100
#define WDGAP 10
#define WR0 5
#define WR1 3
#define WR2 6
#define WEARLY 1

__global__ void __cluster_dims__(2, 1, 1) __launch_bounds__(512, 1) fused_kernel(const Params p, const __grid_constant__ Maps tm) {
  extern __shared__ __align__(1024) uint8_t smem_raw[];
  constexpr uint32_t sbd = 1024;
  int cta;
  uint32_t rank;
  {
    asm volatile("mov.u32 %0, %%cluster_ctarank;" : "=r"(rank));
    const int c = blockIdx.x >> 1, t = c - 4, u = c - 36, uq = (u * 37) >> 8;
    const int gpc = c < 4 ? 0 : c < 36 ? t & 7 : 1 + u - 7 * uq, idx = c < 4 ? 4 + c : c < 36 ? t >> 3 : 4 + uq;
    cta = __shfl_sync(0xffffffffu, (2 * gpc + (int)rank) * 8 + idx, 0);
  }
  const uint32_t sb = sbd | (rank << 24);
  if ((uint32_t)__cvta_generic_to_shared(smem_raw) != sb) return;
  if (threadIdx.x < 27) asm volatile("prefetch.global.L2 [%0];" ::"l"(p.wqkv + blockIdx.x * 3456 + threadIdx.x * 128));
  const int m = cta >> 3, r = cta & 7;
  const int warp = __shfl_sync(0xffffffffu, (int)(threadIdx.x >> 5), 0);
  const int lane = threadIdx.x & 31;
  uint8_t* const gb = reinterpret_cast<uint8_t*>(p.g);
  auto pack = [&]() -> uint32_t {
    const uint32_t t0 = clock();
    const uint32_t tp = sb + SM_WD + warp * 2304, bar = sb + SM_PART + 8 * warp;
    uint8_t* flag = GA(flagP, (12 * r + warp) * 128 + 4 * m);
    if (warp > 1) {
      asm volatile("bar.sync 4, 512;" ::: "memory");
      cluster_arrive();
      while ((uint32_t)clock() - t0 < (warp - 1) * PKSTEP) {}
    }
    if (elect()) {
      mbar_init(bar, 1);
      asm volatile("fence.mbarrier_init.release.cluster;" ::: "memory");
      mbar_expect(bar, 2304);
      if (warp < 9) tma3(tp, &tm.wq, 72 * r, 64 * warp + 8 * (m >> 1), m & 1, bar);
      else tma2(tp, &tm.wo, 72 * r, 192 * (warp - 9) + 24 * (m >> 1) + 8 * (m & 1), bar);
    }
    __syncwarp();
    if (lane == 0) st_rlx(flag, 0);
    if (warp <= 1) { asm volatile("bar.sync 4, 512;" ::: "memory"); cluster_arrive(); }
    mbar_wait(sb + B_EP, 0);
    const uint32_t epoch = lds32(sb + SM_EP);
    uint8_t* dst = GC(wpack, (r * 12 + warp) * WSTAGE + (27 * (m >> 1) + 14 * (m & 1)) * 128 + lane * 16);
    mbar_wait(bar, 0);
#pragma unroll
    for (int i = 0; i < 4; i++) {
      const int u = 4 * i + (lane >> 3) + 5 * (m & 1);
      const uint4 x = lds128(tp + (lane & 7) * 144 + u * 16 + (u >= 9 ? 1008 : 0));
      if (u < 14 + 4 * (m & 1)) stg128(dst + 512 * i, nz(x.x), nz(x.y), nz(x.z), nz(x.w));
    }
    if (lane == 0) st_rlx(flag, epoch);
    fence_async_smem();
    __syncwarp();
    if (elect()) asm volatile("mbarrier.inval.shared::cta.b64 [%0];" ::"r"(bar) : "memory");
    cluster_wait();
    return epoch;
  };

  if (warp >= 12) {
    asm volatile("setmaxnreg.dec.sync.aligned.u32 24;");
    uint32_t e0 = 0;
    if (elect()) {
#pragma unroll
      for (int i = 0; i < NBAR; i++)
        if (warp - 12 == (i * 4) / NBAR)
          mbar_init(sb + SM_BAR + 8 * i, i < 4 ? 1 : i < 8 ? 16 : i < 16 ? 2 : i < NBAR4 ? 4 : 1);
      asm volatile("fence.mbarrier_init.release.cluster;" ::: "memory");
    }
    __syncwarp();
    if (warp == 15) asm volatile("bar.arrive 4, 512;" ::: "memory");
    else asm volatile("bar.sync 4, 512;" ::: "memory");
    cluster_arrive();
    if (warp == 15) e0 = ld_rlx(GA(epoch, 32 * cta));
    if (warp == 12) {
      mbar_wait(sb + B_EP, 0);
      cluster_wait();
      const uint32_t epoch = lds32(sb + SM_EP);
      const uint32_t half = (m & 1) * (WSTAGE / 2);
      const uint8_t* src = GC(wpack, r * 12 * WSTAGE + half);
      __nanosleep(WPOLL);
#pragma unroll 1
      for (int g = 0; g < 24; g++) {
        const uint32_t slot = g & 3;
        if (g < 12) wait_flags(GA(flagP, (12 * r + g) * 128), lane & 15, epoch);
        if (g == 0) TRL(3, 0);
        if (g >= 4) mbar_wait(sb + B_WEMPTY + 8 * slot, ((g >> 2) - 1) & 1);
        if (elect()) {
          const uint32_t bar = sb + (g < 12 ? B_WL : B_WFULL) + 8 * slot;
          mbar_expect(bar, WSTAGE);
          bulk_g2s_pair(sb + SM_W + slot * WSTAGE + half, src + (g >= 12 ? g - 12 : g) * WSTAGE, WSTAGE / 2, bar);
        }
      }
    } else if (warp <= 14) {
      const int w = warp - 13;
      const uint32_t full = sb + B_XFULL + 32 * w, empty = sb + B_XEMPTY + 32 * w, ring = sb + SM_X + w * 4 * XSTAGE;
      mbar_wait(sb + B_EP, 0);
      cluster_wait();
      const uint32_t epoch = lds32(sb + SM_EP);
      if (lane < 4) st_rlx(GA(flagX, 128 * (2 * m + w) + 16 * r + 4 * lane), epoch * 4);
#pragma unroll 1
      for (int gemm = 0; gemm < 4; gemm++) {
        const uint8_t* src = GC(act, (gemm - 1) * ACT + (2 * m + w) * 73728);
        if (gemm & 1) {
          mbar_wait(empty, 0);
          if (elect()) {
            mbar_expect(sb + B_RES + 8 * w, 9216);
            if (gemm == 1) tma3(ring, &tm.xr, 72 * r, w, m * 64, sb + B_RES + 8 * w);
            else bulk_g2s(ring, GC(act, ACT + (2 * m + w) * 73728 + r * 9216), 9216, sb + B_RES + 8 * w);
          }
        }
        if (gemm > 0) {
          mbar_wait(gemm & 1 ? sb + B_RC + 8 * w : empty, gemm & 1 ? gemm >> 1 : 1);
          TRL(3, 11 + w * 4 + gemm);
          wait_flags(GA(flagX, 128 * (2 * m + w)), lane, epoch * 4 + gemm);
          TRL(3, 1 + w * 4 + gemm);
        }
        if (gemm & 1) {
          if (elect()) {
#pragma unroll
            for (int s = 0; s < 9; s++) {
              if (s > 0 && s < 5) { const uint32_t t1 = clock(); while ((uint32_t)clock() - t1 < OGAP) {} }
              if (s == 4) {
                mbar_wait(sb + B_RC + 8 * (w ^ 1), gemm >> 1);
                mbar_expect(sb + B_XE + 8 * w, XSTAGE);
                bulk_g2s(sb + SM_W + w * XSTAGE, src + 4 * XSTAGE, XSTAGE, sb + B_XE + 8 * w);
                continue;
              }
              const int sl = s < 4 ? s : s - 5;
              if (s >= 5) mbar_wait(empty + 8 * sl, s == 5);
              mbar_expect(full + 8 * sl, XSTAGE);
              bulk_g2s(ring + sl * XSTAGE, src + s * XSTAGE, XSTAGE, full + 8 * sl);
              mbar_arrive(full + 8 * sl);
            }
            mbar_wait(empty, 0);
            mbar_arrive(full);
            mbar_arrive(full);
          }
          __syncwarp();
          continue;
        }
        bool gate = gemm == 2;
#pragma unroll 1
        for (int s = 0; s < (gemm == 2 ? 11 : 9); s++) {
          const uint32_t slot = s & 3;
          if (gemm == 0 && s < 4) __nanosleep(s ? XSTEP : XSTART);
          if (gemm == 2 && s > 0 && s < 4) __nanosleep(XGAP);
          if (s >= 4) mbar_wait(empty + 8 * slot, s >> 3);
          const bool hold = gate && s >= 4 && mbar_test(sb + B_WANT, 0);
          if (lane == 0 && !hold && (gemm != 2 || (s & ~1) != 2)) mbar_arrive(full + 8 * (gemm == 2 && s >= 4 ? (s - 2) & 3 : slot));
          if (s < 9 && elect()) {
            mbar_expect(full + 8 * slot, XSTAGE);
            if (gemm == 0) tma3(ring + slot * XSTAGE, &tm.x, s * 64, w, m * 64, full + 8 * slot);
            else bulk_g2s(ring + slot * XSTAGE, src + s * XSTAGE, XSTAGE, full + 8 * slot);
          }
          if (hold) {
            mbar_wait(sb + B_DONE, 0);
            gate = false;
            if (lane == 0) mbar_arrive(full + 8 * ((s - 2) & 3));
          }
        }
      }
    } else {
      const uint32_t epoch = e0 + 1;
      if (lane == 0) {
        sts32(sb + SM_EP, epoch);
        mbar_arrive(sb + B_EP);
      }
      __syncwarp();
      cluster_wait();
      int pi = lane;
      auto prefetch = [&]() {
        const uint8_t* pp = pi < 648 ? ((cta & 1) ? p.wu : p.wg) + (uint32_t)(((pi / 72) * 63 + (cta >> 1)) * 9216 + pi * 128)
                                     : p.wd + (uint32_t)((cta * 324 + pi - 648) * 128);
        if (pi < 972 && !(ABL & 2)) asm volatile("prefetch.global.L2 [%0];" ::"l"(pp));
        pi += 32;
      };
      __nanosleep(PFSTART);
#pragma unroll 1
      for (int i = 0; i < PFPRE; i++) { prefetch(); __nanosleep(PFNS); }
      uint32_t ph = 0;
#pragma unroll 1
      for (int g = 0; g < 12; g++) {
        const uint32_t slot = g & 3;
#pragma unroll 1
        for (int n = 0; n < 4096; n++) {
          mbar_wait(sb + B_WL + 8 * slot, (ph >> slot) & 1);
          ph ^= 1 << slot;
          const uint32_t a = sb + SM_W + slot * WSTAGE + lane * 128 + (lane & 3) * 32 + (lane >> 2) * 4;
          uint32_t mn = lds32(a + (lane < 24 ? 6 * 4096 : 0));
#pragma unroll
          for (int u = 0; u < 6; u++) mn = min(mn, lds32(a + u * 4096));
          if (!__any_sync(0xffffffffu, mn == 0) || (ABL & 32)) break;
          fence_async_smem();
          __syncwarp();
          if (elect()) {
            mbar_expect(sb + B_WL + 8 * slot, WSTAGE);
            bulk_g2s(sb + SM_W + slot * WSTAGE, GC(wpack, (r * 12 + g) * WSTAGE), WSTAGE, sb + B_WL + 8 * slot);
          }
        }
        if (lane == 0) mbar_arrive(sb + B_WFULL + 8 * slot);
#pragma unroll 1
        for (int i = 0; i < PFPER; i++) prefetch();
      }
      TRL(3, 22);
      mbar_wait(sb + B_FD, 0);
      TRL(3, 20);
      if (elect()) {
        mbar_expect(sb + B_WD, (ABL & 64) ? 0 : 41472);
#pragma unroll 4
        for (int i = 0; i < 36; i++) {
          { const uint32_t t1 = clock(); while ((uint32_t)clock() - t1 < WDGAP) {} }
          if (!(ABL & 64)) bulk_g2s(sb + SM_WD + i * WDP, p.wd + (uint32_t)(cta * 36 + i) * 1152u, 1152, sb + B_WD);
        }
      }
      __syncwarp();
      TRL(3, 21);
      {
        const uint32_t epoch = e0, h = (lane >> 1) * 128 + (lane & 1) * 16;
        mbar_wait(sb + B_IDX, 0);
#pragma unroll 1
        for (int i = cta; i < 1296; i += 128) { stg128(GC(wpack, i * 2048 + (lane & 6) * 16 + h), 0, 0, 0, 0); __nanosleep(CLNS); }
#pragma unroll 1
        for (int i = 0; i < 5; i++) {
          stg128(GC(halo, (cta * 5 + i) * 2048 + h), 0, 0, 0, 0);
          if (i < 4 || lane < 16) stg128(GC(candrow, cta * 2304 + i * 512 + lane * 16), 0, 0, 0, 0);
          stg128(GC(act, (cta * 27 + i) * 2048 + 96 + h), 0, 0, 0, 0);
          __nanosleep(CLNS);
        }
        mbar_wait(sb + B_EPI, 1);
#pragma unroll 1
        for (int i = 5; i < 27; i++) { stg128(GC(act, (cta * 27 + i) * 2048 + 96 + h), 0, 0, 0, 0); __nanosleep(CLNS); }
      }
      TRL(3, 23);
    }
  } else if (warp >= 8) {
    asm volatile("setmaxnreg.inc.sync.aligned.u32 200;");
    const int sw = warp - 8, s = threadIdx.x - 256;
    const uint32_t t0 = clock();
    const uint32_t epoch = pack();
    TR(2, 0);
    auto ffn_round = [&](int u) {
      const uint32_t bar = sb + B_FF + 8 * (u % FDEPTH), dst = sb + SM_WD + (u % FDEPTH) * FSLOT;
      if (ABL & 4) { mbar_arrive(bar); return; }
      mbar_expect(bar, 12288);
      tma2(dst, &tm.wg, ((cta * 72) >> 5) << 4, 64 * u, bar);
      tma2(dst + FSLOT / 2, &tm.wu, ((cta * 72) >> 5) << 4, 64 * u, bar);
    };
    const int xi = 8 * r + 4 * (sw >> 1) + (lane >> 3);
    uint4 xv[9];
    uint32_t wr[9];
        {
          const uint8_t* xsrc = p.x + (uint32_t)((128 * m + 2 * xi + (sw & 1)) * 1152 + (lane & 7) * 16);
#pragma unroll
          for (int u = 0; u < 9; u++) xv[u] = ldg128(xsrc + u * 128);
#pragma unroll
          for (int u = 0; u < 9; u++) wr[u] = sw == 0 ? ldg32(p.wr + 128 * u + 4 * lane) : 0u;
        }
    {
      asm volatile("bar.sync 15, 384;" ::: "memory");
      const int u = (s >> 3) + 5 * (m & 1);
      uint4 v[9];
#pragma unroll
      for (int g = 0; g < 9; g++) v[g] = lds128(sb + SM_WD + g * 2304 + u * 16 + (u >= 9 ? 1008 : 0) + (s & 7) * 144);
      fence_async_smem();
      bar_sync(3);
      if (sw == 0) {
        while ((uint32_t)clock() - t0 < FSTART) {}
        if (elect()) {
#pragma unroll
          for (int u = 0; u < FDEPTH; u++) ffn_round(u);
        }
        __syncwarp();
      }
      float a[8] = {};
#pragma unroll
      for (int g = 0; g < 9; g++) {
        a[0] += blo(v[g].x); a[1] += bhi(v[g].x); a[2] += blo(v[g].y); a[3] += bhi(v[g].y);
        a[4] += blo(v[g].z); a[5] += bhi(v[g].z); a[6] += blo(v[g].w); a[7] += bhi(v[g].w);
      }
      const bool b4 = s & 4, b2 = s & 2;
      float b[4];
#pragma unroll
      for (int e = 0; e < 4; e++) b[e] = (b4 ? a[4 + e] : a[e]) + shx(b4 ? a[e] : a[4 + e], 4);
      float c0 = (b2 ? b[2] : b[0]) + shx(b2 ? b[0] : b[2], 2), c1 = (b2 ? b[3] : b[1]) + shx(b2 ? b[1] : b[3], 2);
      c0 += shx(c0, 1); c1 += shx(c1, 1);
      if (!(s & 1) && (s >> 3) < 14 - (m & 1))
        st_rlx2(GA(colpart, (8 * r + (m >> 1)) * 864 + 14 * (m & 1) * 32 + 4 * s), __float_as_uint(c0), (__float_as_uint(c1) & ~15u) | (epoch & 15));
      TR(2, 1);
    }
        {
          float sum = 0.f;
#pragma unroll
          for (int u = 0; u < 9; u++)
            sum += (blo(xv[u].x) + bhi(xv[u].x)) + (blo(xv[u].y) + bhi(xv[u].y)) + (blo(xv[u].z) + bhi(xv[u].z)) + (blo(xv[u].w) + bhi(xv[u].w));
          sum += shx(sum, 1); sum += shx(sum, 2); sum += shx(sum, 4);
          const float mu = sum * (1.f / kD);
          float q = 0.f;
#pragma unroll
          for (int u = 0; u < 9; u++) {
            const uint32_t ww[4] = {xv[u].x, xv[u].y, xv[u].z, xv[u].w};
#pragma unroll
            for (int e = 0; e < 4; e++) {
              const float d0 = blo(ww[e]) - mu, d1 = bhi(ww[e]) - mu;
              q = fmaf(d0, d0, q); q = fmaf(d1, d1, q);
            }
          }
          q += shx(q, 1); q += shx(q, 2); q += shx(q, 4);
          const float rho = rcp(ln_sd(q * (1.f / kD)));
          if ((lane & 7) == 0) st_msg(GA(stats0, 16 * (128 * m + 64 * (sw & 1) + xi)), __float_as_uint(rho), __float_as_uint(mu), 0, epoch);
          if (sw == 0) {
            float wsum = 0.f;
#pragma unroll
            for (int u = 0; u < 9; u++) wsum += blo(wr[u]) + bhi(wr[u]);
#pragma unroll
            for (int o = 1; o < 32; o <<= 1) wsum += shx(wsum, o);
            if (lane == 0) stsf(sb + SM_WSUM, wsum);
          }
          TR(2, 3);
        }
    uint32_t WF[9][4][4];
    {
      const int g = lane >> 2, t = lane & 3;
      const uint32_t c0 = (cta * 72) & 31, ra = 2 * (lane & 6) + (lane & 1) + 2 * ((lane >> 4) ^ ((lane >> 2) & 1));
      const uint32_t fa = sb + SM_WD + (16 * sw + ra) * 128 + ((((c0 + 8) >> 4) + ((lane >> 3) & 1)) << 4);
      const uint32_t fa0 = fa ^ ((ra & 7) << 4), fa1 = (fa + 32) ^ ((ra & 7) << 4);
      const uint32_t rl = 2 * (g & 6) + (g & 1) + 2 * (g >> 2);
      const uint32_t fl = sb + SM_WD + 16 * sw * 128 + (t >> 1) * (FSLOT / 2) + c0 + 64 * (~cta & 1) + 4 * (t & 1);
      const uint32_t fl0 = (fl + rl * 128) ^ ((rl & 7) << 4), fl1 = (fl + (rl ^ 2) * 128) ^ (((rl ^ 2) & 7) << 4);
#pragma unroll
      for (int i = 0; i < 9; i++) {
        mbar_wait(sb + B_FF + 8 * (i % FDEPTH), (i / FDEPTH) & 1);
#pragma unroll
        for (int e = 0; e < 4; e++) ldsm4t(WF[i][e], ((e & 1) ? fa1 : fa0) + (e >> 1) * (FSLOT / 2) + (i % FDEPTH) * FSLOT);
        const uint32_t v0 = lds32(fl0 + (i % FDEPTH) * FSLOT), v1 = lds32(fl1 + (i % FDEPTH) * FSLOT);
        if (i + FDEPTH < 9 || i == 8) {
          fence_async_smem();
          bar_sync(3);
          if (sw == 0 && elect()) {
            if (i < 8) ffn_round(i + FDEPTH);
            else mbar_arrive(sb + B_FD);
          }
        }
        sts64(sb + SM_LEFT + i * 1024 + s * 8, movm(v0), movm(v1));
        if (i == CSROUND) {
          TR(2, 21);
          float c0, c1;
          uint4 s0;
          uint32_t nc = 0;
          _Pragma("unroll 1") while (true) {
            s0 = ld_msg(GA(stats0, 16 * (128 * m + s)));
            uint32_t bad = s0.w != epoch;
            c0 = 0.f; c1 = 0.f;
#pragma unroll
            for (int mm = 0; mm < 8; mm++) {
              const uint2 v = ld_rlx2(GA(colpart, 8 * 864 * r + 8 * min(s, 107)) + mm * 864);
              c0 += __uint_as_float(v.x); c1 += __uint_as_float(v.y & ~15u);
              bad |= v.y ^ epoch;
            }
            if (!__any_sync(0xffffffffu, bad & 15)) break;
            spin_guard(nc);
          }
          if (s < 108) {
            const uint32_t hi = packbf(c0, c1);
            sts32(sb + SM_COLSUM + 32 * (s >> 2) + 4 * (s & 3), hi);
            sts32(sb + SM_COLSUM + 32 * (s >> 2) + 4 * (s & 3) + 16, packbf(c0 - blo(hi), c1 - bhi(hi)));
          }
          sts32(sb + SM_ROWC + 4 * s, s0.x);
          sts64(sb + SM_ROWM + 8 * s, s0.y, __float_as_uint(1.f));
          fence_async_smem();
          __syncwarp();
          if (lane == 0) mbar_arrive(sb + B_COLSUM);
          TR(2, 13);
        }
      }
      TR(2, 4);
    }
    {
      mbar_wait(sb + B_OS, 0);
      const uint32_t y = epoch * 2 - 1;
      st_msg(GA(ypart, (s >> 1) * 4096 + cta * 32 + (s & 1) * 16), y, y, y, y);
      if (s < 16) {
        st_msg(GA(ypart, (64 + (s >> 1)) * 4096 + cta * 32 + (s & 1) * 16), y, y, y, y);
        st_rlx(GA(fixmsg, 1024 * r + 64 * m + 4 * s), epoch - 1);
      }
      if (s < 64 && cta < 72) st_rlx(GA(x2msg, (s >> 3) * 2304 + 32 * cta + 4 * (s & 7)), epoch - 1);
    }
#pragma unroll 1
    for (int L = 0; L < 2; L++) {
      const uint32_t tag = epoch * 2 + L;
      int s0 = __shfl_sync(0xffffffffu, (int)threadIdx.x + L, threadIdx.x & 31) - L - 256;
#define RELANE asm volatile("" : "+r"(s0)); const int s = s0, lane = s & 31, g = lane >> 2, t = lane & 3; (void)g; (void)t
      RELANE;
      const uint8_t* crow = GC(candrow, L * 128 * 1152);
      const uint8_t* cptr = GA(cand, (8 * L + r) * 2048 + 16 * s);
      asm volatile("" : "+l"(crow), "+l"(cptr));
      mbar_wait2(sb + B_WD, 0, sb + B_EPI, L);
      uint32_t win;
      {
        uint32_t c, n = 0;
        _Pragma("unroll 1") while (true) {
          c = ld_rlx(cptr) ^ (epoch & 0x7f);
          if (!__any_sync(0xffffffffu, c & 0x7f)) break;
          spin_guard(n);
        }
        const int wm = __reduce_max_sync(0xffffffffu, (int)(c | s));
        if (lane == 0) sts32(sb + SM_RED + 4 * sw, wm);
        bar_sync(3);
        const uint4 v = lds128(sb + SM_RED);
        win = max(max((int)v.x, (int)v.y), max((int)v.z, (int)v.w));
      }
      crow += (win & 127) * 1152;
      if (s == 0) {
        if (L == 0 && WEARLY) mbar_arrive(sb + B_WANT);
        sts32(sb + SM_SEL + 4 * L, win & 0x7ff);
        mbar_arrive(sb + B_IDX + 8 * L);
      }
      TR(2, 5 + 10 * L);
      uint2 xw[9];
      {
        if (sw < 3) {
          uint4 v;
          uint32_t n = 0;
          _Pragma("unroll 1") while (true) {
            v = ld_msg(crow + 16 * min(s, 71));
            if (!__any_sync(0xffffffffu, min(min(v.x, v.y), min(v.z, v.w)) == 0)) break;
            spin_guard(n);
          }
          if (s < 72) sts128(sb + SM_PART + 16 * s, v.x, v.y, v.z, v.w);
        }
        bar_sync(3);
#pragma unroll
        for (int i = 0; i < 9; i++) xw[i] = lds64(sb + SM_PART + 128 * i + 32 * sw + 8 * t);
      }
      if (L == 0 && !WEARLY && s == 0) mbar_arrive(sb + B_WANT);
      TR(2, 6 + 10 * L);
      {
        float a[4][4] = {}, al[4] = {};
#pragma unroll
        for (int i = 0; i < 9; i++) {
          const uint2 wl = lds64(sb + SM_LEFT + s * 8 + i * 1024);
#pragma unroll
          for (int e = 0; e < 4; e++) mma16a(a[e], WF[i][e], xw[i].x, xw[i].y);
          mma8(al, wl.x, wl.y, (g & 1) ? xw[i].y : xw[i].x);
        }
        bar_sync(3);
        const uint32_t pp = sb + SM_PART + ((t >> 1) * 36 + 16 * (t & 1) + g + 4 * (cta & 1)) * 16 + 4 * sw;
        stsf(pp, selp(t & 2, selp(t & 1, a[3][0], a[2][0]), selp(t & 1, a[1][0], a[0][0])));
        stsf(pp + 128, selp(t & 2, selp(t & 1, a[3][2], a[2][2]), selp(t & 1, a[1][2], a[0][2])));
        stsf(sb + SM_PART + ((g >> 2) * 36 + 32 * (~cta & 1) + (g & 3)) * 16 + 4 * sw, al[0] + al[3]);
      }
      {
        RELANE;
        const uint32_t wa = sb + SM_WD + 288 * sw + ((lane >> 3) & 1) * 16 + ((lane & 7) + 8 * (lane >> 4)) * WDP;
        const uint32_t wb = sb + SM_WD + 288 * sw + ((lane >> 3) & 1) * 16 + (32 + (lane & 3)) * WDP;
        uint32_t f[4][4];
#pragma unroll
        for (int u = 0; u < 4; u++) ldsm4t(f[u], wa + 32 * (u & 1) + (u >> 1) * 16 * WDP);
        bar_sync(3);
        {
          float hv[2];
#pragma unroll
          for (int e = 0; e < 2; e++) {
            const uint32_t pp = sb + SM_PART + 16 * (e ? 32 + t : lane);
            const uint4 pg = lds128(pp), pu = lds128(pp + 576);
            const float gp = rbf((__uint_as_float(pg.x) + __uint_as_float(pg.y)) + (__uint_as_float(pg.z) + __uint_as_float(pg.w)));
            const float u = rbf((__uint_as_float(pu.x) + __uint_as_float(pu.y)) + (__uint_as_float(pu.z) + __uint_as_float(pu.w)));
            hv[e] = rbf(gp * sigmoidf(gp)) * u;
          }
          const uint32_t hh = packbf(hv[0], hv[1]);
          sts16(sb + SM_H + 80 * sw + 2 * lane, hh);
          sts16(sb + SM_H + 80 * sw + 64 + 2 * t, hh >> 16);
          __syncwarp();
        }
        TR(2, 7 + 10 * L);
        uint32_t hp[5];
#pragma unroll
        for (int i = 0; i < 4; i++) hp[i] = lds32(sb + SM_H + 80 * sw + 16 * i + 4 * t);
        hp[4] = lds32(sb + SM_H + 80 * sw + 64 + 4 * (t & 1));
        float Y[4] = {}, Z[4] = {}, C[4] = {};
        {
          uint32_t e0[4], e1[4], e2[4];
          const uint32_t wq = wb + 32 * (((lane >> 2) & 1) + 2 * (lane >> 4));
          ldsm4t(e0, wq); ldsm4t(e1, wq + 128); ldsm4t(e2, wb + 256);
          mma16a(Y, e0, g == (t >> 1) ? hp[4] : 0u, g == 2 + (t >> 1) ? hp[4] : 0u);
          mma16a(Z, e1, g == 4 + (t >> 1) ? hp[4] : 0u, g == 6 + (t >> 1) ? hp[4] : 0u);
          mma8(C, e2[0], e2[1], t < 2 ? hp[4] : 0u);
        }
#pragma unroll
        for (int u = 0; u < 4; u++) {
          const uint32_t wn = wa + 64 * (u + 1);
          const bool p0 = g == 2 * u, p1 = g == 2 * u + 1;
          mma16a(Y, f[0], p0 ? hp[0] : 0u, p0 ? hp[1] : 0u);
          mma16a(Z, f[1], p1 ? hp[0] : 0u, p1 ? hp[1] : 0u);
          ldsm4t(f[0], wn);
          if (u < 3) ldsm4t(f[1], wn + 32);
          mma16a(Y, f[2], p0 ? hp[2] : 0u, p0 ? hp[3] : 0u);
          mma16a(Z, f[3], p1 ? hp[2] : 0u, p1 ? hp[3] : 0u);
          ldsm4t(f[2], wn + 16 * WDP);
          if (u < 3) ldsm4t(f[3], wn + 32 + 16 * WDP);
        }
        mma16a(C, f[0], hp[0], hp[1]);
        mma16a(C, f[2], hp[2], hp[3]);
#pragma unroll
        for (int e = 0; e < 4; e++) Y[e] += Z[e];
        const uint32_t t4 = tag & 15;
        {
          uint8_t* yo = GA(ypart, (18 * sw + 4 * t) * 4096 + cta * 32 + 4 * g);
#pragma unroll
          for (int e = 0; e < 4; e++) st_rlx(yo + (2 * (e & 1) + (e >> 1)) * 4096, (__float_as_uint(Y[e]) & ~15u) | t4);
          if (t < 2) st_rlx(yo + (16 - 3 * t) * 4096, (__float_as_uint(t ? C[2] : C[0]) & ~15u) | t4);
          if (L == 0 && lane == 0) mbar_arrive(sb + B_DONE);
        }
      }
      TR(2, 8 + 10 * L);
      if (cta < 72) {
        RELANE;
        const uint32_t xn = ld_rlx(GC(candrow, (L * 128 + (win & 127)) * 1152 + 16 * cta + 2 * ((s & 6) ^ (2 * (cta & 1)))));
        const uint4 cm = ld_msg(GA(cand, (8 * L + r) * 2048 + 16 * (win & 127)));
        const uint8_t* yp = GA(ypart, cta * 4096 + s * 16);
        uint4 u0, u1;
        uint32_t n = 0;
        _Pragma("unroll 1") while (true) {
          u0 = ld_msg(yp);
          u1 = ld_msg(yp + 2048);
          const uint32_t t4 = tag & 15;
          u0.x ^= t4; u0.y ^= t4; u0.z ^= t4; u0.w ^= t4; u1.x ^= t4; u1.y ^= t4; u1.z ^= t4; u1.w ^= t4;
          if (!__any_sync(0xffffffffu, (u0.x | u0.y | u0.z | u0.w | u1.x | u1.y | u1.z | u1.w) & 15)) break;
          spin_guard(n);
        }
        const float a0 = __uint_as_float(u0.x) + __uint_as_float(u1.x), a1 = __uint_as_float(u0.y) + __uint_as_float(u1.y);
        const float a2 = __uint_as_float(u0.z) + __uint_as_float(u1.z), a3 = __uint_as_float(u0.w) + __uint_as_float(u1.w);
        const bool b4 = lane & 4, b2 = lane & 2;
        const float c0 = (b4 ? a2 : a0) + shx(b4 ? a0 : a2, 4), c1 = (b4 ? a3 : a1) + shx(b4 ? a1 : a3, 4);
        float d = (b2 ? c1 : c0) + shx(b2 ? c0 : c1, 2);
        d += shx(d, 8);
        if (!(lane & 8)) stsf(sb + SM_RED + 32 * (4 * (lane & 1) + ((lane >> 1) & 3)) + 8 * sw + 4 * (lane >> 4), d);
        bar_sync(3);
        if (s < 64) {
          const uint4 p0 = lds128(sb + SM_RED + 32 * (s & 7)), p1 = lds128(sb + SM_RED + 32 * (s & 7) + 16);
          const float y = rbf(((__uint_as_float(p0.x) + __uint_as_float(p0.y)) + (__uint_as_float(p0.z) + __uint_as_float(p0.w))) +
                              ((__uint_as_float(p1.x) + __uint_as_float(p1.y)) + (__uint_as_float(p1.z) + __uint_as_float(p1.w))));
          const uint32_t v = packbf(0.f, fmaf((s & 1) ? bhi(xn) : blo(xn), __uint_as_float(cm.z), __uint_as_float(cm.w)) + rbf(y * __uint_as_float(cm.y)));
          if (L == 0) st_rlx(GA(x2msg, (s >> 3) * 2304 + 32 * cta + 4 * (s & 7)), v | (epoch & 0xffff));
          const int tok = 128 * ((win >> 3) & 15) + 2 * (16 * (win & 3) + ((win >> 7) & 15)) + ((win >> 2) & 1);
          if (L == 1 && s < 8) *reinterpret_cast<uint16_t*>(p.out + (uint32_t)(tok * 1152 + 16 * cta + 2 * s)) = (uint16_t)(v >> 16);
        }
      }
      TR(2, 9 + 10 * L);
      if (L == 0 && m < 14) {
        RELANE;
        const int c = min(2 * m + ((s >> 3) & 1), 26);
        const uint8_t* wsrc = GC(wpack, r * 12 * WSTAGE + (s >> 4) * 3456 + c * 128 + (s & 7) * 16);
        const int k0 = 8 * (s >> 4) + (s & 7);
        uint4 wv[5];
#pragma unroll
        for (int i = 0; i < 5; i++) wv[i] = ldcg128(wsrc + i * WSTAGE);
        uint32_t xv[9];
        {
          uint32_t n = 0;
          _Pragma("unroll 1") while (true) {
            uint32_t bad = 0;
#pragma unroll
            for (int i = 0; i < 9; i++) { xv[i] = ld_rlx(GA(x2msg, r * 2304 + 4 * k0) + 256 * i); bad |= xv[i] ^ epoch; }
            if (!__any_sync(0xffffffffu, bad & 0xffff)) break;
            spin_guard(n);
          }
        }
        TR(2, 10);
        float a[8], z = 0.f;
#pragma unroll
        for (int e = 0; e < 8; e++) a[e] = 0.f;
#pragma unroll
        for (int i = 0; i < 9; i++) {
          const float xx = bhi(xv[i]);
          const uint4 w4 = wv[i % 5];
          if (i < 4) wv[i] = ldcg128(wsrc + (i + 5) * WSTAGE);
          z = fmaf(xx, (lane & 8) ? xx : 1.f, z);
          a[0] = fmaf(xx, blo(w4.x), a[0]); a[1] = fmaf(xx, bhi(w4.x), a[1]);
          a[2] = fmaf(xx, blo(w4.y), a[2]); a[3] = fmaf(xx, bhi(w4.y), a[3]);
          a[4] = fmaf(xx, blo(w4.z), a[4]); a[5] = fmaf(xx, bhi(w4.z), a[5]);
          a[6] = fmaf(xx, blo(w4.w), a[6]); a[7] = fmaf(xx, bhi(w4.w), a[7]);
        }
        const bool b4 = lane & 4, b2 = lane & 2, b1 = lane & 1;
        float b[4];
#pragma unroll
        for (int e = 0; e < 4; e++) b[e] = (b4 ? a[4 + e] : a[e]) + shx(b4 ? a[e] : a[4 + e], 4);
        z += shx(z, 4);
        const float c0 = (b2 ? b[2] : b[0]) + shx(b2 ? b[0] : b[2], 2);
        const float c1 = (b2 ? b[3] : b[1]) + shx(b2 ? b[1] : b[3], 2);
        z += shx(z, 2);
        float d = (b1 ? c1 : c0) + shx(b1 ? c0 : c1, 1);
        z += shx(z, 1);
        d += shx(d, 16);
        z += shx(z, 16);
        if (lane < 16) stsf(sb + SM_GEMV + 16 * lane + 4 * sw, d);
        if ((lane & 23) == 0) stsf(sb + SM_GEMV + 256 + 2 * lane + 4 * sw, z);
        bar_sync(3);
        if (s < 16) {
          const uint4 pd = lds128(sb + SM_GEMV + 16 * s), p1 = lds128(sb + SM_GEMV + 256), p2 = lds128(sb + SM_GEMV + 272);
          const float acc = (__uint_as_float(pd.x) + __uint_as_float(pd.y)) + (__uint_as_float(pd.z) + __uint_as_float(pd.w));
          const float m1 = ((__uint_as_float(p1.x) + __uint_as_float(p1.y)) + (__uint_as_float(p1.z) + __uint_as_float(p1.w))) * (1.f / kD);
          const float m2 = ((__uint_as_float(p2.x) + __uint_as_float(p2.y)) + (__uint_as_float(p2.z) + __uint_as_float(p2.w))) * (1.f / kD);
          const float cs = blo(lds16(sb + SM_COLSUM + 32 * c + 2 * (s & 7))) + blo(lds16(sb + SM_COLSUM + 32 * c + 2 * (s & 7) + 16));
          const float v = (acc - m1 * cs) * rcp(ln_sd(fmaxf(m2 - m1 * m1, 0.f)));
          st_rlx(GA(fixmsg, 1024 * r + 64 * m + 4 * s), __float_as_uint(rbf(v)) | (epoch & 0xffff));
        }
        TR(2, 11);
      }
      {
        if (L == 0 && (int)((win >> 3) & 15) == m) {
          RELANE;
          if (s < 72) {
            const uint8_t* fp = s < 54 ? GA(fixmsg, 1024 * r + 16 * s) : GA(x2msg, r * (2304 + 288) + 16 * (s - 54));
            uint4 v;
            uint32_t n = 0;
            _Pragma("unroll 1") while (true) {
              v = ld_msg(fp);
              if ((((v.x ^ epoch) | (v.y ^ epoch) | (v.z ^ epoch) | (v.w ^ epoch)) & 0xffff) == 0) break;
              spin_guard(n);
            }
            sts128(sb + SM_FIXQ + 16 * s, v.x & 0xffff0000u, v.y & 0xffff0000u, v.z & 0xffff0000u, v.w & 0xffff0000u);
          }
          __syncwarp();
          if (lane == 0) mbar_arrive(sb + B_FIX);
          TR(2, 12);
        }
      }
    }
    if (s == 0) st_rlx(GA(epoch, 32 * cta), epoch);
  } else {
    asm volatile("setmaxnreg.inc.sync.aligned.u32 144;");
    const int w = warp >> 2, j = warp & 3;
    const uint32_t xfull = sb + B_XFULL + 32 * w, xempty = sb + B_XEMPTY + 32 * w, xring = sb + SM_X + w * 4 * XSTAGE;
    if (threadIdx.x >= 128 && threadIdx.x < 188) { sts128(sb + SM_COLSUM + 16 * (threadIdx.x - 128), 0, 0, 0, 0); fence_async_smem(); }
    {
      const uint32_t epoch = pack();
      asm volatile("bar.arrive 15, 384;" ::: "memory");
      TRW(24);
      if (!(ABL & 8)) {
        if (lane < 16) st_msg(GA(statsP, (2 * m + w) * 8192 + r * 1024 + (16 * j + lane) * 16), 0, 0, 0, 0);
        if (lane < 2) st_msg(GA(cand, (8 * lane + r) * 2048 + 16 * (8 * m + warp)), ~epoch, 0, 0, 0);
        __syncwarp();
      }
      TRW(11);
    }
    const uint32_t mw = 2 * m + w, cid = 8 * m + warp;
    const uint32_t rowc = sb + SM_ROWC + 64 * warp, rowm = sb + SM_ROWM + 128 * warp;
#pragma unroll 1
    for (int L = 0; L < 2; L++) {
      int ln0 = __shfl_sync(0xffffffffu, lane + L, lane) - L;
#define RELANE2 asm volatile("" : "+r"(ln0)); const int ln = ln0, g = ln >> 2, t = ln & 3; \
      const uint32_t pa = xring + j * 256 + (ln & 7) * 1028 + ((ln >> 3) & 1) * 128 + 96; (void)pa
      uint32_t P[27][2], H[20];
      const uint8_t* hl;
      auto halo = [&]() {
#pragma unroll
        for (int u = 0; u < 5; u++) {
          const uint4 v = ld_gen(hl + u * 512);
          H[4 * u] = v.x; H[4 * u + 1] = v.y; H[4 * u + 2] = v.z; H[4 * u + 3] = v.w;
        }
      };
      {
        RELANE2;
        const uint32_t epoch = __shfl_sync(0xffffffffu, lds32(sb + SM_EP), 0);
        int selrow = -1;
        bool tgtwg = false;
        float d[108];
        uint32_t am[4];
        auto split_mean = [&](float m0, float m1) {
          const uint32_t h0 = packbf(m0, m0), h1 = packbf(m1, m1);
          const float l0 = m0 - bhi(h0), l1 = m1 - bhi(h1);
          am[0] = t ? 0u : h0; am[1] = t ? 0u : h1; am[2] = t ? 0u : packbf(l0, l0); am[3] = t ? 0u : packbf(l1, l1);
        };
        const uint32_t cdesc = mkdesc(sbd + SM_COLSUM, 0);
        am[0] = am[1] = am[2] = am[3] = 0;
        if (L == 1) split_mean(ldsf(rowm + 8 * g), ldsf(rowm + 8 * g + 64));
        asm volatile("wgmma.fence.sync.aligned;" ::: "memory");
        wgmma_n144_set(d + 36, am, cdesc + 18);
        wgmma_n72_set(d, am, cdesc);
        asm volatile("wgmma.commit_group.sync.aligned;" ::: "memory");
        const uint32_t adesc = mkdesc(sbd + SM_X + w * 4 * XSTAGE, 1024), ahi = L == 0 ? 0x40000040u : 8u, astep = L == 0 ? 2 : 128;
        const uint32_t bdesc = mkdesc(sbd + SM_W, 3456);
        const uint8_t* xsrc = GC(act, ACT + mw * 73728);
        mbar_wait2(sb + B_WFULL, L, xfull, 0);
        if (L == 1) check_stage(probe_stage(pa), xring, xsrc);
        TRW(0 + 12 * L);
#pragma unroll 1
        for (int s = 0; s < 7; s++) {
          TRQ(s + 9 * L);
          const uint32_t da = adesc + (s & 3) * (XSTAGE >> 4), db = bdesc + (s & 3) * (WSTAGE >> 4);
          const uint32_t nx = (s + 1) & 3, px = ((s + 1) >> 2) & 1;
          asm volatile("wgmma.fence.sync.aligned;" ::: "memory");
          wgmma_n72(d, da, ahi, db);
          wgmma_n144(d + 36, da, ahi, db + (1152 >> 4));
          wgmma_n72(d, da + astep, ahi, db + (6912 >> 4));
          asm volatile("wgmma.commit_group.sync.aligned;" ::: "memory");
          asm volatile("wgmma.wait_group.sync.aligned 1;" ::: "memory");
          if (s > 0 && ln == 0) {
            mbar_arrive_pair(sb + B_WEMPTY + 8 * ((s - 1) & 3));
            mbar_arrive(xempty + 8 * ((s - 1) & 3));
          }
          wgmma_n144(d + 36, da + astep, ahi, db + ((6912 + 1152) >> 4));
          wgmma_n72(d, da + 2 * astep, ahi, db + 2 * (6912 >> 4));
          uint32_t pv;
          const uint32_t dsc[6] = {da + 2 * astep, db + ((2 * 6912 + 1152) >> 4), da + 3 * astep, db + 3 * (6912 >> 4),
                                   da + 3 * astep, db + ((3 * 6912 + 1152) >> 4)};
          const uint32_t bar[4] = {sb + B_WFULL + 8 * nx, px ^ L, xfull + 8 * nx, px}, adr = pa + nx * XSTAGE;
          q_tail(d, &pv, ahi, dsc, bar, &adr);
          if (L == 1) check_stage(pv, xring + nx * XSTAGE, xsrc + (s + 1) * XSTAGE);
          if (s == 1 && j == 3) {
            uint8_t* hp = GC(halo, (4 * cta + 2 * L + w) * 2560 + ln * 16);
#pragma unroll
            for (int u = 0; u < 5; u++) st_msg(hp + u * 512, 0, 0, 0, 0);
          }
        }
        TRQ(7 + 9 * L);
        const uint32_t da7 = adesc + 3 * (XSTAGE >> 4), db7 = bdesc + 3 * (WSTAGE >> 4);
        asm volatile("wgmma.fence.sync.aligned;" ::: "memory");
        wgmma_n144(d + 36, da7, ahi, db7 + (1152 >> 4));
        wgmma_n144(d + 36, da7 + astep, ahi, db7 + ((6912 + 1152) >> 4));
        asm volatile("wgmma.commit_group.sync.aligned;" ::: "memory");
        asm volatile("wgmma.wait_group.sync.aligned 1;" ::: "memory");
        if (ln == 0) { mbar_arrive_pair(sb + B_WEMPTY + 16); mbar_arrive(xempty + 16); }
        {
          uint32_t v[2];
          const uint32_t dsc[4] = {da7 + 2 * astep, db7 + ((2 * 6912 + 1152) >> 4), da7 + 3 * astep, db7 + ((3 * 6912 + 1152) >> 4)};
          const uint32_t bar[6] = {sb + B_WFULL, (uint32_t)L, xfull, 0, sb + (L ? B_IDX : B_COLSUM), 0}, adr[2] = {pa, sb + SM_SEL + (ln >> 5)};
          kv_tail(d, v, ahi, dsc, bar, adr);
          if (L == 1) {
            if ((v[1] & 127) == cid) selrow = v[1] >> 7;
            tgtwg = ((v[1] & 127) >> 2) == (cid >> 2);
            check_stage(v[0], xring, xsrc + 8 * XSTAGE);
          }
        }
        TRQ(8 + 9 * L);
        const float m0 = ldsf(rowm + 8 * g), m1 = ldsf(rowm + 8 * g + 64);
        {
          uint32_t dsc[8];
#pragma unroll
          for (int kk = 0; kk < 4; kk++) { dsc[2 * kk] = adesc + kk * astep; dsc[2 * kk + 1] = bdesc + ((kk * 6912 + 1152) >> 4); }
          const uint32_t bar[2] = {xempty + 16, 1};
          asm volatile("wgmma.fence.sync.aligned;" ::: "memory");
          kv_last(d, nullptr, ahi, dsc, bar, nullptr);
        }
        if (L == 0) {
          split_mean(m0, m1);
          asm volatile("wgmma.fence.sync.aligned;" ::: "memory");
          wgmma_n144_add(d + 36, am, cdesc + 18);
          wgmma_n72_add(d, am, cdesc);
          asm volatile("wgmma.commit_group.sync.aligned;" ::: "memory");
        }
        auto qstep = [&](int k) {
          wgmma_n72(d, (k < 4 ? da7 : adesc) + (k & 3) * astep, ahi, (k < 4 ? db7 : bdesc) + (k & 3) * (6912 >> 4));
        };
#pragma unroll
        for (int k = 0; k < QPRE; k++) qstep(k);
        asm volatile("wgmma.commit_group.sync.aligned;" ::: "memory");
        if (tgtwg) {
          asm volatile("wgmma.fence.sync.aligned;" ::: "memory");
#pragma unroll
          for (int k = QPRE; k < 8; k++) qstep(k);
          asm volatile("wgmma.commit_group.sync.aligned;" ::: "memory");
        }
        asm volatile("wgmma.wait_group.sync.aligned 1;" ::: "memory");
#pragma unroll
        for (int i = 36; i < 108; i++) asm volatile("" : "+f"(d[i])::"memory");
        if (selrow >= 0) {
          mbar_wait(sb + B_FIX, 0);
          stsf(rowc + 4 * selrow, 1.f);
#pragma unroll
          for (int q = 18; q < 54; q++) lds64f_if(selrow == g + 8 * (q & 1), d[2 * q], d[2 * q + 1], sb + SM_FIXQ + 32 * (q >> 1) + 8 * t);
          __syncwarp();
        }
#pragma unroll
        for (int q = 26; q >= 9; q--) { P[q][1] = packbf(d[4 * q + 2], d[4 * q + 3]); P[q][0] = packbf(d[4 * q], d[4 * q + 1]); }
#pragma unroll
        for (int q = 26; q >= 18; q--) P[q][1] = movm(P[q][1]);
        const uint2 ck1 = lds64(rowc + 32 + 8 * t);
        uint8_t* ha = (j < 3 ? smem_raw + (SM_X + (4 * w + 2) * XSTAGE + j * 2560) : GC(halo, (4 * cta + 2 * L + w) * 2560)) + ln * 16;
        P[9][1] = nz(P[9][1]); P[13][1] = nz(P[13][1]); P[17][1] = nz(P[17][1]);
        st_gen(ha, P[9][1], P[10][1], P[11][1], P[12][1]);
        st_gen(ha + 512, P[13][1], P[14][1], P[15][1], P[16][1]);
        st_gen(ha + 2048, nz(ck1.y), P[24][1], P[25][1], P[26][1]);
        st_gen(ha + 1536, nz(ck1.x), P[21][1], P[22][1], P[23][1]);
        st_gen(ha + 1024, P[17][1], P[18][1], P[19][1], P[20][1]);
#pragma unroll
        for (int q = 9; q < 27; q++) asm volatile("" : "+r"(P[q][0]));
        if (j < 3) asm volatile("bar.arrive %0, 64;" ::"r"(5 + warp) : "memory");
        mbar_wait(sb + B_EP, 0);
#pragma unroll
        for (int q = 26; q >= 18; q--) P[q][0] = movm(P[q][0]);
        if (!tgtwg)
        {
          asm volatile("wgmma.fence.sync.aligned;" ::: "memory");
#pragma unroll
          for (int k = QPRE; k < 8; k++) qstep(k);
          asm volatile("wgmma.commit_group.sync.aligned;" ::: "memory");
        }
        hl = (j > 0 || m == 0 ? smem_raw + (SM_X + (4 * w + 2) * XSTAGE + max(j - 1, 0) * 2560)
                              : GC(halo, (4 * (cta - 8) + 2 * L + w) * 2560)) + ln * 16;
        if (j > 0) asm volatile("bar.sync %0, 64;" ::"r"(4 + warp) : "memory");
        asm volatile("wgmma.wait_group.sync.aligned 0;" ::: "memory");
#pragma unroll
        for (int i = 0; i < 36; i++) asm volatile("" : "+f"(d[i])::"memory");
        TRW(1 + 12 * L);
        if (selrow >= 0) {
#pragma unroll
          for (int q = 0; q < 18; q++) lds64f_if(selrow == g + 8 * (q & 1), d[2 * q], d[2 * q + 1], sb + SM_FIXQ + 32 * (q >> 1) + 8 * t);
        }
#pragma unroll
        for (int q = 0; q < 9; q++) { P[q][0] = packbf(d[4 * q], d[4 * q + 1]); P[q][1] = packbf(d[4 * q + 2], d[4 * q + 3]); }
      }
      TRW(2 + 12 * L);
      const uint32_t epoch = lds32(sb + SM_EP);
      uint8_t* fptr = GA(flagX, 128 * mw + 16 * r + 4 * j + ln0);
      {
        RELANE2;
        halo();
        if (ln == 0) { mbar_arrive(xempty + 24); mbar_arrive(xempty); }
        const bool le0 = 2 * t <= g, le1 = 2 * t + 1 <= g;
        uint32_t A0[4][2], A2[4][2];
        float s0[4][4], s1[4][4];
#pragma unroll
        for (int h = 0; h < 4; h++) {
          const int T = 2 * h;
          A0[h][0] = t >= h ? P[T][0] : 0u; A0[h][1] = t >= h ? P[T][1] : 0u;
          A2[h][0] = t <= h ? P[T + 2][0] : 0u; A2[h][1] = t <= h ? P[T + 2][1] : 0u;
          mma8z(s0[h], A2[h][0], A2[h][1], P[9 + T + 2][0]);
          mma8z(s1[h], A2[h][0], A2[h][1], P[9 + T + 2][1]);
        }
#pragma unroll
        for (int h = 0; h < 4; h++) {
          const int T = 2 * h;
          mma16(s0[h], A0[h][0], A0[h][1], P[T + 1][0], P[T + 1][1], P[9 + T][0], P[9 + T + 1][0]);
          mma16(s1[h], A0[h][0], A0[h][1], P[T + 1][0], P[T + 1][1], P[9 + T][1], P[9 + T + 1][1]);
        }
        const uint2 ck0 = lds64(rowc + 8 * t), ck1 = lds64(rowc + 32 + 8 * t);
        const float sc = 0.23570226039551584f * 1.4426950408889634f;
        const float cq0 = ldsf(rowc + 4 * g) * sc, cq1 = ldsf(rowc + 32 + 4 * g) * sc;
        uint8_t* ob = GC(act, 2 * L * ACT + mw * 73728 + r * 9216 + j * 256 + ln * 4);
        float l[2][4][2], ks[2][2], mx[2][4];
        ks[1][0] = __uint_as_float(le0 ? ck1.x : ck0.x); ks[1][1] = __uint_as_float(le1 ? ck1.y : ck0.y);
#pragma unroll
        for (int h = 0; h < 4; h++) {
          l[1][h][0] = (le0 ? s1[h][2] : s0[h][2]) * (cq1 * ks[1][0]); l[1][h][1] = (le1 ? s1[h][3] : s0[h][3]) * (cq1 * ks[1][1]);
          asm volatile("" : "+f"(l[1][h][0]), "+f"(l[1][h][1]));
        }
        asm volatile("" : "+l"(fptr), "+l"(ob));
        {
          uint32_t n = 0;
          _Pragma("unroll 1") while (__any_sync(0xffffffffu, min(min(min(H[0], H[4]), min(H[8], H[12])), H[16]) == 0)) {
            halo();
            spin_guard(n);
          }
        }
        if (ln == 0) mbar_arrive_pair(sb + B_WEMPTY + 24);
        TRW(3 + 12 * L);
        {
          float sm[4][4];
#pragma unroll
          for (int h = 0; h < 4; h++) mma8z(sm[h], A2[h][0], A2[h][1], H[2 * h + 2]);
#pragma unroll
          for (int h = 0; h < 4; h++) mma16(sm[h], A0[h][0], A0[h][1], P[2 * h + 1][0], P[2 * h + 1][1], H[2 * h], H[2 * h + 1]);
          ks[0][0] = __uint_as_float(le0 ? ck0.x : H[12]); ks[0][1] = __uint_as_float(le1 ? ck0.y : H[16]);
          const bool nohalo = (m == 0 && j == 0);
          const float b0 = (nohalo && !le0) ? -INFINITY : 0.f, b1 = (nohalo && !le1) ? -INFINITY : 0.f;
#pragma unroll
          for (int h = 0; h < 4; h++) {
            l[0][h][0] = fmaf(le0 ? s0[h][0] : sm[h][0], cq0 * ks[0][0], b0);
            l[0][h][1] = fmaf(le1 ? s0[h][1] : sm[h][1], cq0 * ks[0][1], b1);
          }
        }
#pragma unroll
        for (int i = 7; i >= 0; i--) mx[i >> 2][i & 3] = fmaxf(l[i >> 2][i & 3][0], l[i >> 2][i & 3][1]);
#pragma unroll
        for (int x = 1; x <= 2; x <<= 1) {
#pragma unroll
          for (int i = 7; i >= 0; i--) mx[i >> 2][i & 3] = fmaxf(mx[i >> 2][i & 3], shx(mx[i >> 2][i & 3], x));
        }
        const uint32_t mle = (le0 ? 0xffffu : 0u) | (le1 ? 0xffff0000u : 0u);
        uint32_t pp[2][4], pc[2][4];
#pragma unroll
        for (int i = 3; i >= 0; i--) {
          const int e = i >> 1, h = 2 * (i & 1);
          const float p0 = ex2(l[e][h][0] - mx[e][h]), p1 = ex2(l[e][h][1] - mx[e][h]);
          const float p2 = ex2(l[e][h + 1][0] - mx[e][h + 1]), p3 = ex2(l[e][h + 1][1] - mx[e][h + 1]);
          float sum[4];
          mma8z(sum, packbf(p0, p1), packbf(p2, p3), 0x3f803f80u);
          const float inv = rcp(sum[0] * sum[2]);
          const float ia = inv * sum[2], ib = inv * sum[0];
          const uint32_t u0 = packbf(p0 * ks[e][0] * ia, p1 * ks[e][1] * ia), u1 = packbf(p2 * ks[e][0] * ib, p3 * ks[e][1] * ib);
          pp[e][h] = u0 & ~mle; pc[e][h] = u0 & mle; pp[e][h + 1] = u1 & ~mle; pc[e][h + 1] = u1 & mle;
        }
#pragma unroll
        for (int e = 1; e >= 0; e--) {
#pragma unroll
          for (int q = 8; q >= 0; q--) {
            const int h = q < 4 ? 0 : q == 4 ? 1 : 2;
            float a[4];
            mma16z(a, pp[e][h], pp[e][h + 1], pc[e][h], pc[e][h + 1], e ? P[18 + q][0] : H[9 + q + q / 3], P[18 + q][e]);
            const bool second = q == 2 * h + 2 ? t > h : q > 2 * h + 2;
            st_rlx(ob + q * 1024 + e * 128, nz(packbf(second ? a[2] : a[0], second ? a[3] : a[1])));
          }
        }
        if (ln == 0) st_rlx(fptr, epoch * 4 + 1 + 2 * L);
        TRW(4 + 12 * L);
      }
      RELANE2;
      float d[36];
      uint32_t WB[9];
      {
        uint32_t R[10][2];
        const uint32_t qs = L == 0 ? 16 : 1024, ra = xring + (16 * j + (ln & 15)) * (L == 0 ? 144 : 16) + (ln >> 4) * qs;
        mbar_wait(sb + B_RES + 8 * w, L);
#pragma unroll
        for (int q = 0; q < 10; q += 2) ldsm4(&R[q][0], ra + q * qs);
        fence_async_smem();
        __syncwarp();
        if (ln == 0) mbar_arrive(sb + B_RC + 8 * w);
#pragma unroll
        for (int q = 0; q < 9; q++) WB[q] = ldg32(p.wr + (uint32_t)(r * 144 + 4 * t) + 16 * q);
#pragma unroll
        for (int h = 0; h < 2; h++) {
          const uint2 mf = lds64(rowm + 8 * g + 64 * h);
          const float f = __uint_as_float(mf.y), k = -__uint_as_float(mf.x) * f;
#pragma unroll
          for (int q = 0; q < 9; q++) { d[4 * q + 2 * h] = fmaf(blo(R[q][h]), f, k); d[4 * q + 2 * h + 1] = fmaf(bhi(R[q][h]), f, k); }
        }
        const uint32_t sel = lds32(sb + SM_SEL);
        if (L == 1 && (sel & 127) == cid) {
          const int selrow = sel >> 7;
#pragma unroll
          for (int q = 0; q < 18; q++) lds64f_if(selrow == g + 8 * (q & 1), d[2 * q], d[2 * q + 1], sb + SM_X2R + 32 * (q >> 1) + 8 * t);
        }
#pragma unroll
        for (int q = 0; q < 9; q++) WB[q] = (g & 1) ? WB[q] : 0x3f803f80u;
        __syncwarp();
      }
      uint8_t* xb = GC(act, ACT + mw * 73728 + r * 9216 + j * 256 + ln * 4);
      uint8_t* sst = GA(statsP, mw * 8192 + r * 1024 + (16 * j + g + 8 * t) * 16);
      const uint8_t* sld = GA(statsP, mw * 8192 + (ln >> 4) * 4096 + (16 * j + (ln & 15)) * 16);
      uint8_t* cptr = GA(cand, (8 * L + r) * 2048 + 16 * cid);
      uint8_t* crow = GC(candrow, (128 * L + cid) * 1152 + 144 * r + 4 * t);
      uint32_t tag = epoch * 2 + L, ktag = ((ln & 15) << 7) | (epoch & 0x7f);
      float wsum = ldsf(sb + SM_WSUM);
      float pivot = __uint_as_float(ld_rlx(GA(stats0, 16 * (16 * cid + (ln & 15)) + 4))) + (L ? ldsf(rowm + 8 * (ln & 15)) : 0.f);
      asm volatile("" : "+l"(xb), "+l"(sst), "+l"(sld), "+l"(cptr), "+l"(crow), "+r"(tag), "+r"(ktag), "+f"(wsum), "+f"(pivot));
      TRW(5 + 12 * L);
      {
        constexpr uint32_t bdesc = mkdesc(sbd + SM_W + WSTAGE, 1152);
        uint32_t adesc[3];
#pragma unroll
        for (int i = 0; i < 3; i++) adesc[i] = __shfl_sync(0xffffffffu, mkdesc(sbd + SM_X + w * 4 * XSTAGE, 1024) + (ln >> 2), i);
#pragma unroll
        for (int i = 0; i < 36; i++) asm volatile("" : "+f"(d[i])::"memory");
        const bool lead = warp == 0 && ln == 0;
        const uint8_t* osrc = GC(act, 2 * L * ACT + mw * 73728);
        mbar_wait2(sb + B_WFULL + 8, L, xfull, 1);
        check_stage(probe_stage(pa), xring, osrc);
        TRW(6 + 12 * L);
#pragma unroll
        for (int s = 0; s < 9; s++) {
          TRQ(18 + s);
          const uint32_t da = s == 4 ? adesc[1] - ((SM_X - SM_W) >> 4) - w * 3 * (XSTAGE >> 4) : adesc[s >> 2] + (s < 4 ? s : s - 5) * (XSTAGE >> 4);
          const uint32_t db = bdesc + s * (9216 >> 4);
          const int n1 = s + 1, nx = n1 < 4 ? n1 : n1 - 5;
          const uint32_t xoff = n1 == 4 ? SM_W - SM_X - w * 3 * XSTAGE : nx * XSTAGE;
          asm volatile("wgmma.fence.sync.aligned;" ::: "memory");
          wgmma_n72(d, da, 8u, db);
          wgmma_n72(d, da + 128, 8u, db + (2304 >> 4));
          asm volatile("wgmma.commit_group.sync.aligned;" ::: "memory");
          if (s > 0) {
            asm volatile("wgmma.wait_group.sync.aligned 1;" ::: "memory");
            if (ln == 0) {
              if (s != 5) mbar_arrive(xempty + 8 * (s < 5 ? s - 1 : s - 6));
              if (L == 0) {
                if (s == WR0) mbar_arrive_pair(sb + B_WEMPTY);
                if (s == WR1) mbar_arrive_pair(sb + B_WEMPTY + 8);
                if (s == WR2) mbar_arrive_pair(sb + B_WEMPTY + 16);
              }
            }
          }
          const uint32_t xbar = n1 == 4 ? sb + B_XE + 8 * w : xfull + 8 * nx, px = n1 == 4 ? L : n1 >= 6;
          if ((s == 0 || s == 8) && lead) mbar_arrive(sb + (s ? B_EPI : B_OS));
          if (s < 8) {
            uint32_t pv;
            const uint32_t dsc[4] = {da + 256, db + (4608 >> 4), da + 384, db + (6912 >> 4)};
            const uint32_t bar[4] = {sb + B_WFULL + 8 + 8 * ((s + 1) / 3), (uint32_t)L, xbar, px}, adr = pa + xoff;
            o_tail2(d, &pv, 8u, dsc, bar, &adr);
            check_stage(pv, xring + xoff, osrc + (s + 1) * XSTAGE);
          } else {
            wgmma_n72(d, da + 256, 8u, db + (4608 >> 4));
            wgmma_n72(d, da + 384, 8u, db + (6912 >> 4));
            asm volatile("wgmma.commit_group.sync.aligned;" ::: "memory");
          }
        }
        asm volatile("wgmma.wait_group.sync.aligned 0;" ::: "memory");
#pragma unroll
        for (int i = 0; i < 36; i++) asm volatile("" : "+f"(d[i])::"memory");
        mbar_wait(xfull, 1);
        if (ln == 0) { if (L == 0) mbar_arrive_pair(sb + B_WEMPTY + 24); mbar_arrive(xempty + 24); mbar_arrive(xempty); }
      }
      TRW(7 + 12 * L);
      uint32_t R[9][2];
#pragma unroll
      for (int q = 0; q < 9; q++) { R[q][0] = packbf(d[4 * q], d[4 * q + 1]); R[q][1] = packbf(d[4 * q + 2], d[4 * q + 3]); }
      {
        float sa[4], sc[4];
        mma16z(sa, R[0][0], R[0][1], R[1][0], R[1][1], WB[0], WB[1]);
        mma16z(sc, R[2][0], R[2][1], R[3][0], R[3][1], WB[2], WB[3]);
        mma16(sa, R[4][0], R[4][1], R[5][0], R[5][1], WB[4], WB[5]);
        mma16(sc, R[6][0], R[6][1], R[7][0], R[7][1], WB[6], WB[7]);
        mma8(sa, R[8][0], R[8][1], WB[8]);
        float qq[4] = {0.f, 0.f, 0.f, 0.f};
#pragma unroll
        for (int q = 0; q < 36; q++) qq[q & 3] = fmaf(d[q], d[q], qq[q & 3]);
        const float qa = qq[0] + qq[1], qc = qq[2] + qq[3];
        const bool odd = t & 1;
        float q2 = (odd ? qc : qa) + shx(odd ? qa : qc, 1);
        q2 += shx(q2, 2);
        if (t < 2)
          st_msg(sst, __float_as_uint(odd ? sa[2] + sc[2] : sa[0] + sc[0]), __float_as_uint(q2),
                 __float_as_uint(odd ? sa[3] + sc[3] : sa[1] + sc[1]), tag);
      }
      if (L == 0) {
#pragma unroll
        for (int q = 0; q < 9; q++) { st_rlx(xb + q * 1024, nz(R[q][0])); st_rlx(xb + q * 1024 + 128, nz(R[q][1])); }
        if (ln == 0) st_rlx(fptr, epoch * 4 + 2);
      }
      TRW(8 + 12 * L);
      {
        uint4 u[4];
        uint32_t n = 0;
        _Pragma("unroll 1") while (true) {
#pragma unroll
          for (int i = 0; i < 4; i++) u[i] = ld_msg(sld + 1024 * i);
          if (!__any_sync(0xffffffffu, (u[0].w ^ tag) | (u[1].w ^ tag) | (u[2].w ^ tag) | (u[3].w ^ tag))) break;
          spin_guard(n);
        }
        TRW(9 + 12 * L);
        float s1 = (__uint_as_float(u[0].x) + __uint_as_float(u[1].x)) + (__uint_as_float(u[2].x) + __uint_as_float(u[3].x));
        float s2 = (__uint_as_float(u[0].y) + __uint_as_float(u[1].y)) + (__uint_as_float(u[2].y) + __uint_as_float(u[3].y));
        float s3 = (__uint_as_float(u[0].z) + __uint_as_float(u[1].z)) + (__uint_as_float(u[2].z) + __uint_as_float(u[3].z));
        s1 += shx(s1, 16); s2 += shx(s2, 16); s3 += shx(s3, 16);
        const float mu = s1 * (1.f / kD);
        const float var = fmaxf(fmaf(s2, 1.f / kD, -mu * mu), 0.f);
        const float sd = ln_sd(var), rho = rcp(sd);
        const float rr = (s3 - mu * wsum) * rho;
        const int key = __reduce_max_sync(0xffffffffu, (int)((fkey(rr) & ~0x7ff) | ktag));
        const int best = (key >> 7) & 15;
        if (ln == best) st_msg(cptr, key, __float_as_uint(rbf(sigmoidf(rbf(rr)))), __float_as_uint(1.f + sd), __float_as_uint(L ? pivot + mu : 0.f));
        const float rb = __shfl_sync(0xffffffffu, rho, best), nb = __shfl_sync(0xffffffffu, -mu * rho, best);
        if ((best & 7) == g) {
          const bool hi = best >= 8;
#pragma unroll
          for (int q = 0; q < 9; q++)
            st_rlx(crow + (((q ^ r) & 1) * (4 - 8 * (t & 1))) + 16 * q, nz(packbf(fmaf(hi ? d[4 * q + 2] : d[4 * q], rb, nb), fmaf(hi ? d[4 * q + 3] : d[4 * q + 1], rb, nb))));
        }
        const float f = 1.f + rho, k = pivot - mu * rho;
        sts32(rowc + 4 * (ln & 15), __float_as_uint(f * rcp(ln_sd(var * f * f))));
        sts64(rowm + 8 * (ln & 15), __float_as_uint(L == 0 ? mu : k), __float_as_uint(f));
        __syncwarp();
      }
      TRW(10 + 12 * L);
      if (L == 1) {
#pragma unroll
        for (int h = 0; h < 2; h++) {
          const uint2 kf = lds64(rowm + 8 * g + 64 * h);
          const float k = __uint_as_float(kf.x), f = __uint_as_float(kf.y);
#pragma unroll
          for (int q = 0; q < 9; q++) R[q][h] = packbf(fmaf(d[4 * q + 2 * h], f, k), fmaf(d[4 * q + 2 * h + 1], f, k));
        }
        mbar_wait(xempty + 16, 1);
        const uint32_t st = xring + XSTAGE + (16 * j + (ln & 15)) * 144;
#pragma unroll
        for (int q = 0; q < 8; q += 2) stsm4(st + (ln >> 4) * 16 + q * 16, R[q][0], R[q][1], R[q + 1][0], R[q + 1][1]);
        stsm2(st + 128, R[8][0], R[8][1]);
        fence_async_smem();
        __syncwarp();
        mbar_wait(sb + B_IDX + 8, 0);
        const uint32_t sel = lds32(sb + SM_SEL + 4);
        if ((sel & 127) != cid) {
          if (elect())
            asm volatile("cp.async.bulk.tensor.3d.global.shared::cta.bulk_group [%0, {%2,%3,%4}], [%1];" ::"l"(&tm.out),
                         "r"(xring + XSTAGE + 16 * j * 144), "r"(72 * r), "r"(w), "r"(64 * m + 16 * j) : "memory");
        } else if (ln < 16 && ln != (sel >> 7)) {
          bulk_s2g(p.out + (uint32_t)((128 * m + 2 * (16 * j + ln) + w) * 1152 + r * 144), st, 144);
        }
        asm volatile("cp.async.bulk.commit_group;" ::: "memory");
        asm volatile("cp.async.bulk.wait_group.read 0;" ::: "memory");
        TRW(11 + 12 * L);
        TRDUMP(w);
      }
    }
  }
}

typedef CUresult (*EncodeFn)(CUtensorMap*, CUtensorMapDataType, cuuint32_t, void*, const cuuint64_t*, const cuuint64_t*,
                             const cuuint32_t*, const cuuint32_t*, CUtensorMapInterleave, CUtensorMapSwizzle,
                             CUtensorMapL2promotion, CUtensorMapFloatOOBfill);

}

extern "C" void kernel_launch(void* const* d_in, const int* in_sizes, int n_in, void* d_out, int out_size) {
  static EncodeFn enc = nullptr;
  static Scratch* scratch = nullptr;
  if (!enc) {
    cudaDriverEntryPointQueryResult q;
    cudaGetDriverEntryPoint("cuTensorMapEncodeTiled", (void**)&enc, cudaEnableDefault, &q);
    cudaGetSymbolAddress((void**)&scratch, g_s);
    cudaFuncSetAttribute(fused_kernel, cudaFuncAttributeMaxDynamicSharedMemorySize, 232448);
  }
  Maps tm;
  auto mk = [&](CUtensorMap* t, void* ptr, int rank, const cuuint64_t* dims, const cuuint64_t* strides, const cuuint32_t* box,
                CUtensorMapSwizzle sw, CUtensorMapL2promotion pr) {
    const cuuint32_t es[4] = {1, 1, 1, 1};
    enc(t, CU_TENSOR_MAP_DATA_TYPE_BFLOAT16, rank, ptr, dims, strides, box, es, CU_TENSOR_MAP_INTERLEAVE_NONE, sw, pr,
        CU_TENSOR_MAP_FLOAT_OOB_FILL_NONE);
  };
  { const cuuint64_t d[3] = {576, 2, 1024}, st[2] = {1152, 2304}; const cuuint32_t bx[3] = {64, 1, 64};
    mk(&tm.x, d_in[0], 3, d, st, bx, CU_TENSOR_MAP_SWIZZLE_128B, CU_TENSOR_MAP_L2_PROMOTION_NONE);
    const cuuint32_t br[3] = {72, 1, 64};
    mk(&tm.xr, d_in[0], 3, d, st, br, CU_TENSOR_MAP_SWIZZLE_NONE, CU_TENSOR_MAP_L2_PROMOTION_NONE);
    const cuuint32_t bo[3] = {72, 1, 16};
    mk(&tm.out, d_out, 3, d, st, bo, CU_TENSOR_MAP_SWIZZLE_NONE, CU_TENSOR_MAP_L2_PROMOTION_NONE); }
  { const cuuint64_t d[3] = {576, 576, 3}, st[2] = {3456, 1152}; const cuuint32_t bx[3] = {72, 8, 2};
    mk(&tm.wq, d_in[1], 3, d, st, bx, CU_TENSOR_MAP_SWIZZLE_NONE, CU_TENSOR_MAP_L2_PROMOTION_NONE); }
  { const cuuint64_t d[2] = {576, 576}, st[1] = {1152}; const cuuint32_t bx[2] = {72, 16};
    mk(&tm.wo, d_in[2], 2, d, st, bx, CU_TENSOR_MAP_SWIZZLE_NONE, CU_TENSOR_MAP_L2_PROMOTION_NONE); }
  { const cuuint64_t d[2] = {4608, 576}, st[1] = {9216}; const cuuint32_t bx[2] = {48, 64};
    mk(&tm.wg, d_in[5], 2, d, st, bx, CU_TENSOR_MAP_SWIZZLE_128B, CU_TENSOR_MAP_L2_PROMOTION_L2_128B);
    mk(&tm.wu, d_in[6], 2, d, st, bx, CU_TENSOR_MAP_SWIZZLE_128B, CU_TENSOR_MAP_L2_PROMOTION_L2_128B); }
  Params p;
  p.x = (const uint8_t*)d_in[0]; p.wqkv = (const uint8_t*)d_in[1]; p.wo = (const uint8_t*)d_in[2];
  p.wr = (const uint8_t*)d_in[4]; p.wg = (const uint8_t*)d_in[5]; p.wu = (const uint8_t*)d_in[6]; p.wd = (const uint8_t*)d_in[7];
  p.out = (uint8_t*)d_out;
  p.g = scratch;
  fused_kernel<<<128, 512, 232448>>>(p, tm);
}
```

```cpp
#include <cuda_runtime.h>
#include <cuda_bf16.h>
#include <cuda.h>
#include <stdint.h>
#include <stddef.h>

#define DEVI __device__ __forceinline__

namespace {

constexpr int kD = 576, kF = 4608;
constexpr uint32_t WSTAGE = 27648, XSTAGE = 8192;
constexpr float kEps = 1e-5f;

constexpr uint32_t WDP = 1168;
constexpr uint32_t SM_W = 0;
constexpr uint32_t SM_X = 110592;
constexpr uint32_t SM_WD = 176128;
constexpr uint32_t SM_LEFT = SM_WD + 36 * WDP;
constexpr uint32_t SM_COLSUM = SM_LEFT + 9216;
constexpr uint32_t SM_ROWC = SM_COLSUM + 960;
constexpr uint32_t SM_ROWM = SM_ROWC + 512;
constexpr uint32_t SM_PART = SM_ROWM + 1024;
constexpr uint32_t SM_FIXQ = SM_PART;
constexpr uint32_t SM_X2R = SM_PART + 864;
constexpr uint32_t SM_H = SM_PART + 1152;
constexpr uint32_t SM_GEMV = SM_H;
constexpr uint32_t SM_RED = SM_H + 320;
constexpr uint32_t SM_SEL = SM_RED + 256;
constexpr uint32_t SM_EP = SM_SEL + 8, SM_WSUM = SM_SEL + 12;
constexpr uint32_t SM_BAR = SM_SEL + 16;
constexpr uint32_t B_WFULL = SM_BAR, B_WEMPTY = B_WFULL + 32, B_XFULL = B_WEMPTY + 32, B_XEMPTY = B_XFULL + 64;
constexpr uint32_t B_RC = B_XEMPTY + 64;
constexpr uint32_t B_COLSUM = B_RC + 16, B_PKF = B_COLSUM + 8, B_FIX = B_PKF + 8, B_DONE = B_FIX + 8;
constexpr uint32_t B_FF = B_DONE + 8;
constexpr uint32_t B_IDX = B_FF + 24;
constexpr uint32_t B_WD = B_IDX + 16, B_WANT = B_WD + 8, B_EPI = B_WANT + 8, B_EP = B_EPI + 8, B_OS = B_EP + 8, B_FD = B_OS + 8;
constexpr uint32_t B_WL = B_FD + 8;
constexpr uint32_t B_RES = B_WL + 32;
constexpr uint32_t B_XE = B_RES + 16;
constexpr uint32_t SM_TOTAL = B_XE + 16;
constexpr int NBAR = (SM_TOTAL - SM_BAR) / 8, NBAR4 = (B_FF - SM_BAR) / 8;
static_assert(((B_EP - SM_BAR) / 8 * 4) / NBAR == 3, "warp 15 initialises B_EP");
constexpr uint32_t FSLOT = 16384;
static_assert(SM_TOTAL + 256 <= 232448, "smem");

struct __align__(1024) Checked {
  uint32_t candrow[2][128][288];
  uint4 halo[128][2][2][5][32];
  uint8_t wpack[8][12 * WSTAGE];
  uint8_t act[3][16][2][73728];
};
struct __align__(1024) Scratch {
  uint4 cand[2][8][128];
  uint4 ypart[72][128][2];
  uint32_t x2msg[8][576];
  uint32_t fixmsg[8][256];
  uint32_t flagP[8][12][32];
  uint32_t flagX[16][2][32];
  uint32_t epoch[128][8];
  uint4 stats0[16][2][64];
  uint4 statsP[16][2][8][64];
  float colpart[8][8][216];
  Checked chk[2];
};
__device__ Scratch g_s;
#define GA(member, off) (gb + offsetof(Scratch, member) + (uint32_t)(off))
#define GC(member, off) (gb + offsetof(Scratch, chk) + offsetof(Checked, member) + (uint32_t)((off) + (epoch & 1) * (uint32_t)sizeof(Checked)))
constexpr uint32_t ACT = 16 * 2 * 73728;

#define TR(role, i)
#define TRL(role, i)
#define TRDUMP(role)
#define TRW(i)
#define TRZ(i)
#define TRQ(i)

__device__ __forceinline__ void wgmma_n144(float* d, uint32_t alo, uint32_t ahi, uint32_t blo) {
  asm volatile("{\n.reg .b64 da, db;\nmov.b64 da, {%72, %73};\nmov.b64 db, {%74, 8};\n"
    "wgmma.mma_async.sync.aligned.m64n144k16.f32.bf16.bf16 "
    "{%0, %1, %2, %3, %4, %5, %6, %7, %8, %9, %10, %11, %12, %13, %14, %15, %16, %17, %18, %19, %20, %21, %22, %23, %24, %25, %26, %27, %28, %29, %30, %31, %32, %33, %34, %35, %36, %37, %38, %39, %40, %41, %42, %43, %44, %45, %46, %47, %48, %49, %50, %51, %52, %53, %54, %55, %56, %57, %58, %59, %60, %61, %62, %63, %64, %65, %66, %67, %68, %69, %70, %71}, da, db, 1, 1, 1, 0, 1;\n}\n"
    : "+f"(d[0]), "+f"(d[1]), "+f"(d[2]), "+f"(d[3]), "+f"(d[4]), "+f"(d[5]), "+f"(d[6]), "+f"(d[7]), "+f"(d[8]),
      "+f"(d[9]), "+f"(d[10]), "+f"(d[11]), "+f"(d[12]), "+f"(d[13]), "+f"(d[14]), "+f"(d[15]), "+f"(d[16]), "+f"(d[17]),
      "+f"(d[18]), "+f"(d[19]), "+f"(d[20]), "+f"(d[21]), "+f"(d[22]), "+f"(d[23]), "+f"(d[24]), "+f"(d[25]), "+f"(d[26]),
      "+f"(d[27]), "+f"(d[28]), "+f"(d[29]), "+f"(d[30]), "+f"(d[31]), "+f"(d[32]), "+f"(d[33]), "+f"(d[34]), "+f"(d[35]),
      "+f"(d[36]), "+f"(d[37]), "+f"(d[38]), "+f"(d[39]), "+f"(d[40]), "+f"(d[41]), "+f"(d[42]), "+f"(d[43]), "+f"(d[44]),
      "+f"(d[45]), "+f"(d[46]), "+f"(d[47]), "+f"(d[48]), "+f"(d[49]), "+f"(d[50]), "+f"(d[51]), "+f"(d[52]), "+f"(d[53]),
      "+f"(d[54]), "+f"(d[55]), "+f"(d[56]), "+f"(d[57]), "+f"(d[58]), "+f"(d[59]), "+f"(d[60]), "+f"(d[61]), "+f"(d[62]),
      "+f"(d[63]), "+f"(d[64]), "+f"(d[65]), "+f"(d[66]), "+f"(d[67]), "+f"(d[68]), "+f"(d[69]), "+f"(d[70]), "+f"(d[71])
    : "r"(alo), "r"(ahi), "r"(blo));
}
__device__ __forceinline__ void wgmma_n144_set(float* d, const uint32_t* a, uint32_t blo) {
  asm volatile("{\n.reg .b64 db;\nmov.b64 db, {%76, 2};\n"
    "wgmma.mma_async.sync.aligned.m64n144k16.f32.bf16.bf16 "
    "{%0, %1, %2, %3, %4, %5, %6, %7, %8, %9, %10, %11, %12, %13, %14, %15, %16, %17, %18, %19, %20, %21, %22, %23, %24, %25, %26, %27, %28, %29, %30, %31, %32, %33, %34, %35, %36, %37, %38, %39, %40, %41, %42, %43, %44, %45, %46, %47, %48, %49, %50, %51, %52, %53, %54, %55, %56, %57, %58, %59, %60, %61, %62, %63, %64, %65, %66, %67, %68, %69, %70, %71}, {%72, %73, %74, %75}, db, 0, -1, 1, 1;\n}\n"
    : "=f"(d[0]), "=f"(d[1]), "=f"(d[2]), "=f"(d[3]), "=f"(d[4]), "=f"(d[5]), "=f"(d[6]), "=f"(d[7]), "=f"(d[8]),
      "=f"(d[9]), "=f"(d[10]), "=f"(d[11]), "=f"(d[12]), "=f"(d[13]), "=f"(d[14]), "=f"(d[15]), "=f"(d[16]), "=f"(d[17]),
      "=f"(d[18]), "=f"(d[19]), "=f"(d[20]), "=f"(d[21]), "=f"(d[22]), "=f"(d[23]), "=f"(d[24]), "=f"(d[25]), "=f"(d[26]),
      "=f"(d[27]), "=f"(d[28]), "=f"(d[29]), "=f"(d[30]), "=f"(d[31]), "=f"(d[32]), "=f"(d[33]), "=f"(d[34]), "=f"(d[35]),
      "=f"(d[36]), "=f"(d[37]), "=f"(d[38]), "=f"(d[39]), "=f"(d[40]), "=f"(d[41]), "=f"(d[42]), "=f"(d[43]), "=f"(d[44]),
      "=f"(d[45]), "=f"(d[46]), "=f"(d[47]), "=f"(d[48]), "=f"(d[49]), "=f"(d[50]), "=f"(d[51]), "=f"(d[52]), "=f"(d[53]),
      "=f"(d[54]), "=f"(d[55]), "=f"(d[56]), "=f"(d[57]), "=f"(d[58]), "=f"(d[59]), "=f"(d[60]), "=f"(d[61]), "=f"(d[62]),
      "=f"(d[63]), "=f"(d[64]), "=f"(d[65]), "=f"(d[66]), "=f"(d[67]), "=f"(d[68]), "=f"(d[69]), "=f"(d[70]), "=f"(d[71])
    : "r"(a[0]), "r"(a[1]), "r"(a[2]), "r"(a[3]), "r"(blo));
}
__device__ __forceinline__ void wgmma_n144_add(float* d, const uint32_t* a, uint32_t blo) {
  asm volatile("{\n.reg .b64 db;\nmov.b64 db, {%76, 2};\n"
    "wgmma.mma_async.sync.aligned.m64n144k16.f32.bf16.bf16 "
    "{%0, %1, %2, %3, %4, %5, %6, %7, %8, %9, %10, %11, %12, %13, %14, %15, %16, %17, %18, %19, %20, %21, %22, %23, %24, %25, %26, %27, %28, %29, %30, %31, %32, %33, %34, %35, %36, %37, %38, %39, %40, %41, %42, %43, %44, %45, %46, %47, %48, %49, %50, %51, %52, %53, %54, %55, %56, %57, %58, %59, %60, %61, %62, %63, %64, %65, %66, %67, %68, %69, %70, %71}, {%72, %73, %74, %75}, db, 1, -1, 1, 1;\n}\n"
    : "+f"(d[0]), "+f"(d[1]), "+f"(d[2]), "+f"(d[3]), "+f"(d[4]), "+f"(d[5]), "+f"(d[6]), "+f"(d[7]), "+f"(d[8]),
      "+f"(d[9]), "+f"(d[10]), "+f"(d[11]), "+f"(d[12]), "+f"(d[13]), "+f"(d[14]), "+f"(d[15]), "+f"(d[16]), "+f"(d[17]),
      "+f"(d[18]), "+f"(d[19]), "+f"(d[20]), "+f"(d[21]), "+f"(d[22]), "+f"(d[23]), "+f"(d[24]), "+f"(d[25]), "+f"(d[26]),
      "+f"(d[27]), "+f"(d[28]), "+f"(d[29]), "+f"(d[30]), "+f"(d[31]), "+f"(d[32]), "+f"(d[33]), "+f"(d[34]), "+f"(d[35]),
      "+f"(d[36]), "+f"(d[37]), "+f"(d[38]), "+f"(d[39]), "+f"(d[40]), "+f"(d[41]), "+f"(d[42]), "+f"(d[43]), "+f"(d[44]),
      "+f"(d[45]), "+f"(d[46]), "+f"(d[47]), "+f"(d[48]), "+f"(d[49]), "+f"(d[50]), "+f"(d[51]), "+f"(d[52]), "+f"(d[53]),
      "+f"(d[54]), "+f"(d[55]), "+f"(d[56]), "+f"(d[57]), "+f"(d[58]), "+f"(d[59]), "+f"(d[60]), "+f"(d[61]), "+f"(d[62]),
      "+f"(d[63]), "+f"(d[64]), "+f"(d[65]), "+f"(d[66]), "+f"(d[67]), "+f"(d[68]), "+f"(d[69]), "+f"(d[70]), "+f"(d[71])
    : "r"(a[0]), "r"(a[1]), "r"(a[2]), "r"(a[3]), "r"(blo));
}
__device__ __forceinline__ void wgmma_n72(float* d, uint32_t alo, uint32_t ahi, uint32_t blo) {
  asm volatile("{\n.reg .b64 da, db;\nmov.b64 da, {%36, %37};\nmov.b64 db, {%38, 8};\n"
    "wgmma.mma_async.sync.aligned.m64n72k16.f32.bf16.bf16 "
    "{%0, %1, %2, %3, %4, %5, %6, %7, %8, %9, %10, %11, %12, %13, %14, %15, %16, %17, %18, %19, %20, %21, %22, %23, %24, %25, %26, %27, %28, %29, %30, %31, %32, %33, %34, %35}, da, db, 1, 1, 1, 0, 1;\n}\n"
    : "+f"(d[0]), "+f"(d[1]), "+f"(d[2]), "+f"(d[3]), "+f"(d[4]), "+f"(d[5]), "+f"(d[6]), "+f"(d[7]), "+f"(d[8]),
      "+f"(d[9]), "+f"(d[10]), "+f"(d[11]), "+f"(d[12]), "+f"(d[13]), "+f"(d[14]), "+f"(d[15]), "+f"(d[16]), "+f"(d[17]),
      "+f"(d[18]), "+f"(d[19]), "+f"(d[20]), "+f"(d[21]), "+f"(d[22]), "+f"(d[23]), "+f"(d[24]), "+f"(d[25]), "+f"(d[26]),
      "+f"(d[27]), "+f"(d[28]), "+f"(d[29]), "+f"(d[30]), "+f"(d[31]), "+f"(d[32]), "+f"(d[33]), "+f"(d[34]), "+f"(d[35])
    : "r"(alo), "r"(ahi), "r"(blo));
}
__device__ __forceinline__ void wgmma_n72_set(float* d, const uint32_t* a, uint32_t blo) {
  asm volatile("{\n.reg .b64 db;\nmov.b64 db, {%40, 2};\n"
    "wgmma.mma_async.sync.aligned.m64n72k16.f32.bf16.bf16 "
    "{%0, %1, %2, %3, %4, %5, %6, %7, %8, %9, %10, %11, %12, %13, %14, %15, %16, %17, %18, %19, %20, %21, %22, %23, %24, %25, %26, %27, %28, %29, %30, %31, %32, %33, %34, %35}, {%36, %37, %38, %39}, db, 0, -1, 1, 1;\n}\n"
    : "=f"(d[0]), "=f"(d[1]), "=f"(d[2]), "=f"(d[3]), "=f"(d[4]), "=f"(d[5]), "=f"(d[6]), "=f"(d[7]), "=f"(d[8]),
      "=f"(d[9]), "=f"(d[10]), "=f"(d[11]), "=f"(d[12]), "=f"(d[13]), "=f"(d[14]), "=f"(d[15]), "=f"(d[16]), "=f"(d[17]),
      "=f"(d[18]), "=f"(d[19]), "=f"(d[20]), "=f"(d[21]), "=f"(d[22]), "=f"(d[23]), "=f"(d[24]), "=f"(d[25]), "=f"(d[26]),
      "=f"(d[27]), "=f"(d[28]), "=f"(d[29]), "=f"(d[30]), "=f"(d[31]), "=f"(d[32]), "=f"(d[33]), "=f"(d[34]), "=f"(d[35])
    : "r"(a[0]), "r"(a[1]), "r"(a[2]), "r"(a[3]), "r"(blo));
}
__device__ __forceinline__ void wgmma_n72_add(float* d, const uint32_t* a, uint32_t blo) {
  asm volatile("{\n.reg .b64 db;\nmov.b64 db, {%40, 2};\n"
    "wgmma.mma_async.sync.aligned.m64n72k16.f32.bf16.bf16 "
    "{%0, %1, %2, %3, %4, %5, %6, %7, %8, %9, %10, %11, %12, %13, %14, %15, %16, %17, %18, %19, %20, %21, %22, %23, %24, %25, %26, %27, %28, %29, %30, %31, %32, %33, %34, %35}, {%36, %37, %38, %39}, db, 1, -1, 1, 1;\n}\n"
    : "+f"(d[0]), "+f"(d[1]), "+f"(d[2]), "+f"(d[3]), "+f"(d[4]), "+f"(d[5]), "+f"(d[6]), "+f"(d[7]), "+f"(d[8]),
      "+f"(d[9]), "+f"(d[10]), "+f"(d[11]), "+f"(d[12]), "+f"(d[13]), "+f"(d[14]), "+f"(d[15]), "+f"(d[16]), "+f"(d[17]),
      "+f"(d[18]), "+f"(d[19]), "+f"(d[20]), "+f"(d[21]), "+f"(d[22]), "+f"(d[23]), "+f"(d[24]), "+f"(d[25]), "+f"(d[26]),
      "+f"(d[27]), "+f"(d[28]), "+f"(d[29]), "+f"(d[30]), "+f"(d[31]), "+f"(d[32]), "+f"(d[33]), "+f"(d[34]), "+f"(d[35])
    : "r"(a[0]), "r"(a[1]), "r"(a[2]), "r"(a[3]), "r"(blo));
}
__device__ __forceinline__ void q_tail(float* d, uint32_t* v, uint32_t ahi, const uint32_t* dsc, const uint32_t* bar, const uint32_t* adr) {
  asm volatile(
    "{\n.reg .pred p<2>, q;\n.reg .b64 da, db;\n.reg .u32 n;\n"
    "mbarrier.test_wait.parity.shared::cta.b64 p0, [%116], %117;\n"
    "mbarrier.test_wait.parity.shared::cta.b64 p1, [%118], %119;\n"
    "ld.volatile.shared.u32 %108, [%120];\n"
    "mov.b64 da, {%110, %109};\nmov.b64 db, {%111, 8};\n"
    "wgmma.mma_async.sync.aligned.m64n144k16.f32.bf16.bf16 {%36, %37, %38, %39, %40, %41, %42, %43, %44, %45, %46, %47, %48, %49, %50, %51, %52, %53, %54, %55, %56, %57, %58, %59, %60, %61, %62, %63, %64, %65, %66, %67, %68, %69, %70, %71, %72, %73, %74, %75, %76, %77, %78, %79, %80, %81, %82, %83, %84, %85, %86, %87, %88, %89, %90, %91, %92, %93, %94, %95, %96, %97, %98, %99, %100, %101, %102, %103, %104, %105, %106, %107}, da, db, 1, 1, 1, 0, 1;\n"
    "mov.b64 da, {%112, %109};\nmov.b64 db, {%113, 8};\n"
    "wgmma.mma_async.sync.aligned.m64n72k16.f32.bf16.bf16 {%0, %1, %2, %3, %4, %5, %6, %7, %8, %9, %10, %11, %12, %13, %14, %15, %16, %17, %18, %19, %20, %21, %22, %23, %24, %25, %26, %27, %28, %29, %30, %31, %32, %33, %34, %35}, da, db, 1, 1, 1, 0, 1;\n"
    "mov.b64 da, {%114, %109};\nmov.b64 db, {%115, 8};\n"
    "wgmma.mma_async.sync.aligned.m64n144k16.f32.bf16.bf16 {%36, %37, %38, %39, %40, %41, %42, %43, %44, %45, %46, %47, %48, %49, %50, %51, %52, %53, %54, %55, %56, %57, %58, %59, %60, %61, %62, %63, %64, %65, %66, %67, %68, %69, %70, %71, %72, %73, %74, %75, %76, %77, %78, %79, %80, %81, %82, %83, %84, %85, %86, %87, %88, %89, %90, %91, %92, %93, %94, %95, %96, %97, %98, %99, %100, %101, %102, %103, %104, %105, %106, %107}, da, db, 1, 1, 1, 0, 1;\n"
    "wgmma.commit_group.sync.aligned;\n"
    "@p0 bra.uni D0;\nmov.u32 n, 0;\nW0:\nmbarrier.try_wait.parity.shared::cta.b64 q, [%116], %117;\n@q bra.uni R0;\nadd.u32 n, n, 1;\nsetp.lt.u32 q, n, 8192;\n@q bra.uni W0;\nR0:\n"
    "D0:\n"
    "@p1 bra.uni D1;\nmov.u32 n, 0;\nW1:\nmbarrier.try_wait.parity.shared::cta.b64 q, [%118], %119;\n@q bra.uni R1;\nadd.u32 n, n, 1;\nsetp.lt.u32 q, n, 8192;\n@q bra.uni W1;\nR1:\n"
    "ld.volatile.shared.u32 %108, [%120];\n"
    "D1:\n"
    "}\n"
    : "+f"(d[0]), "+f"(d[1]), "+f"(d[2]), "+f"(d[3]), "+f"(d[4]), "+f"(d[5]), "+f"(d[6]), "+f"(d[7]), "+f"(d[8]),
      "+f"(d[9]), "+f"(d[10]), "+f"(d[11]), "+f"(d[12]), "+f"(d[13]), "+f"(d[14]), "+f"(d[15]), "+f"(d[16]), "+f"(d[17]),
      "+f"(d[18]), "+f"(d[19]), "+f"(d[20]), "+f"(d[21]), "+f"(d[22]), "+f"(d[23]), "+f"(d[24]), "+f"(d[25]), "+f"(d[26]),
      "+f"(d[27]), "+f"(d[28]), "+f"(d[29]), "+f"(d[30]), "+f"(d[31]), "+f"(d[32]), "+f"(d[33]), "+f"(d[34]), "+f"(d[35]),
      "+f"(d[36]), "+f"(d[37]), "+f"(d[38]), "+f"(d[39]), "+f"(d[40]), "+f"(d[41]), "+f"(d[42]), "+f"(d[43]), "+f"(d[44]),
      "+f"(d[45]), "+f"(d[46]), "+f"(d[47]), "+f"(d[48]), "+f"(d[49]), "+f"(d[50]), "+f"(d[51]), "+f"(d[52]), "+f"(d[53]),
      "+f"(d[54]), "+f"(d[55]), "+f"(d[56]), "+f"(d[57]), "+f"(d[58]), "+f"(d[59]), "+f"(d[60]), "+f"(d[61]), "+f"(d[62]),
      "+f"(d[63]), "+f"(d[64]), "+f"(d[65]), "+f"(d[66]), "+f"(d[67]), "+f"(d[68]), "+f"(d[69]), "+f"(d[70]), "+f"(d[71]),
      "+f"(d[72]), "+f"(d[73]), "+f"(d[74]), "+f"(d[75]), "+f"(d[76]), "+f"(d[77]), "+f"(d[78]), "+f"(d[79]), "+f"(d[80]),
      "+f"(d[81]), "+f"(d[82]), "+f"(d[83]), "+f"(d[84]), "+f"(d[85]), "+f"(d[86]), "+f"(d[87]), "+f"(d[88]), "+f"(d[89]),
      "+f"(d[90]), "+f"(d[91]), "+f"(d[92]), "+f"(d[93]), "+f"(d[94]), "+f"(d[95]), "+f"(d[96]), "+f"(d[97]), "+f"(d[98]),
      "+f"(d[99]), "+f"(d[100]), "+f"(d[101]), "+f"(d[102]), "+f"(d[103]), "+f"(d[104]), "+f"(d[105]), "+f"(d[106]), "+f"(d[107]),
      "=&r"(v[0])
    : "r"(ahi), "r"(dsc[0]), "r"(dsc[1]), "r"(dsc[2]), "r"(dsc[3]), "r"(dsc[4]), "r"(dsc[5]), "r"(bar[0]), "r"(bar[1]), "r"(bar[2]), "r"(bar[3]), "r"(adr[0]) : "memory");
}
__device__ __forceinline__ void kv_tail(float* d, uint32_t* v, uint32_t ahi, const uint32_t* dsc, const uint32_t* bar, const uint32_t* adr) {
  asm volatile(
    "{\n.reg .pred p<3>, q;\n.reg .b64 da, db;\n.reg .u32 n;\n"
    "mbarrier.test_wait.parity.shared::cta.b64 p0, [%79], %80;\n"
    "mbarrier.test_wait.parity.shared::cta.b64 p1, [%81], %82;\n"
    "mbarrier.test_wait.parity.shared::cta.b64 p2, [%83], %84;\n"
    "ld.volatile.shared.u32 %72, [%85];\n"
    "ld.volatile.shared.u32 %73, [%86];\n"
    "mov.b64 da, {%75, %74};\nmov.b64 db, {%76, 8};\n"
    "wgmma.mma_async.sync.aligned.m64n144k16.f32.bf16.bf16 {%0, %1, %2, %3, %4, %5, %6, %7, %8, %9, %10, %11, %12, %13, %14, %15, %16, %17, %18, %19, %20, %21, %22, %23, %24, %25, %26, %27, %28, %29, %30, %31, %32, %33, %34, %35, %36, %37, %38, %39, %40, %41, %42, %43, %44, %45, %46, %47, %48, %49, %50, %51, %52, %53, %54, %55, %56, %57, %58, %59, %60, %61, %62, %63, %64, %65, %66, %67, %68, %69, %70, %71}, da, db, 1, 1, 1, 0, 1;\n"
    "mov.b64 da, {%77, %74};\nmov.b64 db, {%78, 8};\n"
    "wgmma.mma_async.sync.aligned.m64n144k16.f32.bf16.bf16 {%0, %1, %2, %3, %4, %5, %6, %7, %8, %9, %10, %11, %12, %13, %14, %15, %16, %17, %18, %19, %20, %21, %22, %23, %24, %25, %26, %27, %28, %29, %30, %31, %32, %33, %34, %35, %36, %37, %38, %39, %40, %41, %42, %43, %44, %45, %46, %47, %48, %49, %50, %51, %52, %53, %54, %55, %56, %57, %58, %59, %60, %61, %62, %63, %64, %65, %66, %67, %68, %69, %70, %71}, da, db, 1, 1, 1, 0, 1;\n"
    "wgmma.commit_group.sync.aligned;\n"
    "@p0 bra.uni D0;\nmov.u32 n, 0;\nW0:\nmbarrier.try_wait.parity.shared::cta.b64 q, [%79], %80;\n@q bra.uni R0;\nadd.u32 n, n, 1;\nsetp.lt.u32 q, n, 8192;\n@q bra.uni W0;\nR0:\n"
    "D0:\n"
    "@p1 bra.uni D1;\nmov.u32 n, 0;\nW1:\nmbarrier.try_wait.parity.shared::cta.b64 q, [%81], %82;\n@q bra.uni R1;\nadd.u32 n, n, 1;\nsetp.lt.u32 q, n, 8192;\n@q bra.uni W1;\nR1:\n"
    "ld.volatile.shared.u32 %72, [%85];\n"
    "D1:\n"
    "@p2 bra.uni D2;\nmov.u32 n, 0;\nW2:\nmbarrier.try_wait.parity.shared::cta.b64 q, [%83], %84;\n@q bra.uni R2;\nadd.u32 n, n, 1;\nsetp.lt.u32 q, n, 8192;\n@q bra.uni W2;\nR2:\n"
    "ld.volatile.shared.u32 %73, [%86];\n"
    "D2:\n"
    "}\n"
    : "+f"(d[36]), "+f"(d[37]), "+f"(d[38]), "+f"(d[39]), "+f"(d[40]), "+f"(d[41]), "+f"(d[42]), "+f"(d[43]), "+f"(d[44]),
      "+f"(d[45]), "+f"(d[46]), "+f"(d[47]), "+f"(d[48]), "+f"(d[49]), "+f"(d[50]), "+f"(d[51]), "+f"(d[52]), "+f"(d[53]),
      "+f"(d[54]), "+f"(d[55]), "+f"(d[56]), "+f"(d[57]), "+f"(d[58]), "+f"(d[59]), "+f"(d[60]), "+f"(d[61]), "+f"(d[62]),
      "+f"(d[63]), "+f"(d[64]), "+f"(d[65]), "+f"(d[66]), "+f"(d[67]), "+f"(d[68]), "+f"(d[69]), "+f"(d[70]), "+f"(d[71]),
      "+f"(d[72]), "+f"(d[73]), "+f"(d[74]), "+f"(d[75]), "+f"(d[76]), "+f"(d[77]), "+f"(d[78]), "+f"(d[79]), "+f"(d[80]),
      "+f"(d[81]), "+f"(d[82]), "+f"(d[83]), "+f"(d[84]), "+f"(d[85]), "+f"(d[86]), "+f"(d[87]), "+f"(d[88]), "+f"(d[89]),
      "+f"(d[90]), "+f"(d[91]), "+f"(d[92]), "+f"(d[93]), "+f"(d[94]), "+f"(d[95]), "+f"(d[96]), "+f"(d[97]), "+f"(d[98]),
      "+f"(d[99]), "+f"(d[100]), "+f"(d[101]), "+f"(d[102]), "+f"(d[103]), "+f"(d[104]), "+f"(d[105]), "+f"(d[106]), "+f"(d[107]),
      "=&r"(v[0]), "=&r"(v[1])
    : "r"(ahi), "r"(dsc[0]), "r"(dsc[1]), "r"(dsc[2]), "r"(dsc[3]), "r"(bar[0]), "r"(bar[1]), "r"(bar[2]), "r"(bar[3]), "r"(bar[4]), "r"(bar[5]), "r"(adr[0]), "r"(adr[1]) : "memory");
}
__device__ __forceinline__ void kv_last(float* d, uint32_t* v, uint32_t ahi, const uint32_t* dsc, const uint32_t* bar, const uint32_t* adr) {
  asm volatile(
    "{\n.reg .pred p<1>, q;\n.reg .b64 da, db;\n.reg .u32 n;\n"
    "mbarrier.test_wait.parity.shared::cta.b64 p0, [%81], %82;\n"
    "mov.b64 da, {%73, %72};\nmov.b64 db, {%74, 8};\n"
    "wgmma.mma_async.sync.aligned.m64n144k16.f32.bf16.bf16 {%0, %1, %2, %3, %4, %5, %6, %7, %8, %9, %10, %11, %12, %13, %14, %15, %16, %17, %18, %19, %20, %21, %22, %23, %24, %25, %26, %27, %28, %29, %30, %31, %32, %33, %34, %35, %36, %37, %38, %39, %40, %41, %42, %43, %44, %45, %46, %47, %48, %49, %50, %51, %52, %53, %54, %55, %56, %57, %58, %59, %60, %61, %62, %63, %64, %65, %66, %67, %68, %69, %70, %71}, da, db, 1, 1, 1, 0, 1;\n"
    "mov.b64 da, {%75, %72};\nmov.b64 db, {%76, 8};\n"
    "wgmma.mma_async.sync.aligned.m64n144k16.f32.bf16.bf16 {%0, %1, %2, %3, %4, %5, %6, %7, %8, %9, %10, %11, %12, %13, %14, %15, %16, %17, %18, %19, %20, %21, %22, %23, %24, %25, %26, %27, %28, %29, %30, %31, %32, %33, %34, %35, %36, %37, %38, %39, %40, %41, %42, %43, %44, %45, %46, %47, %48, %49, %50, %51, %52, %53, %54, %55, %56, %57, %58, %59, %60, %61, %62, %63, %64, %65, %66, %67, %68, %69, %70, %71}, da, db, 1, 1, 1, 0, 1;\n"
    "mov.b64 da, {%77, %72};\nmov.b64 db, {%78, 8};\n"
    "wgmma.mma_async.sync.aligned.m64n144k16.f32.bf16.bf16 {%0, %1, %2, %3, %4, %5, %6, %7, %8, %9, %10, %11, %12, %13, %14, %15, %16, %17, %18, %19, %20, %21, %22, %23, %24, %25, %26, %27, %28, %29, %30, %31, %32, %33, %34, %35, %36, %37, %38, %39, %40, %41, %42, %43, %44, %45, %46, %47, %48, %49, %50, %51, %52, %53, %54, %55, %56, %57, %58, %59, %60, %61, %62, %63, %64, %65, %66, %67, %68, %69, %70, %71}, da, db, 1, 1, 1, 0, 1;\n"
    "mov.b64 da, {%79, %72};\nmov.b64 db, {%80, 8};\n"
    "wgmma.mma_async.sync.aligned.m64n144k16.f32.bf16.bf16 {%0, %1, %2, %3, %4, %5, %6, %7, %8, %9, %10, %11, %12, %13, %14, %15, %16, %17, %18, %19, %20, %21, %22, %23, %24, %25, %26, %27, %28, %29, %30, %31, %32, %33, %34, %35, %36, %37, %38, %39, %40, %41, %42, %43, %44, %45, %46, %47, %48, %49, %50, %51, %52, %53, %54, %55, %56, %57, %58, %59, %60, %61, %62, %63, %64, %65, %66, %67, %68, %69, %70, %71}, da, db, 1, 1, 1, 0, 1;\n"
    "wgmma.commit_group.sync.aligned;\n"
    "@p0 bra.uni D0;\nmov.u32 n, 0;\nW0:\nmbarrier.try_wait.parity.shared::cta.b64 q, [%81], %82;\n@q bra.uni R0;\nadd.u32 n, n, 1;\nsetp.lt.u32 q, n, 8192;\n@q bra.uni W0;\nR0:\n"
    "D0:\n"
    "}\n"
    : "+f"(d[36]), "+f"(d[37]), "+f"(d[38]), "+f"(d[39]), "+f"(d[40]), "+f"(d[41]), "+f"(d[42]), "+f"(d[43]), "+f"(d[44]),
      "+f"(d[45]), "+f"(d[46]), "+f"(d[47]), "+f"(d[48]), "+f"(d[49]), "+f"(d[50]), "+f"(d[51]), "+f"(d[52]), "+f"(d[53]),
      "+f"(d[54]), "+f"(d[55]), "+f"(d[56]), "+f"(d[57]), "+f"(d[58]), "+f"(d[59]), "+f"(d[60]), "+f"(d[61]), "+f"(d[62]),
      "+f"(d[63]), "+f"(d[64]), "+f"(d[65]), "+f"(d[66]), "+f"(d[67]), "+f"(d[68]), "+f"(d[69]), "+f"(d[70]), "+f"(d[71]),
      "+f"(d[72]), "+f"(d[73]), "+f"(d[74]), "+f"(d[75]), "+f"(d[76]), "+f"(d[77]), "+f"(d[78]), "+f"(d[79]), "+f"(d[80]),
      "+f"(d[81]), "+f"(d[82]), "+f"(d[83]), "+f"(d[84]), "+f"(d[85]), "+f"(d[86]), "+f"(d[87]), "+f"(d[88]), "+f"(d[89]),
      "+f"(d[90]), "+f"(d[91]), "+f"(d[92]), "+f"(d[93]), "+f"(d[94]), "+f"(d[95]), "+f"(d[96]), "+f"(d[97]), "+f"(d[98]),
      "+f"(d[99]), "+f"(d[100]), "+f"(d[101]), "+f"(d[102]), "+f"(d[103]), "+f"(d[104]), "+f"(d[105]), "+f"(d[106]), "+f"(d[107])
    : "r"(ahi), "r"(dsc[0]), "r"(dsc[1]), "r"(dsc[2]), "r"(dsc[3]), "r"(dsc[4]), "r"(dsc[5]), "r"(dsc[6]), "r"(dsc[7]), "r"(bar[0]), "r"(bar[1]) : "memory");
}
__device__ __forceinline__ void o_tail(float* d, uint32_t* v, uint32_t ahi, const uint32_t* dsc, const uint32_t* bar, const uint32_t* adr) {
  asm volatile(
    "{\n.reg .pred p<1>, q;\n.reg .b64 da, db;\n.reg .u32 n;\n"
    "mbarrier.test_wait.parity.shared::cta.b64 p0, [%42], %43;\n"
    "ld.volatile.shared.u32 %36, [%44];\n"
    "mov.b64 da, {%38, %37};\nmov.b64 db, {%39, 8};\n"
    "wgmma.mma_async.sync.aligned.m64n72k16.f32.bf16.bf16 {%0, %1, %2, %3, %4, %5, %6, %7, %8, %9, %10, %11, %12, %13, %14, %15, %16, %17, %18, %19, %20, %21, %22, %23, %24, %25, %26, %27, %28, %29, %30, %31, %32, %33, %34, %35}, da, db, 1, 1, 1, 0, 1;\n"
    "mov.b64 da, {%40, %37};\nmov.b64 db, {%41, 8};\n"
    "wgmma.mma_async.sync.aligned.m64n72k16.f32.bf16.bf16 {%0, %1, %2, %3, %4, %5, %6, %7, %8, %9, %10, %11, %12, %13, %14, %15, %16, %17, %18, %19, %20, %21, %22, %23, %24, %25, %26, %27, %28, %29, %30, %31, %32, %33, %34, %35}, da, db, 1, 1, 1, 0, 1;\n"
    "wgmma.commit_group.sync.aligned;\n"
    "@p0 bra.uni D0;\nmov.u32 n, 0;\nW0:\nmbarrier.try_wait.parity.shared::cta.b64 q, [%42], %43;\n@q bra.uni R0;\nadd.u32 n, n, 1;\nsetp.lt.u32 q, n, 8192;\n@q bra.uni W0;\nR0:\n"
    "ld.volatile.shared.u32 %36, [%44];\n"
    "D0:\n"
    "}\n"
    : "+f"(d[0]), "+f"(d[1]), "+f"(d[2]), "+f"(d[3]), "+f"(d[4]), "+f"(d[5]), "+f"(d[6]), "+f"(d[7]), "+f"(d[8]),
      "+f"(d[9]), "+f"(d[10]), "+f"(d[11]), "+f"(d[12]), "+f"(d[13]), "+f"(d[14]), "+f"(d[15]), "+f"(d[16]), "+f"(d[17]),
      "+f"(d[18]), "+f"(d[19]), "+f"(d[20]), "+f"(d[21]), "+f"(d[22]), "+f"(d[23]), "+f"(d[24]), "+f"(d[25]), "+f"(d[26]),
      "+f"(d[27]), "+f"(d[28]), "+f"(d[29]), "+f"(d[30]), "+f"(d[31]), "+f"(d[32]), "+f"(d[33]), "+f"(d[34]), "+f"(d[35]),
      "=&r"(v[0])
    : "r"(ahi), "r"(dsc[0]), "r"(dsc[1]), "r"(dsc[2]), "r"(dsc[3]), "r"(bar[0]), "r"(bar[1]), "r"(adr[0]) : "memory");
}
__device__ __forceinline__ void o_tail2(float* d, uint32_t* v, uint32_t ahi, const uint32_t* dsc, const uint32_t* bar, const uint32_t* adr) {
  asm volatile(
    "{\n.reg .pred p<2>, q;\n.reg .b64 da, db;\n.reg .u32 n;\n"
    "mbarrier.test_wait.parity.shared::cta.b64 p0, [%42], %43;\n"
    "mbarrier.test_wait.parity.shared::cta.b64 p1, [%44], %45;\n"
    "ld.volatile.shared.u32 %36, [%46];\n"
    "mov.b64 da, {%38, %37};\nmov.b64 db, {%39, 8};\n"
    "wgmma.mma_async.sync.aligned.m64n72k16.f32.bf16.bf16 {%0, %1, %2, %3, %4, %5, %6, %7, %8, %9, %10, %11, %12, %13, %14, %15, %16, %17, %18, %19, %20, %21, %22, %23, %24, %25, %26, %27, %28, %29, %30, %31, %32, %33, %34, %35}, da, db, 1, 1, 1, 0, 1;\n"
    "mov.b64 da, {%40, %37};\nmov.b64 db, {%41, 8};\n"
    "wgmma.mma_async.sync.aligned.m64n72k16.f32.bf16.bf16 {%0, %1, %2, %3, %4, %5, %6, %7, %8, %9, %10, %11, %12, %13, %14, %15, %16, %17, %18, %19, %20, %21, %22, %23, %24, %25, %26, %27, %28, %29, %30, %31, %32, %33, %34, %35}, da, db, 1, 1, 1, 0, 1;\n"
    "wgmma.commit_group.sync.aligned;\n"
    "@p0 bra.uni D0;\nmov.u32 n, 0;\nW0:\nmbarrier.try_wait.parity.shared::cta.b64 q, [%42], %43;\n@q bra.uni R0;\nadd.u32 n, n, 1;\nsetp.lt.u32 q, n, 8192;\n@q bra.uni W0;\nR0:\n"
    "D0:\n"
    "@p1 bra.uni D1;\nmov.u32 n, 0;\nW1:\nmbarrier.try_wait.parity.shared::cta.b64 q, [%44], %45;\n@q bra.uni R1;\nadd.u32 n, n, 1;\nsetp.lt.u32 q, n, 8192;\n@q bra.uni W1;\nR1:\n"
    "ld.volatile.shared.u32 %36, [%46];\n"
    "D1:\n"
    "}\n"
    : "+f"(d[0]), "+f"(d[1]), "+f"(d[2]), "+f"(d[3]), "+f"(d[4]), "+f"(d[5]), "+f"(d[6]), "+f"(d[7]), "+f"(d[8]),
      "+f"(d[9]), "+f"(d[10]), "+f"(d[11]), "+f"(d[12]), "+f"(d[13]), "+f"(d[14]), "+f"(d[15]), "+f"(d[16]), "+f"(d[17]),
      "+f"(d[18]), "+f"(d[19]), "+f"(d[20]), "+f"(d[21]), "+f"(d[22]), "+f"(d[23]), "+f"(d[24]), "+f"(d[25]), "+f"(d[26]),
      "+f"(d[27]), "+f"(d[28]), "+f"(d[29]), "+f"(d[30]), "+f"(d[31]), "+f"(d[32]), "+f"(d[33]), "+f"(d[34]), "+f"(d[35]),
      "=&r"(v[0])
    : "r"(ahi), "r"(dsc[0]), "r"(dsc[1]), "r"(dsc[2]), "r"(dsc[3]), "r"(bar[0]), "r"(bar[1]), "r"(bar[2]), "r"(bar[3]), "r"(adr[0]) : "memory");
}

DEVI void mbar_init(uint32_t b, int c) { asm volatile("mbarrier.init.shared::cta.b64 [%0], %1;" ::"r"(b), "r"(c)); }
DEVI void mbar_arrive(uint32_t b) { asm volatile("mbarrier.arrive.shared::cta.b64 _, [%0];" ::"r"(b) : "memory"); }
DEVI void mbar_expect(uint32_t b, uint32_t tx) {
  asm volatile("mbarrier.arrive.expect_tx.shared::cta.b64 _, [%0], %1;" ::"r"(b), "r"(tx) : "memory");
}
DEVI void mbar_wait(uint32_t b, uint32_t ph) {
  asm volatile(
      "{\n.reg .pred p;\n.reg .u32 n;\nmov.u32 n, 0;\n"
      "LW:\nmbarrier.try_wait.parity.shared::cta.b64 p, [%0], %1;\n"
      "@p bra LD;\nadd.u32 n, n, 1;\nsetp.lt.u32 p, n, 8192;\n@p bra LW;\nLD:\n}\n" ::"r"(b), "r"(ph)
      : "memory");
}
DEVI void mbar_wait2(uint32_t a, uint32_t pa, uint32_t b, uint32_t pb) {
  asm volatile(
      "{\n.reg .pred p, q;\n.reg .u32 n;\nmov.u32 n, 0;\n"
      "LW:\nmbarrier.try_wait.parity.shared::cta.b64 p, [%0], %1;\nmbarrier.try_wait.parity.shared::cta.b64 q, [%2], %3;\n"
      "and.pred p, p, q;\n@p bra LD;\nadd.u32 n, n, 1;\nsetp.lt.u32 p, n, 8192;\n@p bra LW;\nLD:\n}\n" ::"r"(a), "r"(pa), "r"(b), "r"(pb)
      : "memory");
}
DEVI bool elect() {
  uint32_t el;
  asm volatile("{\n.reg .pred p;\nelect.sync _|p, 0xffffffff;\nselp.u32 %0,1,0,p;\n}\n" : "=r"(el));
  return el;
}
DEVI void bulk_g2s(uint32_t dst, const void* src, uint32_t bytes, uint32_t bar) {
  asm volatile("cp.async.bulk.shared::cluster.global.mbarrier::complete_tx::bytes [%0], [%1], %2, [%3];" ::"r"(dst),
               "l"(src), "r"(bytes), "r"(bar)
               : "memory");
}
DEVI void bulk_g2s_pair(uint32_t dst, const void* src, uint32_t bytes, uint32_t bar) {
  asm volatile("cp.async.bulk.shared::cluster.global.mbarrier::complete_tx::bytes.multicast::cluster [%0], [%1], %2, [%3], %4;" ::"r"(dst),
               "l"(src), "r"(bytes), "r"(bar), "h"((uint16_t)3)
               : "memory");
}
DEVI void mbar_arrive_pair(uint32_t b) {
  asm volatile("mbarrier.arrive.shared::cta.b64 _, [%0];\nmbarrier.arrive.shared::cluster.b64 _, [%1];\n" ::"r"(b), "r"(b ^ 0x1000000u) : "memory");
}
DEVI void cluster_arrive() { asm volatile("barrier.cluster.arrive.relaxed.aligned;" ::: "memory"); }
DEVI void cluster_wait() { asm volatile("barrier.cluster.wait.aligned;" ::: "memory"); }
DEVI void tma3(uint32_t dst, const CUtensorMap* m, int c0, int c1, int c2, uint32_t bar) {
  asm volatile(
      "cp.async.bulk.tensor.3d.shared::cluster.global.mbarrier::complete_tx::bytes [%0], [%1, {%3,%4,%5}], [%2];" ::"r"(dst),
      "l"(m), "r"(bar), "r"(c0), "r"(c1), "r"(c2)
      : "memory");
}
DEVI constexpr uint32_t mkdesc(uint32_t addr, uint32_t lbo) { return ((addr & 0x3FFFF) >> 4) | ((lbo >> 4) << 16); }
DEVI void bar_sync(int id) { asm volatile("bar.sync %0, 128;" ::"r"(id) : "memory"); }
DEVI uint4 ld_msg(const void* p) {
  uint4 v;
  asm volatile("ld.relaxed.gpu.global.v4.u32 {%0,%1,%2,%3}, [%4];" : "=r"(v.x), "=r"(v.y), "=r"(v.z), "=r"(v.w) : "l"(p) : "memory");
  return v;
}
DEVI void st_msg(void* p, uint32_t a, uint32_t b, uint32_t c, uint32_t d) {
  asm volatile("st.relaxed.gpu.global.v4.u32 [%0], {%1,%2,%3,%4};" ::"l"(p), "r"(a), "r"(b), "r"(c), "r"(d) : "memory");
}
DEVI uint4 ld_gen(const void* p) {
  uint4 v;
  asm volatile("ld.relaxed.gpu.v4.u32 {%0,%1,%2,%3}, [%4];" : "=r"(v.x), "=r"(v.y), "=r"(v.z), "=r"(v.w) : "l"(p) : "memory");
  return v;
}
DEVI void st_gen(void* p, uint32_t a, uint32_t b, uint32_t c, uint32_t d) {
  asm volatile("st.relaxed.gpu.v4.u32 [%0], {%1,%2,%3,%4};" ::"l"(p), "r"(a), "r"(b), "r"(c), "r"(d) : "memory");
}
DEVI uint32_t ld_rlx(const void* p) {
  uint32_t v;
  asm volatile("ld.relaxed.gpu.global.u32 %0, [%1];" : "=r"(v) : "l"(p) : "memory");
  return v;
}
DEVI uint2 ld_rlx2(const void* p) {
  uint2 v;
  asm volatile("ld.relaxed.gpu.global.v2.u32 {%0,%1}, [%2];" : "=r"(v.x), "=r"(v.y) : "l"(p) : "memory");
  return v;
}
DEVI void st_rlx(void* p, uint32_t v) { asm volatile("st.relaxed.gpu.global.u32 [%0], %1;" ::"l"(p), "r"(v) : "memory"); }
#define spin_guard(n) if (++n > (1u << 16)) break
DEVI void wait_flags(const uint8_t* p, int word, uint32_t target) {
  uint32_t n = 0;
  p += 4 * word;
  _Pragma("unroll 1") while (__any_sync(0xffffffffu, (int)(ld_rlx(p) - target) < 0)) spin_guard(n);
  asm volatile("fence.acquire.gpu;" ::: "memory");
  asm volatile("fence.proxy.async.global;" ::: "memory");
}
DEVI void bulk_s2g(void* dst, uint32_t src, uint32_t bytes) {
  asm volatile("cp.async.bulk.global.shared::cta.bulk_group [%0], [%1], %2;" ::"l"(dst), "r"(src), "r"(bytes) : "memory");
}
#define ABL 0
DEVI void l2_prefetch(const void* p, uint32_t bytes) { if (!(ABL & 2)) asm volatile("cp.async.bulk.prefetch.L2.global [%0], %1;" ::"l"(p), "r"(bytes) : "memory"); }
DEVI void fence_async_smem() { asm volatile("fence.proxy.async.shared::cta;" ::: "memory"); }
DEVI void tma2(uint32_t dst, const CUtensorMap* m, int c0, int c1, uint32_t bar) {
  asm volatile("cp.async.bulk.tensor.2d.shared::cluster.global.mbarrier::complete_tx::bytes [%0], [%1, {%3,%4}], [%2];" ::"r"(dst),
               "l"(m), "r"(bar), "r"(c0), "r"(c1) : "memory");
}
DEVI void stsm4(uint32_t a, uint32_t r0, uint32_t r1, uint32_t r2, uint32_t r3) {
  asm volatile("stmatrix.sync.aligned.m8n8.x4.shared.b16 [%0], {%1,%2,%3,%4};" ::"r"(a), "r"(r0), "r"(r1), "r"(r2), "r"(r3) : "memory");
}
DEVI void stsm2(uint32_t a, uint32_t r0, uint32_t r1) {
  asm volatile("stmatrix.sync.aligned.m8n8.x2.shared.b16 [%0], {%1,%2};" ::"r"(a), "r"(r0), "r"(r1) : "memory");
}
DEVI uint32_t mbar_test(uint32_t b, uint32_t ph) {
  uint32_t ok;
  asm volatile("{\n.reg .pred p;\nmbarrier.test_wait.parity.shared::cta.b64 p, [%1], %2;\nselp.u32 %0,1,0,p;\n}\n"
               : "=r"(ok) : "r"(b), "r"(ph) : "memory");
  return ok;
}
DEVI void st_rlx2(void* p, uint32_t a, uint32_t b) {
  asm volatile("{\n.reg .b64 v;\nmov.b64 v, {%1,%2};\nst.relaxed.gpu.global.b64 [%0], v;\n}\n" ::"l"(p), "r"(a), "r"(b) : "memory");
}
DEVI float selp(int c, float a, float b) {
  float y;
  asm("{\n.reg .pred p;\nsetp.ne.s32 p, %3, 0;\nselp.f32 %0, %1, %2, p;\n}\n" : "=f"(y) : "f"(a), "f"(b), "r"(c));
  return y;
}
DEVI float ex2(float x) { float y; asm("ex2.approx.ftz.f32 %0, %1;" : "=f"(y) : "f"(x)); return y; }
DEVI float rcp(float x) { float y; asm("rcp.approx.ftz.f32 %0, %1;" : "=f"(y) : "f"(x)); return y; }
DEVI float sqrt_a(float x) { float y; asm("sqrt.approx.ftz.f32 %0, %1;" : "=f"(y) : "f"(x)); return y; }
DEVI void ldsm4t(uint32_t* r, uint32_t a) {
  asm volatile("ldmatrix.sync.aligned.m8n8.x4.trans.shared.b16 {%0,%1,%2,%3}, [%4];"
               : "=r"(r[0]), "=r"(r[1]), "=r"(r[2]), "=r"(r[3]) : "r"(a) : "memory");
}
DEVI void ldsm4(uint32_t* r, uint32_t a) {
  asm volatile("ldmatrix.sync.aligned.m8n8.x4.shared.b16 {%0,%1,%2,%3}, [%4];"
               : "=r"(r[0]), "=r"(r[1]), "=r"(r[2]), "=r"(r[3]) : "r"(a) : "memory");
}
DEVI uint32_t lds16(uint32_t a) {
  uint32_t v;
  asm volatile("ld.shared.u16 %0, [%1];" : "=r"(v) : "r"(a) : "memory");
  return v;
}
DEVI void sts16(uint32_t a, uint32_t x) { asm volatile("st.shared.u16 [%0], %1;" ::"r"(a), "r"(x) : "memory"); }
DEVI uint4 ldg128(const void* p) {
  uint4 v;
  asm volatile("ld.global.nc.v4.u32 {%0,%1,%2,%3}, [%4];" : "=r"(v.x), "=r"(v.y), "=r"(v.z), "=r"(v.w) : "l"(p));
  return v;
}
DEVI uint2 ldg64(const void* p) {
  uint2 v;
  asm volatile("ld.global.nc.v2.u32 {%0,%1}, [%2];" : "=r"(v.x), "=r"(v.y) : "l"(p));
  return v;
}
DEVI uint32_t ldg32(const void* p) {
  uint32_t v;
  asm volatile("ld.global.nc.u32 %0, [%1];" : "=r"(v) : "l"(p));
  return v;
}
DEVI uint4 ldcg128(const void* p) {
  uint4 v;
  asm volatile("ld.global.cg.v4.u32 {%0,%1,%2,%3}, [%4];" : "=r"(v.x), "=r"(v.y), "=r"(v.z), "=r"(v.w) : "l"(p) : "memory");
  return v;
}
DEVI uint2 ldcg64(const void* p) {
  uint2 v;
  asm volatile("ld.global.cg.v2.u32 {%0,%1}, [%2];" : "=r"(v.x), "=r"(v.y) : "l"(p) : "memory");
  return v;
}
DEVI uint32_t ldcg32(const void* p) {
  uint32_t v;
  asm volatile("ld.global.cg.u32 %0, [%1];" : "=r"(v) : "l"(p) : "memory");
  return v;
}
DEVI void stg128(void* p, uint32_t a, uint32_t b, uint32_t c, uint32_t d) {
  asm volatile("st.global.v4.u32 [%0], {%1,%2,%3,%4};" ::"l"(p), "r"(a), "r"(b), "r"(c), "r"(d) : "memory");
}
DEVI void stg32(void* p, uint32_t a) { asm volatile("st.global.u32 [%0], %1;" ::"l"(p), "r"(a) : "memory"); }
DEVI uint4 lds128(uint32_t a) {
  uint4 v;
  asm volatile("ld.shared.v4.u32 {%0,%1,%2,%3}, [%4];" : "=r"(v.x), "=r"(v.y), "=r"(v.z), "=r"(v.w) : "r"(a) : "memory");
  return v;
}
DEVI uint2 lds64(uint32_t a) {
  uint2 v;
  asm volatile("ld.shared.v2.u32 {%0,%1}, [%2];" : "=r"(v.x), "=r"(v.y) : "r"(a) : "memory");
  return v;
}
DEVI uint32_t lds32(uint32_t a) {
  uint32_t v;
  asm volatile("ld.shared.u32 %0, [%1];" : "=r"(v) : "r"(a) : "memory");
  return v;
}
DEVI void lds64f_if(bool p, float& a, float& b, uint32_t addr) {
  asm volatile("{\n.reg .pred p;\nsetp.ne.u32 p, %3, 0;\n@p ld.shared.v2.f32 {%0,%1}, [%2];\n}\n"
               : "+f"(a), "+f"(b) : "r"(addr), "r"((uint32_t)p) : "memory");
}
DEVI float ldsf(uint32_t a) { return __uint_as_float(lds32(a)); }
DEVI void sts128(uint32_t a, uint32_t x, uint32_t y, uint32_t z, uint32_t w) {
  asm volatile("st.shared.v4.u32 [%0], {%1,%2,%3,%4};" ::"r"(a), "r"(x), "r"(y), "r"(z), "r"(w) : "memory");
}
DEVI void sts64(uint32_t a, uint32_t x, uint32_t y) { asm volatile("st.shared.v2.u32 [%0], {%1,%2};" ::"r"(a), "r"(x), "r"(y) : "memory"); }
DEVI void sts32(uint32_t a, uint32_t x) { asm volatile("st.shared.u32 [%0], %1;" ::"r"(a), "r"(x) : "memory"); }
DEVI void stsf(uint32_t a, float x) { sts32(a, __float_as_uint(x)); }
DEVI uint32_t packbf(float lo, float hi) {
  uint32_t r;
  asm("cvt.rn.bf16x2.f32 %0, %1, %2;" : "=r"(r) : "f"(hi), "f"(lo));
  return r;
}
DEVI uint32_t nz(uint32_t w) { uint32_t y; asm("max.u32 %0, %1, 1;" : "=r"(y) : "r"(w)); return y; }
DEVI float blo(uint32_t w) { return __uint_as_float(w << 16); }
DEVI float bhi(uint32_t w) { return __uint_as_float(w & 0xffff0000u); }
DEVI float rbf(float x) { return __uint_as_float(packbf(0.f, x)); }
DEVI float shx(float v, int m) { return __shfl_xor_sync(0xffffffffu, v, m); }
DEVI float quad_sum(float v) { v += shx(v, 1); v += shx(v, 2); return v; }
DEVI uint32_t movm(uint32_t a) {
  uint32_t d;
  asm volatile("movmatrix.sync.aligned.m8n8.trans.b16 %0, %1;" : "=r"(d) : "r"(a));
  return d;
}
DEVI void mma16(float* d, uint32_t a0, uint32_t a1, uint32_t a2, uint32_t a3, uint32_t b0, uint32_t b1) {
  asm("mma.sync.aligned.m16n8k16.row.col.f32.bf16.bf16.f32 {%0,%1,%2,%3},{%4,%5,%6,%7},{%8,%9},{%0,%1,%2,%3};"
      : "+f"(d[0]), "+f"(d[1]), "+f"(d[2]), "+f"(d[3])
      : "r"(a0), "r"(a1), "r"(a2), "r"(a3), "r"(b0), "r"(b1));
}
DEVI void mma8z(float* d, uint32_t a0, uint32_t a1, uint32_t b0) {
  asm("mma.sync.aligned.m16n8k8.row.col.f32.bf16.bf16.f32 {%0,%1,%2,%3},{%4,%5},{%6},{%7,%7,%7,%7};"
      : "=f"(d[0]), "=f"(d[1]), "=f"(d[2]), "=f"(d[3])
      : "r"(a0), "r"(a1), "r"(b0), "f"(0.f));
}
DEVI void mma8(float* d, uint32_t a0, uint32_t a1, uint32_t b0) {
  asm("mma.sync.aligned.m16n8k8.row.col.f32.bf16.bf16.f32 {%0,%1,%2,%3},{%4,%5},{%6},{%0,%1,%2,%3};"
      : "+f"(d[0]), "+f"(d[1]), "+f"(d[2]), "+f"(d[3])
      : "r"(a0), "r"(a1), "r"(b0));
}
DEVI void mma16z(float* d, uint32_t a0, uint32_t a1, uint32_t a2, uint32_t a3, uint32_t b0, uint32_t b1) {
  asm("mma.sync.aligned.m16n8k16.row.col.f32.bf16.bf16.f32 {%0,%1,%2,%3},{%4,%5,%6,%7},{%8,%9},{%10,%10,%10,%10};"
      : "=f"(d[0]), "=f"(d[1]), "=f"(d[2]), "=f"(d[3])
      : "r"(a0), "r"(a1), "r"(a2), "r"(a3), "r"(b0), "r"(b1), "f"(0.f));
}
DEVI void mma16a(float* d, const uint32_t* a, uint32_t b0, uint32_t b1) { mma16(d, a[0], a[1], a[2], a[3], b0, b1); }
DEVI float ln_sd(float var) { return rbf(sqrt_a(rbf(rbf(var) + kEps))); }
DEVI int fkey(float f) { int i = __float_as_int(f); return i ^ ((i >> 31) & 0x7fffffff); }
DEVI float sigmoidf(float x) { return rcp(1.f + ex2(-1.4426950408889634f * x)); }

DEVI uint32_t probe_stage(uint32_t pa) { return lds32(pa); }
DEVI void check_stage(uint32_t pv, uint32_t fa, const uint8_t* src) {
  if (__any_sync(0xffffffffu, pv == 0)) {
    uint32_t n = 0, tid;
    asm volatile("mov.u32 %0, %%tid.x;" : "=r"(tid));
    const uint32_t fo = (tid & 96) * 8 + (tid & 16) * 64 + (tid & 15) * 16;
    fa += fo; src += fo;
#pragma unroll 1
    for (uint32_t o = 0; o < 8192;) {
      const uint4 v = ld_msg(src + o);
      sts128(fa + o, v.x, v.y, v.z, v.w);
      if (!__any_sync(0xffffffffu, min(min(v.x, v.y), min(v.z, v.w)) == 0) || ++n > (1u << 16)) o += 2048;
    }
    fence_async_smem();
    __syncwarp();
  }
}

struct Params {
  const uint8_t *x, *wqkv, *wo, *wr, *wg, *wu, *wd;
  uint8_t* out;
  Scratch* g;
};

struct Maps { CUtensorMap wq, x, wo, xr, wg, wu, out; };
#define QPRE 2
#define FDEPTH 2
#define PFSTART 700
#define PFPRE 0
#define PFPER 3
#define PFNS 200
#define XSTART 100
#define XSTEP 300
#define PKSTEP 350
#define WPOLL 300
#define CSROUND 0
#define XLROUND 0
#define CLNS 20
#define FSTART 4000
#define XLSTART 3000
#define WGAP0 0
#define XGAP 150
#define OGAP 100
#define WDGAP 10
#define WR0 5
#define WR1 3
#define WR2 6
#define WEARLY 1

__global__ void __cluster_dims__(2, 1, 1) __launch_bounds__(512, 1) fused_kernel(const Params p, const __grid_constant__ Maps tm) {
  extern __shared__ __align__(1024) uint8_t smem_raw[];
  constexpr uint32_t sbd = 1024;
  int cta;
  uint32_t rank;
  {
    asm volatile("mov.u32 %0, %%cluster_ctarank;" : "=r"(rank));
    uint32_t sm;
    asm volatile("mov.u32 %0, %%smid;" : "=r"(sm));
    const int t = sm >> 1, u = t - 32, uq = (u * 37) >> 8;
    const int gpc = t < 32 ? t & 7 : t < 60 ? 1 + u - 7 * uq : 0, idx = t < 32 ? t >> 3 : t < 60 ? 4 + uq : t - 58;
    const int c = blockIdx.x >> 1;
    const int pair = gridDim.x != 132 ? 16 * (c >> 3) + (c & 7) : (t == 60 || t == 61) ? 128 : 16 * gpc + idx;
    cta = __shfl_sync(0xffffffffu, pair + 8 * (int)rank, 0);
  }
  const uint32_t sb = sbd | (rank << 24);
  if ((uint32_t)__cvta_generic_to_shared(smem_raw) != sb) return;
  if (threadIdx.x < 27) asm volatile("prefetch.global.L2 [%0];" ::"l"(p.wqkv + blockIdx.x * 3456 + threadIdx.x * 128));
  const int m = cta >> 3, r = cta & 7;
  const int warp = __shfl_sync(0xffffffffu, (int)(threadIdx.x >> 5), 0);
  const int lane = threadIdx.x & 31;
  uint8_t* const gb = reinterpret_cast<uint8_t*>(p.g);
  if (cta >= 128) {
    if (warp < 4) {
      const uint32_t e = ld_rlx(GA(epoch, 0)) + 1;
      __nanosleep(4000);
      wait_flags(GA(flagX, 256 * (4 * warp + (lane >> 3))), 4 * (lane & 7), e * 4);
    }
    return;
  }
  auto pack = [&]() -> uint32_t {
    const uint32_t t0 = clock();
    const uint32_t tp = sb + SM_WD + warp * 2304, bar = sb + SM_PART + 8 * warp;
    uint8_t* flag = GA(flagP, (12 * r + warp) * 128 + 4 * m);
    if (warp > 1) {
      asm volatile("bar.sync 4, 512;" ::: "memory");
      cluster_arrive();
      while ((uint32_t)clock() - t0 < (warp - 1) * PKSTEP) {}
    }
    if (elect()) {
      mbar_init(bar, 1);
      asm volatile("fence.mbarrier_init.release.cluster;" ::: "memory");
      mbar_expect(bar, 2304);
      if (warp < 9) tma3(tp, &tm.wq, 72 * r, 64 * warp + 8 * (m >> 1), m & 1, bar);
      else tma2(tp, &tm.wo, 72 * r, 192 * (warp - 9) + 24 * (m >> 1) + 8 * (m & 1), bar);
    }
    __syncwarp();
    if (lane == 0) st_rlx(flag, 0);
    if (warp <= 1) { asm volatile("bar.sync 4, 512;" ::: "memory"); cluster_arrive(); }
    mbar_wait(sb + B_EP, 0);
    const uint32_t epoch = lds32(sb + SM_EP);
    uint8_t* dst = GC(wpack, (r * 12 + warp) * WSTAGE + (27 * (m >> 1) + 14 * (m & 1)) * 128 + lane * 16);
    mbar_wait(bar, 0);
#pragma unroll
    for (int i = 0; i < 4; i++) {
      const int u = 4 * i + (lane >> 3) + 5 * (m & 1);
      const uint4 x = lds128(tp + (lane & 7) * 144 + u * 16 + (u >= 9 ? 1008 : 0));
      if (u < 14 + 4 * (m & 1)) stg128(dst + 512 * i, nz(x.x), nz(x.y), nz(x.z), nz(x.w));
    }
    if (lane == 0) st_rlx(flag, epoch);
    fence_async_smem();
    __syncwarp();
    if (elect()) asm volatile("mbarrier.inval.shared::cta.b64 [%0];" ::"r"(bar) : "memory");
    cluster_wait();
    return epoch;
  };

  if (warp >= 12) {
    asm volatile("setmaxnreg.dec.sync.aligned.u32 24;");
    uint32_t e0 = 0;
    if (elect()) {
#pragma unroll
      for (int i = 0; i < NBAR; i++)
        if (warp - 12 == (i * 4) / NBAR)
          mbar_init(sb + SM_BAR + 8 * i, i < 4 ? 1 : i < 8 ? 16 : i < 16 ? 2 : i < NBAR4 ? 4 : 1);
      asm volatile("fence.mbarrier_init.release.cluster;" ::: "memory");
    }
    __syncwarp();
    if (warp == 15) asm volatile("bar.arrive 4, 512;" ::: "memory");
    else asm volatile("bar.sync 4, 512;" ::: "memory");
    cluster_arrive();
    if (warp == 15) e0 = ld_rlx(GA(epoch, 32 * cta));
    if (warp == 12) {
      mbar_wait(sb + B_EP, 0);
      cluster_wait();
      const uint32_t epoch = lds32(sb + SM_EP);
      const uint32_t half = (m & 1) * (WSTAGE / 2);
      const uint8_t* src = GC(wpack, r * 12 * WSTAGE + half);
      __nanosleep(WPOLL);
#pragma unroll 1
      for (int g = 0; g < 24; g++) {
        const uint32_t slot = g & 3;
        if (g < 12) wait_flags(GA(flagP, (12 * r + g) * 128), lane & 15, epoch);
        if (g == 0) TRL(3, 0);
        if (g >= 4) mbar_wait(sb + B_WEMPTY + 8 * slot, ((g >> 2) - 1) & 1);
        if (elect()) {
          const uint32_t bar = sb + (g < 12 ? B_WL : B_WFULL) + 8 * slot;
          mbar_expect(bar, WSTAGE);
          bulk_g2s_pair(sb + SM_W + slot * WSTAGE + half, src + (g >= 12 ? g - 12 : g) * WSTAGE, WSTAGE / 2, bar);
        }
      }
    } else if (warp <= 14) {
      const int w = warp - 13;
      const uint32_t full = sb + B_XFULL + 32 * w, empty = sb + B_XEMPTY + 32 * w, ring = sb + SM_X + w * 4 * XSTAGE;
      mbar_wait(sb + B_EP, 0);
      cluster_wait();
      const uint32_t epoch = lds32(sb + SM_EP);
      if (lane < 4) st_rlx(GA(flagX, 128 * (2 * m + w) + 16 * r + 4 * lane), epoch * 4);
#pragma unroll 1
      for (int gemm = 0; gemm < 4; gemm++) {
        const uint8_t* src = GC(act, (gemm - 1) * ACT + (2 * m + w) * 73728);
        if (gemm & 1) {
          mbar_wait(empty, 0);
          if (elect()) {
            mbar_expect(sb + B_RES + 8 * w, 9216);
            if (gemm == 1) tma3(ring, &tm.xr, 72 * r, w, m * 64, sb + B_RES + 8 * w);
            else bulk_g2s(ring, GC(act, ACT + (2 * m + w) * 73728 + r * 9216), 9216, sb + B_RES + 8 * w);
          }
        }
        if (gemm > 0) {
          mbar_wait(gemm & 1 ? sb + B_RC + 8 * w : empty, gemm & 1 ? gemm >> 1 : 1);
          TRL(3, 11 + w * 4 + gemm);
          wait_flags(GA(flagX, 128 * (2 * m + w)), lane, epoch * 4 + gemm);
          TRL(3, 1 + w * 4 + gemm);
        }
        if (gemm & 1) {
          if (elect()) {
#pragma unroll
            for (int s = 0; s < 9; s++) {
              if (s > 0 && s < 5) { const uint32_t t1 = clock(); while ((uint32_t)clock() - t1 < OGAP) {} }
              if (s == 4) {
                mbar_wait(sb + B_RC + 8 * (w ^ 1), gemm >> 1);
                mbar_expect(sb + B_XE + 8 * w, XSTAGE);
                bulk_g2s(sb + SM_W + w * XSTAGE, src + 4 * XSTAGE, XSTAGE, sb + B_XE + 8 * w);
                continue;
              }
              const int sl = s < 4 ? s : s - 5;
              if (s >= 5) mbar_wait(empty + 8 * sl, s == 5);
              mbar_expect(full + 8 * sl, XSTAGE);
              bulk_g2s(ring + sl * XSTAGE, src + s * XSTAGE, XSTAGE, full + 8 * sl);
              mbar_arrive(full + 8 * sl);
            }
            mbar_wait(empty, 0);
            mbar_arrive(full);
            mbar_arrive(full);
          }
          __syncwarp();
          continue;
        }
        bool gate = gemm == 2;
#pragma unroll 1
        for (int s = 0; s < (gemm == 2 ? 11 : 9); s++) {
          const uint32_t slot = s & 3;
          if (gemm == 0 && s < 4) __nanosleep(s ? XSTEP : XSTART);
          if (gemm == 2 && s > 0 && s < 4) __nanosleep(XGAP);
          if (s >= 4) mbar_wait(empty + 8 * slot, s >> 3);
          const bool hold = gate && s >= 4 && mbar_test(sb + B_WANT, 0);
          if (lane == 0 && !hold && (gemm != 2 || (s & ~1) != 2)) mbar_arrive(full + 8 * (gemm == 2 && s >= 4 ? (s - 2) & 3 : slot));
          if (s < 9 && elect()) {
            mbar_expect(full + 8 * slot, XSTAGE);
            if (gemm == 0) tma3(ring + slot * XSTAGE, &tm.x, s * 64, w, m * 64, full + 8 * slot);
            else bulk_g2s(ring + slot * XSTAGE, src + s * XSTAGE, XSTAGE, full + 8 * slot);
          }
          if (hold) {
            mbar_wait(sb + B_DONE, 0);
            gate = false;
            if (lane == 0) mbar_arrive(full + 8 * ((s - 2) & 3));
          }
        }
      }
    } else {
      const uint32_t epoch = e0 + 1;
      if (lane == 0) {
        sts32(sb + SM_EP, epoch);
        mbar_arrive(sb + B_EP);
      }
      __syncwarp();
      cluster_wait();
      int pi = lane;
      auto prefetch = [&]() {
        const uint8_t* pp = pi < 648 ? ((cta & 1) ? p.wu : p.wg) + (uint32_t)(((pi / 72) * 63 + (cta >> 1)) * 9216 + pi * 128)
                                     : p.wd + (uint32_t)((cta * 324 + pi - 648) * 128);
        if (pi < 972 && !(ABL & 2)) asm volatile("prefetch.global.L2 [%0];" ::"l"(pp));
        pi += 32;
      };
      __nanosleep(PFSTART);
#pragma unroll 1
      for (int i = 0; i < PFPRE; i++) { prefetch(); __nanosleep(PFNS); }
      uint32_t ph = 0;
#pragma unroll 1
      for (int g = 0; g < 12; g++) {
        const uint32_t slot = g & 3;
#pragma unroll 1
        for (int n = 0; n < 4096; n++) {
          mbar_wait(sb + B_WL + 8 * slot, (ph >> slot) & 1);
          ph ^= 1 << slot;
          const uint32_t a = sb + SM_W + slot * WSTAGE + lane * 128 + (lane & 3) * 32 + (lane >> 2) * 4;
          uint32_t mn = lds32(a + (lane < 24 ? 6 * 4096 : 0));
#pragma unroll
          for (int u = 0; u < 6; u++) mn = min(mn, lds32(a + u * 4096));
          if (!__any_sync(0xffffffffu, mn == 0) || (ABL & 32)) break;
          fence_async_smem();
          __syncwarp();
          if (elect()) {
            mbar_expect(sb + B_WL + 8 * slot, WSTAGE);
            bulk_g2s(sb + SM_W + slot * WSTAGE, GC(wpack, (r * 12 + g) * WSTAGE), WSTAGE, sb + B_WL + 8 * slot);
          }
        }
        if (lane == 0) mbar_arrive(sb + B_WFULL + 8 * slot);
#pragma unroll 1
        for (int i = 0; i < PFPER; i++) prefetch();
      }
      TRL(3, 22);
      mbar_wait(sb + B_FD, 0);
      TRL(3, 20);
      if (elect()) {
        mbar_expect(sb + B_WD, (ABL & 64) ? 0 : 41472);
#pragma unroll 4
        for (int i = 0; i < 36; i++) {
          { const uint32_t t1 = clock(); while ((uint32_t)clock() - t1 < WDGAP) {} }
          if (!(ABL & 64)) bulk_g2s(sb + SM_WD + i * WDP, p.wd + (uint32_t)(cta * 36 + i) * 1152u, 1152, sb + B_WD);
        }
      }
      __syncwarp();
      TRL(3, 21);
      {
        const uint32_t epoch = e0, h = (lane >> 1) * 128 + (lane & 1) * 16;
        mbar_wait(sb + B_IDX, 0);
#pragma unroll 1
        for (int i = cta; i < 1296; i += 128) { stg128(GC(wpack, i * 2048 + (lane & 6) * 16 + h), 0, 0, 0, 0); __nanosleep(CLNS); }
#pragma unroll 1
        for (int i = 0; i < 5; i++) {
          stg128(GC(halo, (cta * 5 + i) * 2048 + h), 0, 0, 0, 0);
          if (i < 4 || lane < 16) stg128(GC(candrow, cta * 2304 + i * 512 + lane * 16), 0, 0, 0, 0);
          stg128(GC(act, (cta * 27 + i) * 2048 + 96 + h), 0, 0, 0, 0);
          __nanosleep(CLNS);
        }
        mbar_wait(sb + B_EPI, 1);
#pragma unroll 1
        for (int i = 5; i < 27; i++) { stg128(GC(act, (cta * 27 + i) * 2048 + 96 + h), 0, 0, 0, 0); __nanosleep(CLNS); }
      }
      TRL(3, 23);
    }
  } else if (warp >= 8) {
    asm volatile("setmaxnreg.inc.sync.aligned.u32 200;");
    const int sw = warp - 8, s = threadIdx.x - 256;
    const uint32_t t0 = clock();
    const uint32_t epoch = pack();
    TR(2, 0);
    auto ffn_round = [&](int u) {
      const uint32_t bar = sb + B_FF + 8 * (u % FDEPTH), dst = sb + SM_WD + (u % FDEPTH) * FSLOT;
      if (ABL & 4) { mbar_arrive(bar); return; }
      mbar_expect(bar, 12288);
      tma2(dst, &tm.wg, ((cta * 72) >> 5) << 4, 64 * u, bar);
      tma2(dst + FSLOT / 2, &tm.wu, ((cta * 72) >> 5) << 4, 64 * u, bar);
    };
    const int xi = 8 * r + 4 * (sw >> 1) + (lane >> 3);
    uint4 xv[9];
    uint32_t wr[9];
        {
          const uint8_t* xsrc = p.x + (uint32_t)((128 * m + 2 * xi + (sw & 1)) * 1152 + (lane & 7) * 16);
#pragma unroll
          for (int u = 0; u < 9; u++) xv[u] = ldg128(xsrc + u * 128);
#pragma unroll
          for (int u = 0; u < 9; u++) wr[u] = sw == 0 ? ldg32(p.wr + 128 * u + 4 * lane) : 0u;
        }
    {
      asm volatile("bar.sync 15, 384;" ::: "memory");
      const int u = (s >> 3) + 5 * (m & 1);
      uint4 v[9];
#pragma unroll
      for (int g = 0; g < 9; g++) v[g] = lds128(sb + SM_WD + g * 2304 + u * 16 + (u >= 9 ? 1008 : 0) + (s & 7) * 144);
      fence_async_smem();
      bar_sync(3);
      if (sw == 0) {
        while ((uint32_t)clock() - t0 < FSTART) {}
        if (elect()) {
#pragma unroll
          for (int u = 0; u < FDEPTH; u++) ffn_round(u);
        }
        __syncwarp();
      }
      float a[8] = {};
#pragma unroll
      for (int g = 0; g < 9; g++) {
        a[0] += blo(v[g].x); a[1] += bhi(v[g].x); a[2] += blo(v[g].y); a[3] += bhi(v[g].y);
        a[4] += blo(v[g].z); a[5] += bhi(v[g].z); a[6] += blo(v[g].w); a[7] += bhi(v[g].w);
      }
      const bool b4 = s & 4, b2 = s & 2;
      float b[4];
#pragma unroll
      for (int e = 0; e < 4; e++) b[e] = (b4 ? a[4 + e] : a[e]) + shx(b4 ? a[e] : a[4 + e], 4);
      float c0 = (b2 ? b[2] : b[0]) + shx(b2 ? b[0] : b[2], 2), c1 = (b2 ? b[3] : b[1]) + shx(b2 ? b[1] : b[3], 2);
      c0 += shx(c0, 1); c1 += shx(c1, 1);
      if (!(s & 1) && (s >> 3) < 14 - (m & 1))
        st_rlx2(GA(colpart, (8 * r + (m >> 1)) * 864 + 14 * (m & 1) * 32 + 4 * s), __float_as_uint(c0), (__float_as_uint(c1) & ~15u) | (epoch & 15));
      TR(2, 1);
    }
        {
          float sum = 0.f;
#pragma unroll
          for (int u = 0; u < 9; u++)
            sum += (blo(xv[u].x) + bhi(xv[u].x)) + (blo(xv[u].y) + bhi(xv[u].y)) + (blo(xv[u].z) + bhi(xv[u].z)) + (blo(xv[u].w) + bhi(xv[u].w));
          sum += shx(sum, 1); sum += shx(sum, 2); sum += shx(sum, 4);
          const float mu = sum * (1.f / kD);
          float q = 0.f;
#pragma unroll
          for (int u = 0; u < 9; u++) {
            const uint32_t ww[4] = {xv[u].x, xv[u].y, xv[u].z, xv[u].w};
#pragma unroll
            for (int e = 0; e < 4; e++) {
              const float d0 = blo(ww[e]) - mu, d1 = bhi(ww[e]) - mu;
              q = fmaf(d0, d0, q); q = fmaf(d1, d1, q);
            }
          }
          q += shx(q, 1); q += shx(q, 2); q += shx(q, 4);
          const float rho = rcp(ln_sd(q * (1.f / kD)));
          if ((lane & 7) == 0) st_msg(GA(stats0, 16 * (128 * m + 64 * (sw & 1) + xi)), __float_as_uint(rho), __float_as_uint(mu), 0, epoch);
          if (sw == 0) {
            float wsum = 0.f;
#pragma unroll
            for (int u = 0; u < 9; u++) wsum += blo(wr[u]) + bhi(wr[u]);
#pragma unroll
            for (int o = 1; o < 32; o <<= 1) wsum += shx(wsum, o);
            if (lane == 0) stsf(sb + SM_WSUM, wsum);
          }
          TR(2, 3);
        }
    uint32_t WF[9][4][4];
    {
      const int g = lane >> 2, t = lane & 3;
      const uint32_t c0 = (cta * 72) & 31, ra = 2 * (lane & 6) + (lane & 1) + 2 * ((lane >> 4) ^ ((lane >> 2) & 1));
      const uint32_t fa = sb + SM_WD + (16 * sw + ra) * 128 + ((((c0 + 8) >> 4) + ((lane >> 3) & 1)) << 4);
      const uint32_t fa0 = fa ^ ((ra & 7) << 4), fa1 = (fa + 32) ^ ((ra & 7) << 4);
      const uint32_t rl = 2 * (g & 6) + (g & 1) + 2 * (g >> 2);
      const uint32_t fl = sb + SM_WD + 16 * sw * 128 + (t >> 1) * (FSLOT / 2) + c0 + 64 * (~cta & 1) + 4 * (t & 1);
      const uint32_t fl0 = (fl + rl * 128) ^ ((rl & 7) << 4), fl1 = (fl + (rl ^ 2) * 128) ^ (((rl ^ 2) & 7) << 4);
#pragma unroll
      for (int i = 0; i < 9; i++) {
        mbar_wait(sb + B_FF + 8 * (i % FDEPTH), (i / FDEPTH) & 1);
#pragma unroll
        for (int e = 0; e < 4; e++) ldsm4t(WF[i][e], ((e & 1) ? fa1 : fa0) + (e >> 1) * (FSLOT / 2) + (i % FDEPTH) * FSLOT);
        const uint32_t v0 = lds32(fl0 + (i % FDEPTH) * FSLOT), v1 = lds32(fl1 + (i % FDEPTH) * FSLOT);
        if (i + FDEPTH < 9 || i == 8) {
          fence_async_smem();
          bar_sync(3);
          if (sw == 0 && elect()) {
            if (i < 8) ffn_round(i + FDEPTH);
            else mbar_arrive(sb + B_FD);
          }
        }
        sts64(sb + SM_LEFT + i * 1024 + s * 8, movm(v0), movm(v1));
        if (i == CSROUND) {
          TR(2, 21);
          float c0, c1;
          uint4 s0;
          uint32_t nc = 0;
          _Pragma("unroll 1") while (true) {
            s0 = ld_msg(GA(stats0, 16 * (128 * m + s)));
            uint32_t bad = s0.w != epoch;
            c0 = 0.f; c1 = 0.f;
#pragma unroll
            for (int mm = 0; mm < 8; mm++) {
              const uint2 v = ld_rlx2(GA(colpart, 8 * 864 * r + 8 * min(s, 107)) + mm * 864);
              c0 += __uint_as_float(v.x); c1 += __uint_as_float(v.y & ~15u);
              bad |= v.y ^ epoch;
            }
            if (!__any_sync(0xffffffffu, bad & 15)) break;
            spin_guard(nc);
          }
          if (s < 108) {
            const uint32_t hi = packbf(c0, c1);
            sts32(sb + SM_COLSUM + 32 * (s >> 2) + 4 * (s & 3), hi);
            sts32(sb + SM_COLSUM + 32 * (s >> 2) + 4 * (s & 3) + 16, packbf(c0 - blo(hi), c1 - bhi(hi)));
          }
          sts32(sb + SM_ROWC + 4 * s, s0.x);
          sts64(sb + SM_ROWM + 8 * s, s0.y, __float_as_uint(1.f));
          fence_async_smem();
          __syncwarp();
          if (lane == 0) mbar_arrive(sb + B_COLSUM);
          TR(2, 13);
        }
      }
      TR(2, 4);
    }
    {
      mbar_wait(sb + B_OS, 0);
      const uint32_t y = epoch * 2 - 1;
      st_msg(GA(ypart, (s >> 1) * 4096 + cta * 32 + (s & 1) * 16), y, y, y, y);
      if (s < 16) {
        st_msg(GA(ypart, (64 + (s >> 1)) * 4096 + cta * 32 + (s & 1) * 16), y, y, y, y);
        st_rlx(GA(fixmsg, 1024 * r + 64 * m + 4 * s), epoch - 1);
      }
      if (s < 64 && cta < 72) st_rlx(GA(x2msg, (s >> 3) * 2304 + 32 * cta + 4 * (s & 7)), epoch - 1);
    }
#pragma unroll 1
    for (int L = 0; L < 2; L++) {
      const uint32_t tag = epoch * 2 + L;
      int s0 = __shfl_sync(0xffffffffu, (int)threadIdx.x + L, threadIdx.x & 31) - L - 256;
#define RELANE asm volatile("" : "+r"(s0)); const int s = s0, lane = s & 31, g = lane >> 2, t = lane & 3; (void)g; (void)t
      RELANE;
      const uint8_t* crow = GC(candrow, L * 128 * 1152);
      const uint8_t* cptr = GA(cand, (8 * L + r) * 2048 + 16 * s);
      asm volatile("" : "+l"(crow), "+l"(cptr));
      mbar_wait2(sb + B_WD, 0, sb + B_EPI, L);
      uint32_t win;
      {
        uint32_t c, n = 0;
        _Pragma("unroll 1") while (true) {
          c = ld_rlx(cptr) ^ (epoch & 0x7f);
          if (!__any_sync(0xffffffffu, c & 0x7f)) break;
          spin_guard(n);
        }
        const int wm = __reduce_max_sync(0xffffffffu, (int)(c | s));
        if (lane == 0) sts32(sb + SM_RED + 4 * sw, wm);
        bar_sync(3);
        const uint4 v = lds128(sb + SM_RED);
        win = max(max((int)v.x, (int)v.y), max((int)v.z, (int)v.w));
      }
      crow += (win & 127) * 1152;
      if (s == 0) {
        if (L == 0 && WEARLY) mbar_arrive(sb + B_WANT);
        sts32(sb + SM_SEL + 4 * L, win & 0x7ff);
        mbar_arrive(sb + B_IDX + 8 * L);
      }
      TR(2, 5 + 10 * L);
      uint2 xw[9];
      {
        if (sw < 3) {
          uint4 v;
          uint32_t n = 0;
          _Pragma("unroll 1") while (true) {
            v = ld_msg(crow + 16 * min(s, 71));
            if (!__any_sync(0xffffffffu, min(min(v.x, v.y), min(v.z, v.w)) == 0)) break;
            spin_guard(n);
          }
          if (s < 72) sts128(sb + SM_PART + 16 * s, v.x, v.y, v.z, v.w);
        }
        bar_sync(3);
#pragma unroll
        for (int i = 0; i < 9; i++) xw[i] = lds64(sb + SM_PART + 128 * i + 32 * sw + 8 * t);
      }
      if (L == 0 && !WEARLY && s == 0) mbar_arrive(sb + B_WANT);
      TR(2, 6 + 10 * L);
      {
        float a[4][4] = {}, al[4] = {};
#pragma unroll
        for (int i = 0; i < 9; i++) {
          const uint2 wl = lds64(sb + SM_LEFT + s * 8 + i * 1024);
#pragma unroll
          for (int e = 0; e < 4; e++) mma16a(a[e], WF[i][e], xw[i].x, xw[i].y);
          mma8(al, wl.x, wl.y, (g & 1) ? xw[i].y : xw[i].x);
        }
        bar_sync(3);
        const uint32_t pp = sb + SM_PART + ((t >> 1) * 36 + 16 * (t & 1) + g + 4 * (cta & 1)) * 16 + 4 * sw;
        stsf(pp, selp(t & 2, selp(t & 1, a[3][0], a[2][0]), selp(t & 1, a[1][0], a[0][0])));
        stsf(pp + 128, selp(t & 2, selp(t & 1, a[3][2], a[2][2]), selp(t & 1, a[1][2], a[0][2])));
        stsf(sb + SM_PART + ((g >> 2) * 36 + 32 * (~cta & 1) + (g & 3)) * 16 + 4 * sw, al[0] + al[3]);
      }
      {
        RELANE;
        const uint32_t wa = sb + SM_WD + 288 * sw + ((lane >> 3) & 1) * 16 + ((lane & 7) + 8 * (lane >> 4)) * WDP;
        const uint32_t wb = sb + SM_WD + 288 * sw + ((lane >> 3) & 1) * 16 + (32 + (lane & 3)) * WDP;
        uint32_t f[4][4];
#pragma unroll
        for (int u = 0; u < 4; u++) ldsm4t(f[u], wa + 32 * (u & 1) + (u >> 1) * 16 * WDP);
        bar_sync(3);
        {
          float hv[2];
#pragma unroll
          for (int e = 0; e < 2; e++) {
            const uint32_t pp = sb + SM_PART + 16 * (e ? 32 + t : lane);
            const uint4 pg = lds128(pp), pu = lds128(pp + 576);
            const float gp = rbf((__uint_as_float(pg.x) + __uint_as_float(pg.y)) + (__uint_as_float(pg.z) + __uint_as_float(pg.w)));
            const float u = rbf((__uint_as_float(pu.x) + __uint_as_float(pu.y)) + (__uint_as_float(pu.z) + __uint_as_float(pu.w)));
            hv[e] = rbf(gp * sigmoidf(gp)) * u;
          }
          const uint32_t hh = packbf(hv[0], hv[1]);
          sts16(sb + SM_H + 80 * sw + 2 * lane, hh);
          sts16(sb + SM_H + 80 * sw + 64 + 2 * t, hh >> 16);
          __syncwarp();
        }
        TR(2, 7 + 10 * L);
        uint32_t hp[5];
#pragma unroll
        for (int i = 0; i < 4; i++) hp[i] = lds32(sb + SM_H + 80 * sw + 16 * i + 4 * t);
        hp[4] = lds32(sb + SM_H + 80 * sw + 64 + 4 * (t & 1));
        float Y[4] = {}, Z[4] = {}, C[4] = {};
        {
          uint32_t e0[4], e1[4], e2[4];
          const uint32_t wq = wb + 32 * (((lane >> 2) & 1) + 2 * (lane >> 4));
          ldsm4t(e0, wq); ldsm4t(e1, wq + 128); ldsm4t(e2, wb + 256);
          mma16a(Y, e0, g == (t >> 1) ? hp[4] : 0u, g == 2 + (t >> 1) ? hp[4] : 0u);
          mma16a(Z, e1, g == 4 + (t >> 1) ? hp[4] : 0u, g == 6 + (t >> 1) ? hp[4] : 0u);
          mma8(C, e2[0], e2[1], t < 2 ? hp[4] : 0u);
        }
#pragma unroll
        for (int u = 0; u < 4; u++) {
          const uint32_t wn = wa + 64 * (u + 1);
          const bool p0 = g == 2 * u, p1 = g == 2 * u + 1;
          mma16a(Y, f[0], p0 ? hp[0] : 0u, p0 ? hp[1] : 0u);
          mma16a(Z, f[1], p1 ? hp[0] : 0u, p1 ? hp[1] : 0u);
          ldsm4t(f[0], wn);
          if (u < 3) ldsm4t(f[1], wn + 32);
          mma16a(Y, f[2], p0 ? hp[2] : 0u, p0 ? hp[3] : 0u);
          mma16a(Z, f[3], p1 ? hp[2] : 0u, p1 ? hp[3] : 0u);
          ldsm4t(f[2], wn + 16 * WDP);
          if (u < 3) ldsm4t(f[3], wn + 32 + 16 * WDP);
        }
        mma16a(C, f[0], hp[0], hp[1]);
        mma16a(C, f[2], hp[2], hp[3]);
#pragma unroll
        for (int e = 0; e < 4; e++) Y[e] += Z[e];
        const uint32_t t4 = tag & 15;
        {
          uint8_t* yo = GA(ypart, (18 * sw + 4 * t) * 4096 + cta * 32 + 4 * g);
#pragma unroll
          for (int e = 0; e < 4; e++) st_rlx(yo + (2 * (e & 1) + (e >> 1)) * 4096, (__float_as_uint(Y[e]) & ~15u) | t4);
          if (t < 2) st_rlx(yo + (16 - 3 * t) * 4096, (__float_as_uint(t ? C[2] : C[0]) & ~15u) | t4);
          if (L == 0 && lane == 0) mbar_arrive(sb + B_DONE);
        }
      }
      TR(2, 8 + 10 * L);
      if (cta < 72) {
        RELANE;
        const uint32_t xn = ld_rlx(GC(candrow, (L * 128 + (win & 127)) * 1152 + 16 * cta + 2 * ((s & 6) ^ (2 * (cta & 1)))));
        const uint4 cm = ld_msg(GA(cand, (8 * L + r) * 2048 + 16 * (win & 127)));
        const uint8_t* yp = GA(ypart, cta * 4096 + s * 16);
        uint4 u0, u1;
        uint32_t n = 0;
        _Pragma("unroll 1") while (true) {
          u0 = ld_msg(yp);
          u1 = ld_msg(yp + 2048);
          const uint32_t t4 = tag & 15;
          u0.x ^= t4; u0.y ^= t4; u0.z ^= t4; u0.w ^= t4; u1.x ^= t4; u1.y ^= t4; u1.z ^= t4; u1.w ^= t4;
          if (!__any_sync(0xffffffffu, (u0.x | u0.y | u0.z | u0.w | u1.x | u1.y | u1.z | u1.w) & 15)) break;
          spin_guard(n);
        }
        const float a0 = __uint_as_float(u0.x) + __uint_as_float(u1.x), a1 = __uint_as_float(u0.y) + __uint_as_float(u1.y);
        const float a2 = __uint_as_float(u0.z) + __uint_as_float(u1.z), a3 = __uint_as_float(u0.w) + __uint_as_float(u1.w);
        const bool b4 = lane & 4, b2 = lane & 2;
        const float c0 = (b4 ? a2 : a0) + shx(b4 ? a0 : a2, 4), c1 = (b4 ? a3 : a1) + shx(b4 ? a1 : a3, 4);
        float d = (b2 ? c1 : c0) + shx(b2 ? c0 : c1, 2);
        d += shx(d, 8);
        if (!(lane & 8)) stsf(sb + SM_RED + 32 * (4 * (lane & 1) + ((lane >> 1) & 3)) + 8 * sw + 4 * (lane >> 4), d);
        bar_sync(3);
        if (s < 64) {
          const uint4 p0 = lds128(sb + SM_RED + 32 * (s & 7)), p1 = lds128(sb + SM_RED + 32 * (s & 7) + 16);
          const float y = rbf(((__uint_as_float(p0.x) + __uint_as_float(p0.y)) + (__uint_as_float(p0.z) + __uint_as_float(p0.w))) +
                              ((__uint_as_float(p1.x) + __uint_as_float(p1.y)) + (__uint_as_float(p1.z) + __uint_as_float(p1.w))));
          const uint32_t v = packbf(0.f, fmaf((s & 1) ? bhi(xn) : blo(xn), __uint_as_float(cm.z), __uint_as_float(cm.w)) + rbf(y * __uint_as_float(cm.y)));
          if (L == 0) st_rlx(GA(x2msg, (s >> 3) * 2304 + 32 * cta + 4 * (s & 7)), v | (epoch & 0xffff));
          const int tok = 128 * ((win >> 3) & 15) + 2 * (16 * (win & 3) + ((win >> 7) & 15)) + ((win >> 2) & 1);
          if (L == 1 && s < 8) *reinterpret_cast<uint16_t*>(p.out + (uint32_t)(tok * 1152 + 16 * cta + 2 * s)) = (uint16_t)(v >> 16);
        }
      }
      TR(2, 9 + 10 * L);
      if (L == 0 && m < 14) {
        RELANE;
        const int c = min(2 * m + ((s >> 3) & 1), 26);
        const uint8_t* wsrc = GC(wpack, r * 12 * WSTAGE + (s >> 4) * 3456 + c * 128 + (s & 7) * 16);
        const int k0 = 8 * (s >> 4) + (s & 7);
        uint4 wv[5];
#pragma unroll
        for (int i = 0; i < 5; i++) wv[i] = ldcg128(wsrc + i * WSTAGE);
        uint32_t xv[9];
        {
          uint32_t n = 0;
          _Pragma("unroll 1") while (true) {
            uint32_t bad = 0;
#pragma unroll
            for (int i = 0; i < 9; i++) { xv[i] = ld_rlx(GA(x2msg, r * 2304 + 4 * k0) + 256 * i); bad |= xv[i] ^ epoch; }
            if (!__any_sync(0xffffffffu, bad & 0xffff)) break;
            spin_guard(n);
          }
        }
        TR(2, 10);
        float a[8], z = 0.f;
#pragma unroll
        for (int e = 0; e < 8; e++) a[e] = 0.f;
#pragma unroll
        for (int i = 0; i < 9; i++) {
          const float xx = bhi(xv[i]);
          const uint4 w4 = wv[i % 5];
          if (i < 4) wv[i] = ldcg128(wsrc + (i + 5) * WSTAGE);
          z = fmaf(xx, (lane & 8) ? xx : 1.f, z);
          a[0] = fmaf(xx, blo(w4.x), a[0]); a[1] = fmaf(xx, bhi(w4.x), a[1]);
          a[2] = fmaf(xx, blo(w4.y), a[2]); a[3] = fmaf(xx, bhi(w4.y), a[3]);
          a[4] = fmaf(xx, blo(w4.z), a[4]); a[5] = fmaf(xx, bhi(w4.z), a[5]);
          a[6] = fmaf(xx, blo(w4.w), a[6]); a[7] = fmaf(xx, bhi(w4.w), a[7]);
        }
        const bool b4 = lane & 4, b2 = lane & 2, b1 = lane & 1;
        float b[4];
#pragma unroll
        for (int e = 0; e < 4; e++) b[e] = (b4 ? a[4 + e] : a[e]) + shx(b4 ? a[e] : a[4 + e], 4);
        z += shx(z, 4);
        const float c0 = (b2 ? b[2] : b[0]) + shx(b2 ? b[0] : b[2], 2);
        const float c1 = (b2 ? b[3] : b[1]) + shx(b2 ? b[1] : b[3], 2);
        z += shx(z, 2);
        float d = (b1 ? c1 : c0) + shx(b1 ? c0 : c1, 1);
        z += shx(z, 1);
        d += shx(d, 16);
        z += shx(z, 16);
        if (lane < 16) stsf(sb + SM_GEMV + 16 * lane + 4 * sw, d);
        if ((lane & 23) == 0) stsf(sb + SM_GEMV + 256 + 2 * lane + 4 * sw, z);
        bar_sync(3);
        if (s < 16) {
          const uint4 pd = lds128(sb + SM_GEMV + 16 * s), p1 = lds128(sb + SM_GEMV + 256), p2 = lds128(sb + SM_GEMV + 272);
          const float acc = (__uint_as_float(pd.x) + __uint_as_float(pd.y)) + (__uint_as_float(pd.z) + __uint_as_float(pd.w));
          const float m1 = ((__uint_as_float(p1.x) + __uint_as_float(p1.y)) + (__uint_as_float(p1.z) + __uint_as_float(p1.w))) * (1.f / kD);
          const float m2 = ((__uint_as_float(p2.x) + __uint_as_float(p2.y)) + (__uint_as_float(p2.z) + __uint_as_float(p2.w))) * (1.f / kD);
          const float cs = blo(lds16(sb + SM_COLSUM + 32 * c + 2 * (s & 7))) + blo(lds16(sb + SM_COLSUM + 32 * c + 2 * (s & 7) + 16));
          const float v = (acc - m1 * cs) * rcp(ln_sd(fmaxf(m2 - m1 * m1, 0.f)));
          st_rlx(GA(fixmsg, 1024 * r + 64 * m + 4 * s), __float_as_uint(rbf(v)) | (epoch & 0xffff));
        }
        TR(2, 11);
      }
      {
        if (L == 0 && (int)((win >> 3) & 15) == m) {
          RELANE;
          if (s < 72) {
            const uint8_t* fp = s < 54 ? GA(fixmsg, 1024 * r + 16 * s) : GA(x2msg, r * (2304 + 288) + 16 * (s - 54));
            uint4 v;
            uint32_t n = 0;
            _Pragma("unroll 1") while (true) {
              v = ld_msg(fp);
              if ((((v.x ^ epoch) | (v.y ^ epoch) | (v.z ^ epoch) | (v.w ^ epoch)) & 0xffff) == 0) break;
              spin_guard(n);
            }
            sts128(sb + SM_FIXQ + 16 * s, v.x & 0xffff0000u, v.y & 0xffff0000u, v.z & 0xffff0000u, v.w & 0xffff0000u);
          }
          __syncwarp();
          if (lane == 0) mbar_arrive(sb + B_FIX);
          TR(2, 12);
        }
      }
    }
    if (s == 0) st_rlx(GA(epoch, 32 * cta), epoch);
  } else {
    asm volatile("setmaxnreg.inc.sync.aligned.u32 144;");
    const int w = warp >> 2, j = warp & 3;
    const uint32_t xfull = sb + B_XFULL + 32 * w, xempty = sb + B_XEMPTY + 32 * w, xring = sb + SM_X + w * 4 * XSTAGE;
    if (threadIdx.x >= 128 && threadIdx.x < 188) { sts128(sb + SM_COLSUM + 16 * (threadIdx.x - 128), 0, 0, 0, 0); fence_async_smem(); }
    {
      const uint32_t epoch = pack();
      asm volatile("bar.arrive 15, 384;" ::: "memory");
      TRW(24);
      if (!(ABL & 8)) {
        if (lane < 16) st_msg(GA(statsP, (2 * m + w) * 8192 + r * 1024 + (16 * j + lane) * 16), 0, 0, 0, 0);
        if (lane < 2) st_msg(GA(cand, (8 * lane + r) * 2048 + 16 * (8 * m + warp)), ~epoch, 0, 0, 0);
        __syncwarp();
      }
      TRW(11);
    }
    const uint32_t mw = 2 * m + w, cid = 8 * m + warp;
    const uint32_t rowc = sb + SM_ROWC + 64 * warp, rowm = sb + SM_ROWM + 128 * warp;
#pragma unroll 1
    for (int L = 0; L < 2; L++) {
      int ln0 = __shfl_sync(0xffffffffu, lane + L, lane) - L;
#define RELANE2 asm volatile("" : "+r"(ln0)); const int ln = ln0, g = ln >> 2, t = ln & 3; \
      const uint32_t pa = xring + j * 256 + (ln & 7) * 1028 + ((ln >> 3) & 1) * 128 + 96; (void)pa
      uint32_t P[27][2], H[20];
      const uint8_t* hl;
      auto halo = [&]() {
#pragma unroll
        for (int u = 0; u < 5; u++) {
          const uint4 v = ld_gen(hl + u * 512);
          H[4 * u] = v.x; H[4 * u + 1] = v.y; H[4 * u + 2] = v.z; H[4 * u + 3] = v.w;
        }
      };
      {
        RELANE2;
        const uint32_t epoch = __shfl_sync(0xffffffffu, lds32(sb + SM_EP), 0);
        int selrow = -1;
        bool tgtwg = false;
        float d[108];
        uint32_t am[4];
        auto split_mean = [&](float m0, float m1) {
          const uint32_t h0 = packbf(m0, m0), h1 = packbf(m1, m1);
          const float l0 = m0 - bhi(h0), l1 = m1 - bhi(h1);
          am[0] = t ? 0u : h0; am[1] = t ? 0u : h1; am[2] = t ? 0u : packbf(l0, l0); am[3] = t ? 0u : packbf(l1, l1);
        };
        const uint32_t cdesc = mkdesc(sbd + SM_COLSUM, 0);
        am[0] = am[1] = am[2] = am[3] = 0;
        if (L == 1) split_mean(ldsf(rowm + 8 * g), ldsf(rowm + 8 * g + 64));
        asm volatile("wgmma.fence.sync.aligned;" ::: "memory");
        wgmma_n144_set(d + 36, am, cdesc + 18);
        wgmma_n72_set(d, am, cdesc);
        asm volatile("wgmma.commit_group.sync.aligned;" ::: "memory");
        const uint32_t adesc = mkdesc(sbd + SM_X + w * 4 * XSTAGE, 1024), ahi = L == 0 ? 0x40000040u : 8u, astep = L == 0 ? 2 : 128;
        const uint32_t bdesc = mkdesc(sbd + SM_W, 3456);
        const uint8_t* xsrc = GC(act, ACT + mw * 73728);
        mbar_wait2(sb + B_WFULL, L, xfull, 0);
        if (L == 1) check_stage(probe_stage(pa), xring, xsrc);
        TRW(0 + 12 * L);
#pragma unroll 1
        for (int s = 0; s < 7; s++) {
          TRQ(s + 9 * L);
          const uint32_t da = adesc + (s & 3) * (XSTAGE >> 4), db = bdesc + (s & 3) * (WSTAGE >> 4);
          const uint32_t nx = (s + 1) & 3, px = ((s + 1) >> 2) & 1;
          asm volatile("wgmma.fence.sync.aligned;" ::: "memory");
          wgmma_n72(d, da, ahi, db);
          wgmma_n144(d + 36, da, ahi, db + (1152 >> 4));
          wgmma_n72(d, da + astep, ahi, db + (6912 >> 4));
          asm volatile("wgmma.commit_group.sync.aligned;" ::: "memory");
          asm volatile("wgmma.wait_group.sync.aligned 1;" ::: "memory");
          if (s > 0 && ln == 0) {
            mbar_arrive_pair(sb + B_WEMPTY + 8 * ((s - 1) & 3));
            mbar_arrive(xempty + 8 * ((s - 1) & 3));
          }
          wgmma_n144(d + 36, da + astep, ahi, db + ((6912 + 1152) >> 4));
          wgmma_n72(d, da + 2 * astep, ahi, db + 2 * (6912 >> 4));
          uint32_t pv;
          const uint32_t dsc[6] = {da + 2 * astep, db + ((2 * 6912 + 1152) >> 4), da + 3 * astep, db + 3 * (6912 >> 4),
                                   da + 3 * astep, db + ((3 * 6912 + 1152) >> 4)};
          const uint32_t bar[4] = {sb + B_WFULL + 8 * nx, px ^ L, xfull + 8 * nx, px}, adr = pa + nx * XSTAGE;
          q_tail(d, &pv, ahi, dsc, bar, &adr);
          if (L == 1) check_stage(pv, xring + nx * XSTAGE, xsrc + (s + 1) * XSTAGE);
          if (s == 1 && j == 3) {
            uint8_t* hp = GC(halo, (4 * cta + 2 * L + w) * 2560 + ln * 16);
#pragma unroll
            for (int u = 0; u < 5; u++) st_msg(hp + u * 512, 0, 0, 0, 0);
          }
        }
        TRQ(7 + 9 * L);
        const uint32_t da7 = adesc + 3 * (XSTAGE >> 4), db7 = bdesc + 3 * (WSTAGE >> 4);
        asm volatile("wgmma.fence.sync.aligned;" ::: "memory");
        wgmma_n144(d + 36, da7, ahi, db7 + (1152 >> 4));
        wgmma_n144(d + 36, da7 + astep, ahi, db7 + ((6912 + 1152) >> 4));
        asm volatile("wgmma.commit_group.sync.aligned;" ::: "memory");
        asm volatile("wgmma.wait_group.sync.aligned 1;" ::: "memory");
        if (ln == 0) { mbar_arrive_pair(sb + B_WEMPTY + 16); mbar_arrive(xempty + 16); }
        {
          uint32_t v[2];
          const uint32_t dsc[4] = {da7 + 2 * astep, db7 + ((2 * 6912 + 1152) >> 4), da7 + 3 * astep, db7 + ((3 * 6912 + 1152) >> 4)};
          const uint32_t bar[6] = {sb + B_WFULL, (uint32_t)L, xfull, 0, sb + (L ? B_IDX : B_COLSUM), 0}, adr[2] = {pa, sb + SM_SEL + (ln >> 5)};
          kv_tail(d, v, ahi, dsc, bar, adr);
          if (L == 1) {
            if ((v[1] & 127) == cid) selrow = v[1] >> 7;
            tgtwg = ((v[1] & 127) >> 2) == (cid >> 2);
            check_stage(v[0], xring, xsrc + 8 * XSTAGE);
          }
        }
        TRQ(8 + 9 * L);
        const float m0 = ldsf(rowm + 8 * g), m1 = ldsf(rowm + 8 * g + 64);
        {
          uint32_t dsc[8];
#pragma unroll
          for (int kk = 0; kk < 4; kk++) { dsc[2 * kk] = adesc + kk * astep; dsc[2 * kk + 1] = bdesc + ((kk * 6912 + 1152) >> 4); }
          const uint32_t bar[2] = {xempty + 16, 1};
          asm volatile("wgmma.fence.sync.aligned;" ::: "memory");
          kv_last(d, nullptr, ahi, dsc, bar, nullptr);
        }
        if (L == 0) {
          split_mean(m0, m1);
          asm volatile("wgmma.fence.sync.aligned;" ::: "memory");
          wgmma_n144_add(d + 36, am, cdesc + 18);
          wgmma_n72_add(d, am, cdesc);
          asm volatile("wgmma.commit_group.sync.aligned;" ::: "memory");
        }
        auto qstep = [&](int k) {
          wgmma_n72(d, (k < 4 ? da7 : adesc) + (k & 3) * astep, ahi, (k < 4 ? db7 : bdesc) + (k & 3) * (6912 >> 4));
        };
#pragma unroll
        for (int k = 0; k < QPRE; k++) qstep(k);
        asm volatile("wgmma.commit_group.sync.aligned;" ::: "memory");
        if (tgtwg) {
          asm volatile("wgmma.fence.sync.aligned;" ::: "memory");
#pragma unroll
          for (int k = QPRE; k < 8; k++) qstep(k);
          asm volatile("wgmma.commit_group.sync.aligned;" ::: "memory");
        }
        asm volatile("wgmma.wait_group.sync.aligned 1;" ::: "memory");
#pragma unroll
        for (int i = 36; i < 108; i++) asm volatile("" : "+f"(d[i])::"memory");
        if (selrow >= 0) {
          mbar_wait(sb + B_FIX, 0);
          stsf(rowc + 4 * selrow, 1.f);
#pragma unroll
          for (int q = 18; q < 54; q++) lds64f_if(selrow == g + 8 * (q & 1), d[2 * q], d[2 * q + 1], sb + SM_FIXQ + 32 * (q >> 1) + 8 * t);
          __syncwarp();
        }
#pragma unroll
        for (int q = 26; q >= 9; q--) { P[q][1] = packbf(d[4 * q + 2], d[4 * q + 3]); P[q][0] = packbf(d[4 * q], d[4 * q + 1]); }
#pragma unroll
        for (int q = 26; q >= 18; q--) P[q][1] = movm(P[q][1]);
        const uint2 ck1 = lds64(rowc + 32 + 8 * t);
        uint8_t* ha = (j < 3 ? smem_raw + (SM_X + (4 * w + 2) * XSTAGE + j * 2560) : GC(halo, (4 * cta + 2 * L + w) * 2560)) + ln * 16;
        P[9][1] = nz(P[9][1]); P[13][1] = nz(P[13][1]); P[17][1] = nz(P[17][1]);
        st_gen(ha, P[9][1], P[10][1], P[11][1], P[12][1]);
        st_gen(ha + 512, P[13][1], P[14][1], P[15][1], P[16][1]);
        st_gen(ha + 2048, nz(ck1.y), P[24][1], P[25][1], P[26][1]);
        st_gen(ha + 1536, nz(ck1.x), P[21][1], P[22][1], P[23][1]);
        st_gen(ha + 1024, P[17][1], P[18][1], P[19][1], P[20][1]);
#pragma unroll
        for (int q = 9; q < 27; q++) asm volatile("" : "+r"(P[q][0]));
        if (j < 3) asm volatile("bar.arrive %0, 64;" ::"r"(5 + warp) : "memory");
        mbar_wait(sb + B_EP, 0);
#pragma unroll
        for (int q = 26; q >= 18; q--) P[q][0] = movm(P[q][0]);
        if (!tgtwg)
        {
          asm volatile("wgmma.fence.sync.aligned;" ::: "memory");
#pragma unroll
          for (int k = QPRE; k < 8; k++) qstep(k);
          asm volatile("wgmma.commit_group.sync.aligned;" ::: "memory");
        }
        hl = (j > 0 || m == 0 ? smem_raw + (SM_X + (4 * w + 2) * XSTAGE + max(j - 1, 0) * 2560)
                              : GC(halo, (4 * (cta - 8) + 2 * L + w) * 2560)) + ln * 16;
        if (j > 0) asm volatile("bar.sync %0, 64;" ::"r"(4 + warp) : "memory");
        asm volatile("wgmma.wait_group.sync.aligned 0;" ::: "memory");
#pragma unroll
        for (int i = 0; i < 36; i++) asm volatile("" : "+f"(d[i])::"memory");
        TRW(1 + 12 * L);
        if (selrow >= 0) {
#pragma unroll
          for (int q = 0; q < 18; q++) lds64f_if(selrow == g + 8 * (q & 1), d[2 * q], d[2 * q + 1], sb + SM_FIXQ + 32 * (q >> 1) + 8 * t);
        }
#pragma unroll
        for (int q = 0; q < 9; q++) { P[q][0] = packbf(d[4 * q], d[4 * q + 1]); P[q][1] = packbf(d[4 * q + 2], d[4 * q + 3]); }
      }
      TRW(2 + 12 * L);
      const uint32_t epoch = lds32(sb + SM_EP);
      uint8_t* fptr = GA(flagX, 128 * mw + 16 * r + 4 * j + ln0);
      {
        RELANE2;
        halo();
        if (ln == 0) { mbar_arrive(xempty + 24); mbar_arrive(xempty); }
        const bool le0 = 2 * t <= g, le1 = 2 * t + 1 <= g;
        uint32_t A0[4][2], A2[4][2];
        float s0[4][4], s1[4][4];
#pragma unroll
        for (int h = 0; h < 4; h++) {
          const int T = 2 * h;
          A0[h][0] = t >= h ? P[T][0] : 0u; A0[h][1] = t >= h ? P[T][1] : 0u;
          A2[h][0] = t <= h ? P[T + 2][0] : 0u; A2[h][1] = t <= h ? P[T + 2][1] : 0u;
          mma8z(s0[h], A2[h][0], A2[h][1], P[9 + T + 2][0]);
          mma8z(s1[h], A2[h][0], A2[h][1], P[9 + T + 2][1]);
        }
#pragma unroll
        for (int h = 0; h < 4; h++) {
          const int T = 2 * h;
          mma16(s0[h], A0[h][0], A0[h][1], P[T + 1][0], P[T + 1][1], P[9 + T][0], P[9 + T + 1][0]);
          mma16(s1[h], A0[h][0], A0[h][1], P[T + 1][0], P[T + 1][1], P[9 + T][1], P[9 + T + 1][1]);
        }
        const uint2 ck0 = lds64(rowc + 8 * t), ck1 = lds64(rowc + 32 + 8 * t);
        const float sc = 0.23570226039551584f * 1.4426950408889634f;
        const float cq0 = ldsf(rowc + 4 * g) * sc, cq1 = ldsf(rowc + 32 + 4 * g) * sc;
        uint8_t* ob = GC(act, 2 * L * ACT + mw * 73728 + r * 9216 + j * 256 + ln * 4);
        float l[2][4][2], ks[2][2], mx[2][4];
        ks[1][0] = __uint_as_float(le0 ? ck1.x : ck0.x); ks[1][1] = __uint_as_float(le1 ? ck1.y : ck0.y);
#pragma unroll
        for (int h = 0; h < 4; h++) {
          l[1][h][0] = (le0 ? s1[h][2] : s0[h][2]) * (cq1 * ks[1][0]); l[1][h][1] = (le1 ? s1[h][3] : s0[h][3]) * (cq1 * ks[1][1]);
          asm volatile("" : "+f"(l[1][h][0]), "+f"(l[1][h][1]));
        }
        asm volatile("" : "+l"(fptr), "+l"(ob));
        {
          uint32_t n = 0;
          _Pragma("unroll 1") while (__any_sync(0xffffffffu, min(min(min(H[0], H[4]), min(H[8], H[12])), H[16]) == 0)) {
            halo();
            spin_guard(n);
          }
        }
        if (ln == 0) mbar_arrive_pair(sb + B_WEMPTY + 24);
        TRW(3 + 12 * L);
        {
          float sm[4][4];
#pragma unroll
          for (int h = 0; h < 4; h++) mma8z(sm[h], A2[h][0], A2[h][1], H[2 * h + 2]);
#pragma unroll
          for (int h = 0; h < 4; h++) mma16(sm[h], A0[h][0], A0[h][1], P[2 * h + 1][0], P[2 * h + 1][1], H[2 * h], H[2 * h + 1]);
          ks[0][0] = __uint_as_float(le0 ? ck0.x : H[12]); ks[0][1] = __uint_as_float(le1 ? ck0.y : H[16]);
          const bool nohalo = (m == 0 && j == 0);
          const float b0 = (nohalo && !le0) ? -INFINITY : 0.f, b1 = (nohalo && !le1) ? -INFINITY : 0.f;
#pragma unroll
          for (int h = 0; h < 4; h++) {
            l[0][h][0] = fmaf(le0 ? s0[h][0] : sm[h][0], cq0 * ks[0][0], b0);
            l[0][h][1] = fmaf(le1 ? s0[h][1] : sm[h][1], cq0 * ks[0][1], b1);
          }
        }
#pragma unroll
        for (int i = 7; i >= 0; i--) mx[i >> 2][i & 3] = fmaxf(l[i >> 2][i & 3][0], l[i >> 2][i & 3][1]);
#pragma unroll
        for (int x = 1; x <= 2; x <<= 1) {
#pragma unroll
          for (int i = 7; i >= 0; i--) mx[i >> 2][i & 3] = fmaxf(mx[i >> 2][i & 3], shx(mx[i >> 2][i & 3], x));
        }
        const uint32_t mle = (le0 ? 0xffffu : 0u) | (le1 ? 0xffff0000u : 0u);
        uint32_t pp[2][4], pc[2][4];
#pragma unroll
        for (int i = 3; i >= 0; i--) {
          const int e = i >> 1, h = 2 * (i & 1);
          const float p0 = ex2(l[e][h][0] - mx[e][h]), p1 = ex2(l[e][h][1] - mx[e][h]);
          const float p2 = ex2(l[e][h + 1][0] - mx[e][h + 1]), p3 = ex2(l[e][h + 1][1] - mx[e][h + 1]);
          float sum[4];
          mma8z(sum, packbf(p0, p1), packbf(p2, p3), 0x3f803f80u);
          const float inv = rcp(sum[0] * sum[2]);
          const float ia = inv * sum[2], ib = inv * sum[0];
          const uint32_t u0 = packbf(p0 * ks[e][0] * ia, p1 * ks[e][1] * ia), u1 = packbf(p2 * ks[e][0] * ib, p3 * ks[e][1] * ib);
          pp[e][h] = u0 & ~mle; pc[e][h] = u0 & mle; pp[e][h + 1] = u1 & ~mle; pc[e][h + 1] = u1 & mle;
        }
#pragma unroll
        for (int e = 1; e >= 0; e--) {
#pragma unroll
          for (int q = 8; q >= 0; q--) {
            const int h = q < 4 ? 0 : q == 4 ? 1 : 2;
            float a[4];
            mma16z(a, pp[e][h], pp[e][h + 1], pc[e][h], pc[e][h + 1], e ? P[18 + q][0] : H[9 + q + q / 3], P[18 + q][e]);
            const bool second = q == 2 * h + 2 ? t > h : q > 2 * h + 2;
            st_rlx(ob + q * 1024 + e * 128, nz(packbf(second ? a[2] : a[0], second ? a[3] : a[1])));
          }
        }
        if (ln == 0) st_rlx(fptr, epoch * 4 + 1 + 2 * L);
        TRW(4 + 12 * L);
      }
      RELANE2;
      float d[36];
      uint32_t WB[9];
      {
        uint32_t R[10][2];
        const uint32_t qs = L == 0 ? 16 : 1024, ra = xring + (16 * j + (ln & 15)) * (L == 0 ? 144 : 16) + (ln >> 4) * qs;
        mbar_wait(sb + B_RES + 8 * w, L);
#pragma unroll
        for (int q = 0; q < 10; q += 2) ldsm4(&R[q][0], ra + q * qs);
        fence_async_smem();
        __syncwarp();
        if (ln == 0) mbar_arrive(sb + B_RC + 8 * w);
#pragma unroll
        for (int q = 0; q < 9; q++) WB[q] = ldg32(p.wr + (uint32_t)(r * 144 + 4 * t) + 16 * q);
#pragma unroll
        for (int h = 0; h < 2; h++) {
          const uint2 mf = lds64(rowm + 8 * g + 64 * h);
          const float f = __uint_as_float(mf.y), k = -__uint_as_float(mf.x) * f;
#pragma unroll
          for (int q = 0; q < 9; q++) { d[4 * q + 2 * h] = fmaf(blo(R[q][h]), f, k); d[4 * q + 2 * h + 1] = fmaf(bhi(R[q][h]), f, k); }
        }
        const uint32_t sel = lds32(sb + SM_SEL);
        if (L == 1 && (sel & 127) == cid) {
          const int selrow = sel >> 7;
#pragma unroll
          for (int q = 0; q < 18; q++) lds64f_if(selrow == g + 8 * (q & 1), d[2 * q], d[2 * q + 1], sb + SM_X2R + 32 * (q >> 1) + 8 * t);
        }
#pragma unroll
        for (int q = 0; q < 9; q++) WB[q] = (g & 1) ? WB[q] : 0x3f803f80u;
        __syncwarp();
      }
      uint8_t* xb = GC(act, ACT + mw * 73728 + r * 9216 + j * 256 + ln * 4);
      uint8_t* sst = GA(statsP, mw * 8192 + r * 1024 + (16 * j + g + 8 * t) * 16);
      const uint8_t* sld = GA(statsP, mw * 8192 + (ln >> 4) * 4096 + (16 * j + (ln & 15)) * 16);
      uint8_t* cptr = GA(cand, (8 * L + r) * 2048 + 16 * cid);
      uint8_t* crow = GC(candrow, (128 * L + cid) * 1152 + 144 * r + 4 * t);
      uint32_t tag = epoch * 2 + L, ktag = ((ln & 15) << 7) | (epoch & 0x7f);
      float wsum = ldsf(sb + SM_WSUM);
      float pivot = __uint_as_float(ld_rlx(GA(stats0, 16 * (16 * cid + (ln & 15)) + 4))) + (L ? ldsf(rowm + 8 * (ln & 15)) : 0.f);
      asm volatile("" : "+l"(xb), "+l"(sst), "+l"(sld), "+l"(cptr), "+l"(crow), "+r"(tag), "+r"(ktag), "+f"(wsum), "+f"(pivot));
      TRW(5 + 12 * L);
      {
        constexpr uint32_t bdesc = mkdesc(sbd + SM_W + WSTAGE, 1152);
        uint32_t adesc[3];
#pragma unroll
        for (int i = 0; i < 3; i++) adesc[i] = __shfl_sync(0xffffffffu, mkdesc(sbd + SM_X + w * 4 * XSTAGE, 1024) + (ln >> 2), i);
#pragma unroll
        for (int i = 0; i < 36; i++) asm volatile("" : "+f"(d[i])::"memory");
        const bool lead = warp == 0 && ln == 0;
        const uint8_t* osrc = GC(act, 2 * L * ACT + mw * 73728);
        mbar_wait2(sb + B_WFULL + 8, L, xfull, 1);
        check_stage(probe_stage(pa), xring, osrc);
        TRW(6 + 12 * L);
#pragma unroll
        for (int s = 0; s < 9; s++) {
          TRQ(18 + s);
          const uint32_t da = s == 4 ? adesc[1] - ((SM_X - SM_W) >> 4) - w * 3 * (XSTAGE >> 4) : adesc[s >> 2] + (s < 4 ? s : s - 5) * (XSTAGE >> 4);
          const uint32_t db = bdesc + s * (9216 >> 4);
          const int n1 = s + 1, nx = n1 < 4 ? n1 : n1 - 5;
          const uint32_t xoff = n1 == 4 ? SM_W - SM_X - w * 3 * XSTAGE : nx * XSTAGE;
          asm volatile("wgmma.fence.sync.aligned;" ::: "memory");
          wgmma_n72(d, da, 8u, db);
          wgmma_n72(d, da + 128, 8u, db + (2304 >> 4));
          asm volatile("wgmma.commit_group.sync.aligned;" ::: "memory");
          if (s > 0) {
            asm volatile("wgmma.wait_group.sync.aligned 1;" ::: "memory");
            if (ln == 0) {
              if (s != 5) mbar_arrive(xempty + 8 * (s < 5 ? s - 1 : s - 6));
              if (L == 0) {
                if (s == WR0) mbar_arrive_pair(sb + B_WEMPTY);
                if (s == WR1) mbar_arrive_pair(sb + B_WEMPTY + 8);
                if (s == WR2) mbar_arrive_pair(sb + B_WEMPTY + 16);
              }
            }
          }
          const uint32_t xbar = n1 == 4 ? sb + B_XE + 8 * w : xfull + 8 * nx, px = n1 == 4 ? L : n1 >= 6;
          if ((s == 0 || s == 8) && lead) mbar_arrive(sb + (s ? B_EPI : B_OS));
          if (s < 8) {
            uint32_t pv;
            const uint32_t dsc[4] = {da + 256, db + (4608 >> 4), da + 384, db + (6912 >> 4)};
            const uint32_t bar[4] = {sb + B_WFULL + 8 + 8 * ((s + 1) / 3), (uint32_t)L, xbar, px}, adr = pa + xoff;
            o_tail2(d, &pv, 8u, dsc, bar, &adr);
            check_stage(pv, xring + xoff, osrc + (s + 1) * XSTAGE);
          } else {
            wgmma_n72(d, da + 256, 8u, db + (4608 >> 4));
            wgmma_n72(d, da + 384, 8u, db + (6912 >> 4));
            asm volatile("wgmma.commit_group.sync.aligned;" ::: "memory");
          }
        }
        asm volatile("wgmma.wait_group.sync.aligned 0;" ::: "memory");
#pragma unroll
        for (int i = 0; i < 36; i++) asm volatile("" : "+f"(d[i])::"memory");
        mbar_wait(xfull, 1);
        if (ln == 0) { if (L == 0) mbar_arrive_pair(sb + B_WEMPTY + 24); mbar_arrive(xempty + 24); mbar_arrive(xempty); }
      }
      TRW(7 + 12 * L);
      uint32_t R[9][2];
#pragma unroll
      for (int q = 0; q < 9; q++) { R[q][0] = packbf(d[4 * q], d[4 * q + 1]); R[q][1] = packbf(d[4 * q + 2], d[4 * q + 3]); }
      {
        float sa[4], sc[4];
        mma16z(sa, R[0][0], R[0][1], R[1][0], R[1][1], WB[0], WB[1]);
        mma16z(sc, R[2][0], R[2][1], R[3][0], R[3][1], WB[2], WB[3]);
        mma16(sa, R[4][0], R[4][1], R[5][0], R[5][1], WB[4], WB[5]);
        mma16(sc, R[6][0], R[6][1], R[7][0], R[7][1], WB[6], WB[7]);
        mma8(sa, R[8][0], R[8][1], WB[8]);
        float qq[4] = {0.f, 0.f, 0.f, 0.f};
#pragma unroll
        for (int q = 0; q < 36; q++) qq[q & 3] = fmaf(d[q], d[q], qq[q & 3]);
        const float qa = qq[0] + qq[1], qc = qq[2] + qq[3];
        const bool odd = t & 1;
        float q2 = (odd ? qc : qa) + shx(odd ? qa : qc, 1);
        q2 += shx(q2, 2);
        if (t < 2)
          st_msg(sst, __float_as_uint(odd ? sa[2] + sc[2] : sa[0] + sc[0]), __float_as_uint(q2),
                 __float_as_uint(odd ? sa[3] + sc[3] : sa[1] + sc[1]), tag);
      }
      if (L == 0) {
#pragma unroll
        for (int q = 0; q < 9; q++) { st_rlx(xb + q * 1024, nz(R[q][0])); st_rlx(xb + q * 1024 + 128, nz(R[q][1])); }
        if (ln == 0) st_rlx(fptr, epoch * 4 + 2);
      }
      TRW(8 + 12 * L);
      {
        uint4 u[4];
        uint32_t n = 0;
        _Pragma("unroll 1") while (true) {
#pragma unroll
          for (int i = 0; i < 4; i++) u[i] = ld_msg(sld + 1024 * i);
          if (!__any_sync(0xffffffffu, (u[0].w ^ tag) | (u[1].w ^ tag) | (u[2].w ^ tag) | (u[3].w ^ tag))) break;
          spin_guard(n);
        }
        TRW(9 + 12 * L);
        float s1 = (__uint_as_float(u[0].x) + __uint_as_float(u[1].x)) + (__uint_as_float(u[2].x) + __uint_as_float(u[3].x));
        float s2 = (__uint_as_float(u[0].y) + __uint_as_float(u[1].y)) + (__uint_as_float(u[2].y) + __uint_as_float(u[3].y));
        float s3 = (__uint_as_float(u[0].z) + __uint_as_float(u[1].z)) + (__uint_as_float(u[2].z) + __uint_as_float(u[3].z));
        s1 += shx(s1, 16); s2 += shx(s2, 16); s3 += shx(s3, 16);
        const float mu = s1 * (1.f / kD);
        const float var = fmaxf(fmaf(s2, 1.f / kD, -mu * mu), 0.f);
        const float sd = ln_sd(var), rho = rcp(sd);
        const float rr = (s3 - mu * wsum) * rho;
        const int key = __reduce_max_sync(0xffffffffu, (int)((fkey(rr) & ~0x7ff) | ktag));
        const int best = (key >> 7) & 15;
        if (ln == best) st_msg(cptr, key, __float_as_uint(rbf(sigmoidf(rbf(rr)))), __float_as_uint(1.f + sd), __float_as_uint(L ? pivot + mu : 0.f));
        const float rb = __shfl_sync(0xffffffffu, rho, best), nb = __shfl_sync(0xffffffffu, -mu * rho, best);
        if ((best & 7) == g) {
          const bool hi = best >= 8;
#pragma unroll
          for (int q = 0; q < 9; q++)
            st_rlx(crow + (((q ^ r) & 1) * (4 - 8 * (t & 1))) + 16 * q, nz(packbf(fmaf(hi ? d[4 * q + 2] : d[4 * q], rb, nb), fmaf(hi ? d[4 * q + 3] : d[4 * q + 1], rb, nb))));
        }
        const float f = 1.f + rho, k = pivot - mu * rho;
        sts32(rowc + 4 * (ln & 15), __float_as_uint(f * rcp(ln_sd(var * f * f))));
        sts64(rowm + 8 * (ln & 15), __float_as_uint(L == 0 ? mu : k), __float_as_uint(f));
        __syncwarp();
      }
      TRW(10 + 12 * L);
      if (L == 1) {
#pragma unroll
        for (int h = 0; h < 2; h++) {
          const uint2 kf = lds64(rowm + 8 * g + 64 * h);
          const float k = __uint_as_float(kf.x), f = __uint_as_float(kf.y);
#pragma unroll
          for (int q = 0; q < 9; q++) R[q][h] = packbf(fmaf(d[4 * q + 2 * h], f, k), fmaf(d[4 * q + 2 * h + 1], f, k));
        }
        mbar_wait(xempty + 16, 1);
        const uint32_t st = xring + XSTAGE + (16 * j + (ln & 15)) * 144;
#pragma unroll
        for (int q = 0; q < 8; q += 2) stsm4(st + (ln >> 4) * 16 + q * 16, R[q][0], R[q][1], R[q + 1][0], R[q + 1][1]);
        stsm2(st + 128, R[8][0], R[8][1]);
        fence_async_smem();
        __syncwarp();
        mbar_wait(sb + B_IDX + 8, 0);
        const uint32_t sel = lds32(sb + SM_SEL + 4);
        if ((sel & 127) != cid) {
          if (elect())
            asm volatile("cp.async.bulk.tensor.3d.global.shared::cta.bulk_group [%0, {%2,%3,%4}], [%1];" ::"l"(&tm.out),
                         "r"(xring + XSTAGE + 16 * j * 144), "r"(72 * r), "r"(w), "r"(64 * m + 16 * j) : "memory");
        } else if (ln < 16 && ln != (sel >> 7)) {
          bulk_s2g(p.out + (uint32_t)((128 * m + 2 * (16 * j + ln) + w) * 1152 + r * 144), st, 144);
        }
        asm volatile("cp.async.bulk.commit_group;" ::: "memory");
        asm volatile("cp.async.bulk.wait_group.read 0;" ::: "memory");
        TRW(11 + 12 * L);
        TRDUMP(w);
      }
    }
  }
}

typedef CUresult (*EncodeFn)(CUtensorMap*, CUtensorMapDataType, cuuint32_t, void*, const cuuint64_t*, const cuuint64_t*,
                             const cuuint32_t*, const cuuint32_t*, CUtensorMapInterleave, CUtensorMapSwizzle,
                             CUtensorMapL2promotion, CUtensorMapFloatOOBfill);

}

extern "C" void kernel_launch(void* const* d_in, const int* in_sizes, int n_in, void* d_out, int out_size) {
  static EncodeFn enc = nullptr;
  static Scratch* scratch = nullptr;
  static int nsm = 0;
  if (!enc) {
    cudaDriverEntryPointQueryResult q;
    cudaGetDriverEntryPoint("cuTensorMapEncodeTiled", (void**)&enc, cudaEnableDefault, &q);
    int dev = 0;
    cudaGetDevice(&dev);
    cudaDeviceGetAttribute(&nsm, cudaDevAttrMultiProcessorCount, dev);
    cudaGetSymbolAddress((void**)&scratch, g_s);
    cudaFuncSetAttribute(fused_kernel, cudaFuncAttributeMaxDynamicSharedMemorySize, 232448);
  }
  Maps tm;
  auto mk = [&](CUtensorMap* t, void* ptr, int rank, const cuuint64_t* dims, const cuuint64_t* strides, const cuuint32_t* box,
                CUtensorMapSwizzle sw, CUtensorMapL2promotion pr) {
    const cuuint32_t es[4] = {1, 1, 1, 1};
    enc(t, CU_TENSOR_MAP_DATA_TYPE_BFLOAT16, rank, ptr, dims, strides, box, es, CU_TENSOR_MAP_INTERLEAVE_NONE, sw, pr,
        CU_TENSOR_MAP_FLOAT_OOB_FILL_NONE);
  };
  { const cuuint64_t d[3] = {576, 2, 1024}, st[2] = {1152, 2304}; const cuuint32_t bx[3] = {64, 1, 64};
    mk(&tm.x, d_in[0], 3, d, st, bx, CU_TENSOR_MAP_SWIZZLE_128B, CU_TENSOR_MAP_L2_PROMOTION_NONE);
    const cuuint32_t br[3] = {72, 1, 64};
    mk(&tm.xr, d_in[0], 3, d, st, br, CU_TENSOR_MAP_SWIZZLE_NONE, CU_TENSOR_MAP_L2_PROMOTION_NONE);
    const cuuint32_t bo[3] = {72, 1, 16};
    mk(&tm.out, d_out, 3, d, st, bo, CU_TENSOR_MAP_SWIZZLE_NONE, CU_TENSOR_MAP_L2_PROMOTION_NONE); }
  { const cuuint64_t d[3] = {576, 576, 3}, st[2] = {3456, 1152}; const cuuint32_t bx[3] = {72, 8, 2};
    mk(&tm.wq, d_in[1], 3, d, st, bx, CU_TENSOR_MAP_SWIZZLE_NONE, CU_TENSOR_MAP_L2_PROMOTION_NONE); }
  { const cuuint64_t d[2] = {576, 576}, st[1] = {1152}; const cuuint32_t bx[2] = {72, 16};
    mk(&tm.wo, d_in[2], 2, d, st, bx, CU_TENSOR_MAP_SWIZZLE_NONE, CU_TENSOR_MAP_L2_PROMOTION_NONE); }
  { const cuuint64_t d[2] = {4608, 576}, st[1] = {9216}; const cuuint32_t bx[2] = {48, 64};
    mk(&tm.wg, d_in[5], 2, d, st, bx, CU_TENSOR_MAP_SWIZZLE_128B, CU_TENSOR_MAP_L2_PROMOTION_L2_128B);
    mk(&tm.wu, d_in[6], 2, d, st, bx, CU_TENSOR_MAP_SWIZZLE_128B, CU_TENSOR_MAP_L2_PROMOTION_L2_128B); }
  Params p;
  p.x = (const uint8_t*)d_in[0]; p.wqkv = (const uint8_t*)d_in[1]; p.wo = (const uint8_t*)d_in[2];
  p.wr = (const uint8_t*)d_in[4]; p.wg = (const uint8_t*)d_in[5]; p.wu = (const uint8_t*)d_in[6]; p.wd = (const uint8_t*)d_in[7];
  p.out = (uint8_t*)d_out;
  p.g = scratch;
  fused_kernel<<<nsm == 132 ? 132 : 128, 512, 232448>>>(p, tm);
}
```
